```python
import torch

def _softmax(x, axis=-1):
    return torch.softmax(x, dim=axis)
def _gelu(x):
    return torch.nn.functional.gelu(x, approximate="tanh")
def _silu(x):
    return torch.nn.functional.silu(x)
def _sigmoid(x):
    return torch.sigmoid(x)
def _layernorm(x, axis=-1, eps=1e-5):
    m = x.mean(dim=axis, keepdim=True)
    v = x.var(dim=axis, keepdim=True, unbiased=False)
    return (x - m) / torch.sqrt(v + eps)
def _scatter_add(tgt, idx, src, axis=0):
    return tgt.clone().index_add_(axis, idx, src)
def _segment_sum(src, seg, n):
    out = torch.zeros((n,) + src.shape[1:], dtype=src.dtype)
    return out.index_add_(0, seg, src)
def _pad(x, pw):
    flat = tuple(v for pair in reversed(pw) for v in pair)
    return torch.nn.functional.pad(x, flat)

kernel_name = 'gated_mix__spectral_gfnet__swiglu_ffn__prompt'

def setup_inputs():

    _w = (lambda a: (lambda t: t.to(torch.bfloat16) if t.is_floating_point() else t)(torch.as_tensor(a)))
    def _A_setup():
        B, S, D = 1, 2048, 448
        Df = D // 2 + 1
        return {
            "x": _w((lambda *s: torch.randn(*s, dtype=torch.bfloat16) * 0.05)(B, S, D)),
            "w_r": _w((lambda *s: torch.randn(*s, dtype=torch.bfloat16) * 0.8)(S, Df) * 0.02),
            "w_i": _w((lambda *s: torch.randn(*s, dtype=torch.bfloat16) * 0.8)(S, Df) * 0.02),
        }
    _A_in = _A_setup()

    def _B_setup():
        B, S, D, F = 1, 2048, 448, 1792
        return {
            "x": _w((lambda *s: torch.randn(*s, dtype=torch.bfloat16) * 0.05)(B, S, D)),
            "w_gate": _w((lambda *s: torch.randn(*s, dtype=torch.bfloat16) * 0.05)(D, F)),
            "w_up": _w((lambda *s: torch.randn(*s, dtype=torch.bfloat16) * 0.05)(D, F)),
            "w_down": _w((lambda *s: torch.randn(*s, dtype=torch.bfloat16) * 0.05)(F, D)),
        }
    _B_in = _B_setup()

    return {
        "A_x": _A_in["x"],
        "A_w_r": _A_in["w_r"],
        "A_w_i": _A_in["w_i"],
        "B_x": _B_in["x"],
        "B_w_gate": _B_in["w_gate"],
        "B_w_up": _B_in["w_up"],
        "B_w_down": _B_in["w_down"],
        "gate_w": _w((lambda *s: torch.randn(*s, dtype=torch.bfloat16) * 0.05)(448) * 16.0),
    }

def reference(A_x, A_w_r, A_w_i, B_x, B_w_gate, B_w_up, B_w_down, gate_w):
    def _A_ref(x, w_r, w_i):
        B, S, D = x.shape
        X = (lambda x, axes=(-2,-1): torch.fft.rfft2(x.float(), dim=axes))(x, axes=(-2, -1))
        W = w_r + 1j * w_i
        X = X * W
        y = (lambda x, s, axes=(-2,-1): torch.fft.irfft2(x, s=s, dim=axes).to(torch.bfloat16))(X, (S, D), axes=(-2, -1))
        return y

    def _B_ref(x, w_gate, w_up, w_down):
        g = _silu(x @ w_gate)
        u = x @ w_up
        return (g * u) @ w_down

    x = A_x
    g = _sigmoid((x * gate_w).sum(-1, keepdims=True))
    a = _A_ref(x, A_w_r, A_w_i)
    b = _B_ref(x, B_w_gate, B_w_up, B_w_down)
    return g * a + (1 - g) * b
```

```cpp
#include <cuda_runtime.h>
#include <cuda_bf16.h>
#include <cuda.h>
#include <stdint.h>

namespace {

constexpr int S_ = 2048, D_ = 448, F_ = 1792, DF_ = 225;
constexpr int NFFN = 112, NSPEC = 20, NCTA = NFFN + NSPEC;
constexpr int NSTAGE = 7, STAGE_BYTES = 16384;
constexpr int SM_X = 0, SM_RING = 114688, SM_BAR = 229376, SM_TOTAL = SM_BAR + 512;
constexpr int SP_Z = 0, SP_W = 98304, SP_TW = 196608, SP_T = 212992;
constexpr uint32_t SPIN_LIMIT = 1u << 20;

namespace tab {
constexpr double PI = 3.14159265358979323846264338327950288;
constexpr double csin(double x) {
  double t = x, s = x;
  for (int i = 1; i < 20; i++) { t = -t * x * x / ((2 * i) * (2 * i + 1)); s += t; }
  return s;
}
constexpr double ccos(double x) {
  double t = 1, s = 1;
  for (int i = 1; i < 20; i++) { t = -t * x * x / ((2 * i - 1) * (2 * i)); s += t; }
  return s;
}
constexpr uint32_t to_bf16(double v) {
  uint32_t sign = v < 0 ? 0x8000u : 0u;
  double a = v < 0 ? -v : v;
  if (a < 1e-12) return 0;
  int e = 0;
  while (a >= 2.0) { a /= 2; e++; }
  while (a < 1.0) { a *= 2; e--; }
  double m = a * 128.0;
  int mi = (int)m;
  double fr = m - mi;
  if (fr > 0.5 || (fr == 0.5 && (mi & 1))) mi++;
  if (mi == 256) { mi = 128; e++; }
  return sign | (uint32_t)((e + 127) << 7) | (uint32_t)(mi - 128);
}
struct Base { uint32_t v[448]; };
constexpr Base make_base() {
  Base b{};
  for (int m = 0; m < 448; m++) {
    int mm = m > 224 ? m - 448 : m;
    double ang = 2 * PI * mm / 448.0;
    b.v[m] = to_bf16(ccos(ang)) | (to_bf16(-csin(ang)) << 16);
  }
  return b;
}
constexpr Base base = make_base();
struct Row { uint32_t v[224]; };
constexpr Row make_row(int d) {
  Row r{};
  r.v[0] = 0x3f80u | ((d & 1) ? 0xbf800000u : 0x3f800000u);
  int m = 0;
  for (int c = 1; c < 224; c++) { m += d; if (m >= 448) m -= 448; r.v[c] = base.v[m]; }
  return r;
}
struct Table { Row r[448]; };
constexpr Table make_table() {
  Table t{};
  for (int d = 0; d < 448; d++) t.r[d] = make_row(d);
  return t;
}
}
}

__device__ __align__(1024) const tab::Table g_ctab = tab::make_table();

__device__ __align__(1024) __nv_bfloat16 g_x1t[D_ * S_];
__device__ __align__(1024) __nv_bfloat16 g_yt[D_ * S_];
__device__ __align__(1024) uint4 g_part[16 * 7 * 6 * 2 * 4 * 128];
__device__ float g_gate[S_];
__device__ uint32_t g_cnt_x1[7 * 32];
__device__ uint32_t g_cnt_y[7 * 32];
__device__ uint32_t g_cnt_p[16 * 7 * 2 * 8];
__device__ uint32_t g_epoch[NCTA * 12];
#define TL(i)

namespace {

struct Params {
  CUtensorMap x, wg, wu, wd, ct, x1, yt;
};

__device__ __forceinline__ uint32_t smem_u32(const void* p) { return (uint32_t)__cvta_generic_to_shared(p); }
__device__ __forceinline__ void mbar_init(uint32_t bar, uint32_t cnt) {
  asm volatile("mbarrier.init.shared::cta.b64 [%0], %1;" ::"r"(bar), "r"(cnt) : "memory");
}
__device__ __forceinline__ void mbar_expect_tx(uint32_t bar, uint32_t bytes) {
  asm volatile("mbarrier.arrive.expect_tx.shared::cta.b64 _, [%0], %1;" ::"r"(bar), "r"(bytes) : "memory");
}
__device__ __forceinline__ void mbar_arrive(uint32_t bar) {
  asm volatile("mbarrier.arrive.shared::cta.b64 _, [%0];" ::"r"(bar) : "memory");
}
__device__ __forceinline__ void mbar_arrive_cluster(uint32_t bar, uint32_t cta) {
  asm volatile("{\n.reg .b32 ra;\nmapa.shared::cluster.u32 ra, %0, %1;\n"
               "mbarrier.arrive.shared::cluster.b64 _, [ra];\n}" ::"r"(bar), "r"(cta) : "memory");
}
__device__ __forceinline__ void mbar_wait(uint32_t bar, uint32_t parity) {
  uint32_t ok, n = 0;
  do {
    asm volatile("{\n.reg .pred p;\nmbarrier.try_wait.parity.shared::cta.b64 p, [%1], %2;\nselp.u32 %0, 1, 0, p;\n}"
                 : "=r"(ok) : "r"(bar), "r"(parity) : "memory");
  } while (!ok && ++n < SPIN_LIMIT);
}
__device__ __forceinline__ void mbar_wait_cluster(uint32_t bar, uint32_t parity) {
  uint32_t ok, n = 0;
  do {
    asm volatile("{\n.reg .pred p;\nmbarrier.try_wait.parity.acquire.cluster.shared::cta.b64 p, [%1], %2;\nselp.u32 %0, 1, 0, p;\n}"
                 : "=r"(ok) : "r"(bar), "r"(parity) : "memory");
  } while (!ok && ++n < SPIN_LIMIT);
}
__device__ __forceinline__ void tma2d(uint32_t dst, const CUtensorMap* m, int c0, int c1, uint32_t bar) {
  asm volatile("cp.async.bulk.tensor.2d.shared::cluster.global.mbarrier::complete_tx::bytes [%0], [%1, {%3, %4}], [%2];"
               ::"r"(dst), "l"(m), "r"(bar), "r"(c0), "r"(c1) : "memory");
}
__device__ __forceinline__ void tma3d(uint32_t dst, const CUtensorMap* m, int c0, int c1, int c2, uint32_t bar) {
  asm volatile("cp.async.bulk.tensor.3d.shared::cluster.global.mbarrier::complete_tx::bytes [%0], [%1, {%3, %4, %5}], [%2];"
               ::"r"(dst), "l"(m), "r"(bar), "r"(c0), "r"(c1), "r"(c2) : "memory");
}
__device__ __forceinline__ void tma2d_mc(uint32_t dst, const CUtensorMap* m, int c0, int c1, uint32_t bar) {
  asm volatile("cp.async.bulk.tensor.2d.shared::cluster.global.mbarrier::complete_tx::bytes.multicast::cluster [%0], [%1, {%3, %4}], [%2], %5;"
               ::"r"(dst), "l"(m), "r"(bar), "r"(c0), "r"(c1), "h"((uint16_t)3) : "memory");
}
__device__ __forceinline__ void tma3d_mc(uint32_t dst, const CUtensorMap* m, int c0, int c1, int c2, uint32_t bar) {
  asm volatile("cp.async.bulk.tensor.3d.shared::cluster.global.mbarrier::complete_tx::bytes.multicast::cluster [%0], [%1, {%3, %4, %5}], [%2], %6;"
               ::"r"(dst), "l"(m), "r"(bar), "r"(c0), "r"(c1), "r"(c2), "h"((uint16_t)3) : "memory");
}
__device__ __forceinline__ void prefetch_tmap(const CUtensorMap* m) {
  asm volatile("prefetch.tensormap [%0];" ::"l"(m) : "memory");
}
__device__ __forceinline__ void l2_prefetch(const void* p, uint32_t bytes) {
  asm volatile("cp.async.bulk.prefetch.L2.global [%0], %1;" ::"l"(p), "r"(bytes) : "memory");
}
__device__ __forceinline__ void wg_fence() { asm volatile("wgmma.fence.sync.aligned;" ::: "memory"); }
__device__ __forceinline__ void wg_commit() { asm volatile("wgmma.commit_group.sync.aligned;" ::: "memory"); }
template <int N> __device__ __forceinline__ void wg_wait() { asm volatile("wgmma.wait_group.sync.aligned %0;" ::"n"(N) : "memory"); }
template <int N> __device__ __forceinline__ void fence_regs(float (&d)[N]) {
#pragma unroll
  for (int i = 0; i < N; i++) asm volatile("" : "+f"(d[i])::"memory");
}
template <int N> __device__ __forceinline__ void fence_regs(uint32_t (&d)[N]) {
#pragma unroll
  for (int i = 0; i < N; i++) asm volatile("" : "+r"(d[i])::"memory");
}
__device__ __forceinline__ void bar_sync(int id, int n) { asm volatile("bar.sync %0, %1;" ::"r"(id), "r"(n) : "memory"); }
__device__ __forceinline__ void bar_arrive(int id, int n) { asm volatile("bar.arrive %0, %1;" ::"r"(id), "r"(n) : "memory"); }
__device__ __forceinline__ void fence_gpu() { asm volatile("fence.acq_rel.gpu;" ::: "memory"); }
__device__ __forceinline__ void fence_async() { asm volatile("fence.proxy.async;" ::: "memory"); }
__device__ __forceinline__ void fence_async_smem() { asm volatile("fence.proxy.async.shared::cta;" ::: "memory"); }
__device__ __forceinline__ void red_add(uint32_t* p, uint32_t v) {
  asm volatile("red.relaxed.gpu.global.add.u32 [%0], %1;" ::"l"(p), "r"(v) : "memory");
}
__device__ __forceinline__ uint32_t ld_relaxed(const uint32_t* p) {
  uint32_t v;
  asm volatile("ld.relaxed.gpu.global.u32 %0, [%1];" : "=r"(v) : "l"(p) : "memory");
  return v;
}
__device__ __forceinline__ void wait_counter(const uint32_t* p, uint32_t target) {
  uint32_t v, n = 0;
  while (true) {
    asm volatile("ld.acquire.gpu.global.u32 %0, [%1];" : "=r"(v) : "l"(p) : "memory");
    if ((int32_t)(v - target) >= 0 || ++n > SPIN_LIMIT) break;
  }
}
__device__ __forceinline__ uint4 ld_cg(const uint4* p) {
  uint4 v;
  asm volatile("ld.global.cg.v4.u32 {%0, %1, %2, %3}, [%4];" : "=r"(v.x), "=r"(v.y), "=r"(v.z), "=r"(v.w) : "l"(p) : "memory");
  return v;
}
__device__ __forceinline__ uint32_t pack2(float lo, float hi) {
  uint32_t r;
  asm("cvt.rn.bf16x2.f32 %0, %1, %2;" : "=r"(r) : "f"(hi), "f"(lo));
  return r;
}
__device__ __forceinline__ float bf_lo(uint32_t v) { return __uint_as_float(v << 16); }
__device__ __forceinline__ float bf_hi(uint32_t v) { return __uint_as_float(v & 0xffff0000u); }
__device__ __forceinline__ float bf_round(float v) { return bf_lo(pack2(v, 0.f)); }
__device__ __forceinline__ float tanh_fast(float v) {
  float r;
  asm("tanh.approx.f32 %0, %1;" : "=f"(r) : "f"(v));
  return r;
}
__device__ __forceinline__ uint64_t mk_desc(uint32_t addr, uint32_t lbo, uint32_t sbo, uint32_t mode) {
  return (uint64_t)((addr & 0x3FFFF) >> 4) | ((uint64_t)(lbo >> 4) << 16) | ((uint64_t)(sbo >> 4) << 32) | ((uint64_t)mode << 62);
}
__device__ __forceinline__ void stmatrix_x4(uint32_t addr, uint32_t r0, uint32_t r1, uint32_t r2, uint32_t r3) {
  asm volatile("stmatrix.sync.aligned.m8n8.x4.shared.b16 [%0], {%1, %2, %3, %4};" ::"r"(addr), "r"(r0), "r"(r1), "r"(r2), "r"(r3) : "memory");
}

template <int TA, int TB>
__device__ __forceinline__ void wgmma_ss_n256(float (&d)[128], uint64_t da, uint64_t db, int sd) {
  asm volatile("{\n.reg .pred p;\nsetp.ne.b32 p, %130, 0;\n"
      "wgmma.mma_async.sync.aligned.m64n256k16.f32.bf16.bf16 {"
      "%0, %1, %2, %3, %4, %5, %6, %7, %8, %9, %10, %11, %12, %13, %14, %15, %16, %17, %18, %19, %20, %21, %22, %23, "
      "%24, %25, %26, %27, %28, %29, %30, %31, %32, %33, %34, %35, %36, %37, %38, %39, %40, %41, %42, %43, %44, %45, "
      "%46, %47, %48, %49, %50, %51, %52, %53, %54, %55, %56, %57, %58, %59, %60, %61, %62, %63, %64, %65, %66, %67, "
      "%68, %69, %70, %71, %72, %73, %74, %75, %76, %77, %78, %79, %80, %81, %82, %83, %84, %85, %86, %87, %88, %89, "
      "%90, %91, %92, %93, %94, %95, %96, %97, %98, %99, %100, %101, %102, %103, %104, %105, %106, %107, %108, %109, "
      "%110, %111, %112, %113, %114, %115, %116, %117, %118, %119, %120, %121, %122, %123, %124, %125, %126, %127"
      "}, %128, %129, p, 1, 1, %131, %132;\n}\n"
      : "+f"(d[0]), "+f"(d[1]), "+f"(d[2]), "+f"(d[3]), "+f"(d[4]), "+f"(d[5]), "+f"(d[6]), "+f"(d[7]), "+f"(d[8]),
        "+f"(d[9]), "+f"(d[10]), "+f"(d[11]), "+f"(d[12]), "+f"(d[13]), "+f"(d[14]), "+f"(d[15]), "+f"(d[16]),
        "+f"(d[17]), "+f"(d[18]), "+f"(d[19]), "+f"(d[20]), "+f"(d[21]), "+f"(d[22]), "+f"(d[23]), "+f"(d[24]),
        "+f"(d[25]), "+f"(d[26]), "+f"(d[27]), "+f"(d[28]), "+f"(d[29]), "+f"(d[30]), "+f"(d[31]), "+f"(d[32]),
        "+f"(d[33]), "+f"(d[34]), "+f"(d[35]), "+f"(d[36]), "+f"(d[37]), "+f"(d[38]), "+f"(d[39]), "+f"(d[40]),
        "+f"(d[41]), "+f"(d[42]), "+f"(d[43]), "+f"(d[44]), "+f"(d[45]), "+f"(d[46]), "+f"(d[47]), "+f"(d[48]),
        "+f"(d[49]), "+f"(d[50]), "+f"(d[51]), "+f"(d[52]), "+f"(d[53]), "+f"(d[54]), "+f"(d[55]), "+f"(d[56]),
        "+f"(d[57]), "+f"(d[58]), "+f"(d[59]), "+f"(d[60]), "+f"(d[61]), "+f"(d[62]), "+f"(d[63]), "+f"(d[64]),
        "+f"(d[65]), "+f"(d[66]), "+f"(d[67]), "+f"(d[68]), "+f"(d[69]), "+f"(d[70]), "+f"(d[71]), "+f"(d[72]),
        "+f"(d[73]), "+f"(d[74]), "+f"(d[75]), "+f"(d[76]), "+f"(d[77]), "+f"(d[78]), "+f"(d[79]), "+f"(d[80]),
        "+f"(d[81]), "+f"(d[82]), "+f"(d[83]), "+f"(d[84]), "+f"(d[85]), "+f"(d[86]), "+f"(d[87]), "+f"(d[88]),
        "+f"(d[89]), "+f"(d[90]), "+f"(d[91]), "+f"(d[92]), "+f"(d[93]), "+f"(d[94]), "+f"(d[95]), "+f"(d[96]),
        "+f"(d[97]), "+f"(d[98]), "+f"(d[99]), "+f"(d[100]), "+f"(d[101]), "+f"(d[102]), "+f"(d[103]), "+f"(d[104]),
        "+f"(d[105]), "+f"(d[106]), "+f"(d[107]), "+f"(d[108]), "+f"(d[109]), "+f"(d[110]), "+f"(d[111]),
        "+f"(d[112]), "+f"(d[113]), "+f"(d[114]), "+f"(d[115]), "+f"(d[116]), "+f"(d[117]), "+f"(d[118]),
        "+f"(d[119]), "+f"(d[120]), "+f"(d[121]), "+f"(d[122]), "+f"(d[123]), "+f"(d[124]), "+f"(d[125]),
        "+f"(d[126]), "+f"(d[127])
      : "l"(da), "l"(db), "r"(sd), "n"(TA), "n"(TB));
}
template <int TA, int TB>
__device__ __forceinline__ void wgmma_ss_n128(float (&d)[64], uint64_t da, uint64_t db, int sd) {
  asm volatile("{\n.reg .pred p;\nsetp.ne.b32 p, %66, 0;\n"
      "wgmma.mma_async.sync.aligned.m64n128k16.f32.bf16.bf16 {"
      "%0, %1, %2, %3, %4, %5, %6, %7, %8, %9, %10, %11, %12, %13, %14, %15, %16, %17, %18, %19, %20, %21, %22, %23, "
      "%24, %25, %26, %27, %28, %29, %30, %31, %32, %33, %34, %35, %36, %37, %38, %39, %40, %41, %42, %43, %44, %45, "
      "%46, %47, %48, %49, %50, %51, %52, %53, %54, %55, %56, %57, %58, %59, %60, %61, %62, %63"
      "}, %64, %65, p, 1, 1, %67, %68;\n}\n"
      : "+f"(d[0]), "+f"(d[1]), "+f"(d[2]), "+f"(d[3]), "+f"(d[4]), "+f"(d[5]), "+f"(d[6]), "+f"(d[7]), "+f"(d[8]),
        "+f"(d[9]), "+f"(d[10]), "+f"(d[11]), "+f"(d[12]), "+f"(d[13]), "+f"(d[14]), "+f"(d[15]), "+f"(d[16]),
        "+f"(d[17]), "+f"(d[18]), "+f"(d[19]), "+f"(d[20]), "+f"(d[21]), "+f"(d[22]), "+f"(d[23]), "+f"(d[24]),
        "+f"(d[25]), "+f"(d[26]), "+f"(d[27]), "+f"(d[28]), "+f"(d[29]), "+f"(d[30]), "+f"(d[31]), "+f"(d[32]),
        "+f"(d[33]), "+f"(d[34]), "+f"(d[35]), "+f"(d[36]), "+f"(d[37]), "+f"(d[38]), "+f"(d[39]), "+f"(d[40]),
        "+f"(d[41]), "+f"(d[42]), "+f"(d[43]), "+f"(d[44]), "+f"(d[45]), "+f"(d[46]), "+f"(d[47]), "+f"(d[48]),
        "+f"(d[49]), "+f"(d[50]), "+f"(d[51]), "+f"(d[52]), "+f"(d[53]), "+f"(d[54]), "+f"(d[55]), "+f"(d[56]),
        "+f"(d[57]), "+f"(d[58]), "+f"(d[59]), "+f"(d[60]), "+f"(d[61]), "+f"(d[62]), "+f"(d[63])
      : "l"(da), "l"(db), "r"(sd), "n"(TA), "n"(TB));
}
template <int TA, int TB>
__device__ __forceinline__ void wgmma_ss_n64(float (&d)[32], uint64_t da, uint64_t db, int sd) {
  asm volatile("{\n.reg .pred p;\nsetp.ne.b32 p, %34, 0;\n"
      "wgmma.mma_async.sync.aligned.m64n64k16.f32.bf16.bf16 {"
      "%0, %1, %2, %3, %4, %5, %6, %7, %8, %9, %10, %11, %12, %13, %14, %15, %16, %17, %18, %19, %20, %21, %22, %23, "
      "%24, %25, %26, %27, %28, %29, %30, %31"
      "}, %32, %33, p, 1, 1, %35, %36;\n}\n"
      : "+f"(d[0]), "+f"(d[1]), "+f"(d[2]), "+f"(d[3]), "+f"(d[4]), "+f"(d[5]), "+f"(d[6]), "+f"(d[7]), "+f"(d[8]),
        "+f"(d[9]), "+f"(d[10]), "+f"(d[11]), "+f"(d[12]), "+f"(d[13]), "+f"(d[14]), "+f"(d[15]), "+f"(d[16]),
        "+f"(d[17]), "+f"(d[18]), "+f"(d[19]), "+f"(d[20]), "+f"(d[21]), "+f"(d[22]), "+f"(d[23]), "+f"(d[24]),
        "+f"(d[25]), "+f"(d[26]), "+f"(d[27]), "+f"(d[28]), "+f"(d[29]), "+f"(d[30]), "+f"(d[31])
      : "l"(da), "l"(db), "r"(sd), "n"(TA), "n"(TB));
}
template <int SA, int TB>
__device__ __forceinline__ void wgmma_rs_n128(float (&d)[64], uint32_t a0, uint32_t a1, uint32_t a2, uint32_t a3, uint64_t db, int sd) {
  asm volatile("{\n.reg .pred p;\nsetp.ne.b32 p, %69, 0;\n"
      "wgmma.mma_async.sync.aligned.m64n128k16.f32.bf16.bf16 {"
      "%0, %1, %2, %3, %4, %5, %6, %7, %8, %9, %10, %11, %12, %13, %14, %15, %16, %17, %18, %19, %20, %21, %22, %23, "
      "%24, %25, %26, %27, %28, %29, %30, %31, %32, %33, %34, %35, %36, %37, %38, %39, %40, %41, %42, %43, %44, %45, "
      "%46, %47, %48, %49, %50, %51, %52, %53, %54, %55, %56, %57, %58, %59, %60, %61, %62, %63"
      "}, {%64, %65, %66, %67}, %68, p, %70, 1, %71;\n}\n"
      : "+f"(d[0]), "+f"(d[1]), "+f"(d[2]), "+f"(d[3]), "+f"(d[4]), "+f"(d[5]), "+f"(d[6]), "+f"(d[7]), "+f"(d[8]),
        "+f"(d[9]), "+f"(d[10]), "+f"(d[11]), "+f"(d[12]), "+f"(d[13]), "+f"(d[14]), "+f"(d[15]), "+f"(d[16]),
        "+f"(d[17]), "+f"(d[18]), "+f"(d[19]), "+f"(d[20]), "+f"(d[21]), "+f"(d[22]), "+f"(d[23]), "+f"(d[24]),
        "+f"(d[25]), "+f"(d[26]), "+f"(d[27]), "+f"(d[28]), "+f"(d[29]), "+f"(d[30]), "+f"(d[31]), "+f"(d[32]),
        "+f"(d[33]), "+f"(d[34]), "+f"(d[35]), "+f"(d[36]), "+f"(d[37]), "+f"(d[38]), "+f"(d[39]), "+f"(d[40]),
        "+f"(d[41]), "+f"(d[42]), "+f"(d[43]), "+f"(d[44]), "+f"(d[45]), "+f"(d[46]), "+f"(d[47]), "+f"(d[48]),
        "+f"(d[49]), "+f"(d[50]), "+f"(d[51]), "+f"(d[52]), "+f"(d[53]), "+f"(d[54]), "+f"(d[55]), "+f"(d[56]),
        "+f"(d[57]), "+f"(d[58]), "+f"(d[59]), "+f"(d[60]), "+f"(d[61]), "+f"(d[62]), "+f"(d[63])
      : "r"(a0), "r"(a1), "r"(a2), "r"(a3), "l"(db), "r"(sd), "n"(SA), "n"(TB));
}
template <int SA, int TB>
__device__ __forceinline__ void wgmma_rs_n64(float (&d)[32], uint32_t a0, uint32_t a1, uint32_t a2, uint32_t a3, uint64_t db, int sd) {
  asm volatile("{\n.reg .pred p;\nsetp.ne.b32 p, %37, 0;\n"
      "wgmma.mma_async.sync.aligned.m64n64k16.f32.bf16.bf16 {"
      "%0, %1, %2, %3, %4, %5, %6, %7, %8, %9, %10, %11, %12, %13, %14, %15, %16, %17, %18, %19, %20, %21, %22, %23, "
      "%24, %25, %26, %27, %28, %29, %30, %31"
      "}, {%32, %33, %34, %35}, %36, p, %38, 1, %39;\n}\n"
      : "+f"(d[0]), "+f"(d[1]), "+f"(d[2]), "+f"(d[3]), "+f"(d[4]), "+f"(d[5]), "+f"(d[6]), "+f"(d[7]), "+f"(d[8]),
        "+f"(d[9]), "+f"(d[10]), "+f"(d[11]), "+f"(d[12]), "+f"(d[13]), "+f"(d[14]), "+f"(d[15]), "+f"(d[16]),
        "+f"(d[17]), "+f"(d[18]), "+f"(d[19]), "+f"(d[20]), "+f"(d[21]), "+f"(d[22]), "+f"(d[23]), "+f"(d[24]),
        "+f"(d[25]), "+f"(d[26]), "+f"(d[27]), "+f"(d[28]), "+f"(d[29]), "+f"(d[30]), "+f"(d[31])
      : "r"(a0), "r"(a1), "r"(a2), "r"(a3), "l"(db), "r"(sd), "n"(SA), "n"(TB));
}

__device__ __forceinline__ uint32_t BAR_FULL(uint32_t sb, int i) { return sb + SM_BAR + 8 * i; }
__device__ __forceinline__ uint32_t BAR_EMPTY(uint32_t sb, int i) { return sb + SM_BAR + 64 + 8 * i; }
__device__ __forceinline__ uint32_t BAR_X(uint32_t sb, int i) { return sb + SM_BAR + 128 + 8 * i; }
__device__ __forceinline__ uint32_t BAR_Y(uint32_t sb, int i) { return sb + SM_BAR + 192 + 8 * i; }
__device__ __forceinline__ uint32_t BAR_XFREE(uint32_t sb) { return sb + SM_BAR + 256; }

constexpr int Q_G2 = 32, Q_OWN = 44, Q_P3 = 46, Q_END = 50;

struct Ring {
  uint32_t slot, phase;
  __device__ __forceinline__ void set(int q) { slot = q % NSTAGE; phase = (q / NSTAGE) & 1; }
  __device__ __forceinline__ void next() { if (++slot == NSTAGE) { slot = 0; phase ^= 1; } }
};

__device__ __forceinline__ void release_slot(uint32_t sb, uint32_t slot, int tid, int times) {
  if (tid < 2 * times) mbar_arrive_cluster(BAR_EMPTY(sb, slot), tid & 1);
}

__device__ __forceinline__ void ffn_consumer(uint32_t sb, int wg, int tid, int mt, int jj, __nv_bfloat16* __restrict__ out) {
  const int lane = tid & 31, warp = tid >> 5, q = lane & 3, r0 = 16 * warp + (lane >> 2);
  uint32_t* const my_epoch = &g_epoch[blockIdx.x * 12 + (threadIdx.x >> 5)];
  const uint32_t epoch = ld_relaxed(my_epoch) + 1;
  Ring rg;
  TL(1);
  if (wg == 1) {
    float acc[64];
#pragma unroll 1
    for (int kb = 0; kb < 7; kb++) {
      const uint32_t slot = (kb >> 1) + ((kb >> 2) << 1);
      mbar_wait(BAR_FULL(sb, slot), 0);
      mbar_wait(BAR_X(sb, kb), 0);
      const uint64_t da = mk_desc(sb + SM_RING + slot * STAGE_BYTES + (kb & 1) * 8192, 8192, 1024, 1);
      const uint64_t db = mk_desc(sb + SM_X + kb * 16384, 16, 1024, 1);
      wg_fence();
#pragma unroll
      for (int kk = 0; kk < 4; kk++) wgmma_ss_n128<1, 0>(acc, da + kk * 128, db + kk * 2, (kb | kk) != 0);
      wg_commit();
      wg_wait<1>();
      if (kb > 0 && (kb & 1) == 0) release_slot(sb, ((kb - 1) >> 1) + (((kb - 1) >> 2) << 1), tid, 2);
    }
    wg_wait<0>();
    fence_regs(acc);
    release_slot(sb, 5, tid, 2);
    TL(2);
#pragma unroll
    for (int h = 0; h < 2; h++) {
      uint4* dst = reinterpret_cast<uint4*>(g_x1t + (size_t)(64 * jj + r0 + 8 * h) * S_ + 128 * mt + 8 * q);
#pragma unroll
      for (int t = 0; t < 4; t++) {
        uint4 v;
        v.x = pack2(acc[16 * t + 2 * h], acc[16 * t + 2 * h + 1]);
        v.y = pack2(acc[16 * t + 4 + 2 * h], acc[16 * t + 4 + 2 * h + 1]);
        v.z = pack2(acc[16 * t + 8 + 2 * h], acc[16 * t + 8 + 2 * h + 1]);
        v.w = pack2(acc[16 * t + 12 + 2 * h], acc[16 * t + 12 + 2 * h + 1]);
        dst[4 * t] = v;
      }
    }
    bar_arrive(7, 160);
  }
  uint32_t h0[32], h1[32];
  rg.set(2);
#pragma unroll 1
  for (int pass = 0; pass < 2; pass++) {
    float acc[128];
    uint32_t prev = 0;
#pragma unroll 1
    for (int st = 0; st < 14; st++) {
      if (pass == 0) {
        if (st == 2) rg.set(6);
        if ((st & 1) == 0) mbar_wait(BAR_X(sb, st >> 1), 0);
      }
      mbar_wait(BAR_FULL(sb, rg.slot), rg.phase);
      const uint64_t da = mk_desc(sb + SM_X + (st >> 1) * 16384 + wg * 8192 + (st & 1) * 64, 16, 1024, 1);
      const uint64_t db = mk_desc(sb + SM_RING + rg.slot * STAGE_BYTES, 4096, 1024, 1);
      wg_fence();
      wgmma_ss_n256<0, 1>(acc, da, db, st != 0);
      wgmma_ss_n256<0, 1>(acc, da + 2, db + 128, 1);
      wg_commit();
      if (st > 0) { wg_wait<1>(); release_slot(sb, prev, tid, 1); }
      prev = rg.slot;
      rg.next();
    }
    wg_wait<0>();
    fence_regs(acc);
    release_slot(sb, prev, tid, 1);
    if (pass == 1 && tid == 0) mbar_arrive(BAR_XFREE(sb));
    TL(3 + 2 * pass);
#pragma unroll
    for (int i = 0; i < 32; i++) {
      const float g0 = 0.5f * acc[2 * i], g1 = 0.5f * acc[2 * i + 1];
      const float s0 = fmaf(g0, tanh_fast(g0), g0), s1 = fmaf(g1, tanh_fast(g1), g1);
      h1[i] = pack2(s0 * acc[64 + 2 * i], s1 * acc[64 + 2 * i + 1]);
    }
    if (pass == 0) {
#pragma unroll
      for (int i = 0; i < 32; i++) h0[i] = h1[i];
    }
    TL(4 + 2 * pass);
  }
  fence_regs(h0); fence_regs(h1);
#pragma unroll 1
  for (int c = 0; c < 3; c++) {
    float acc[64];
    uint32_t prev = 0;
#pragma unroll
    for (int st = 0; st < 4; st++) {
      mbar_wait(BAR_FULL(sb, rg.slot), rg.phase);
      const uint64_t db = mk_desc(sb + SM_RING + rg.slot * STAGE_BYTES, 8192, 1024, 1);
      wg_fence();
#pragma unroll
      for (int kk = 0; kk < 4; kk++) {
        const uint32_t* a = (st < 2 ? h0 : h1) + ((st & 1) * 4 + kk) * 4;
        wgmma_rs_n128<1, 1>(acc, a[0], a[1], a[2], a[3], db + kk * 128, (st | kk) != 0);
      }
      wg_commit();
      if (st > 0) { wg_wait<1>(); release_slot(sb, prev, tid, 1); }
      prev = rg.slot;
      rg.next();
    }
    wg_wait<0>();
    fence_regs(acc);
    release_slot(sb, prev, tid, 1);
#pragma unroll
    for (int b = 0; b < 2; b++) {
      int o = jj + 1 + 2 * c + b;
      if (o >= 7) o -= 7;
      uint4* dst = g_part + ((((mt * 7 + o) * 6 + 2 * c + b) * 2 + wg) * 4) * 128 + tid;
#pragma unroll
      for (int v = 0; v < 4; v++) {
        const float* a = acc + 32 * b + 8 * v;
        dst[v * 128] = make_uint4(pack2(a[0], a[1]), pack2(a[2], a[3]), pack2(a[4], a[5]), pack2(a[6], a[7]));
      }
    }
    bar_arrive(1 + 3 * wg + c, 160);
    TL(7 + c);
  }
  float accb[32], acca[32];
  {
    const uint32_t first = rg.slot;
#pragma unroll
    for (int st = 0; st < 2; st++) {
      mbar_wait(BAR_FULL(sb, rg.slot), rg.phase);
      const uint64_t db = mk_desc(sb + SM_RING + rg.slot * STAGE_BYTES, 8192, 1024, 1);
      wg_fence();
#pragma unroll
      for (int kk = 0; kk < 8; kk++) {
        const uint32_t* a = (st == 0 ? h0 : h1) + kk * 4;
        wgmma_rs_n64<1, 1>(accb, a[0], a[1], a[2], a[3], db + kk * 128, (st | kk) != 0);
      }
      rg.next();
    }
    wg_commit();
    TL(10);
    float sum[32];
#pragma unroll
    for (int i = 0; i < 32; i++) sum[i] = 0.f;
    const uint4* src = g_part + (((mt * 7 + jj) * 6 * 2 + wg) * 4) * 128 + tid;
    auto gather = [&](int c) {
      if (lane == 0) wait_counter(&g_cnt_p[((mt * 7 + jj) * 2 + wg) * 8 + c], epoch * 2);
      __syncwarp();
      uint4 pv[8];
#pragma unroll
      for (int i = 0; i < 8; i++) pv[i] = ld_cg(src + ((2 * c + (i >> 2)) * 8 + (i & 3)) * 128);
#pragma unroll
      for (int i = 0; i < 8; i++) {
        const int v = i & 3;
        sum[8 * v + 0] += bf_lo(pv[i].x); sum[8 * v + 1] += bf_hi(pv[i].x);
        sum[8 * v + 2] += bf_lo(pv[i].y); sum[8 * v + 3] += bf_hi(pv[i].y);
        sum[8 * v + 4] += bf_lo(pv[i].z); sum[8 * v + 5] += bf_hi(pv[i].z);
        sum[8 * v + 6] += bf_lo(pv[i].w); sum[8 * v + 7] += bf_hi(pv[i].w);
      }
    };
#pragma unroll
    for (int kb = 0; kb < 7; kb++) {
      if ((kb & 1) == 0) mbar_wait(BAR_FULL(sb, rg.slot), rg.phase);
      mbar_wait(BAR_Y(sb, kb), 0);
      const uint64_t da = mk_desc(sb + SM_X + kb * 16384 + wg * 8192, 8192, 1024, 1);
      const uint64_t db = mk_desc(sb + SM_RING + rg.slot * STAGE_BYTES + (kb & 1) * 8192, 16, 1024, 1);
      wg_fence();
#pragma unroll
      for (int kk = 0; kk < 4; kk++) wgmma_ss_n64<1, 0>(acca, da + kk * 128, db + kk * 2, (kb | kk) != 0);
      if (kb & 1) rg.next();
    }
    wg_commit();
    TL(11);
    const int row = 128 * mt + 64 * wg + r0;
    const float ga0 = __ldcg(&g_gate[row]), ga1 = __ldcg(&g_gate[row + 8]);
#pragma unroll 1
    for (int c = 0; c < 3; c++) gather(c);
    TL(12);
    wg_wait<0>();
    fence_regs(acca);
    fence_regs(accb);
    if (tid < 12) {
      uint32_t sl = first + (tid >> 1);
      if (sl >= NSTAGE) sl -= NSTAGE;
      mbar_arrive_cluster(BAR_EMPTY(sb, sl), tid & 1);
    }
    TL(13);
    const float gb0 = bf_round(1.f - ga0), gb1 = bf_round(1.f - ga1);
    uint32_t* o0 = reinterpret_cast<uint32_t*>(out + (size_t)row * D_ + 64 * jj + 2 * q);
    uint32_t* o1 = o0 + 8 * D_ / 2;
#pragma unroll
    for (int jb = 0; jb < 8; jb++) {
      o0[4 * jb] = pack2(fmaf(ga0, acca[4 * jb], gb0 * (accb[4 * jb] + sum[4 * jb])),
                         fmaf(ga0, acca[4 * jb + 1], gb0 * (accb[4 * jb + 1] + sum[4 * jb + 1])));
      o1[4 * jb] = pack2(fmaf(ga1, acca[4 * jb + 2], gb1 * (accb[4 * jb + 2] + sum[4 * jb + 2])),
                         fmaf(ga1, acca[4 * jb + 3], gb1 * (accb[4 * jb + 3] + sum[4 * jb + 3])));
    }
    if (lane == 0) *my_epoch = epoch;
    TL(14);
  }
}

__device__ __forceinline__ void ffn_producer(uint32_t sb, const Params& p, int warp, int lane, int mt, int jj, uint32_t rank) {
  if (warp == 0) {
    if (lane == 0) {
      Ring rg;
      rg.set(0);
#pragma unroll 1
      for (int qi = 0; qi < Q_END; qi++) {
        if (qi >= NSTAGE) mbar_wait_cluster(BAR_EMPTY(sb, rg.slot), rg.phase ^ 1);
        const uint32_t bar = BAR_FULL(sb, rg.slot);
        const uint32_t dst = sb + SM_RING + rg.slot * STAGE_BYTES + rank * 8192;
        const bool half = (qi == 5 || qi == Q_END - 1);
        mbar_expect_tx(bar, half ? 8192 : 16384);
        if (qi < 6 && (qi & 2) == 0) {
          const int kb = 2 * (qi < 2 ? qi : qi - 2) + rank;
          if (kb < 7) tma2d_mc(dst, &p.ct, 64 * jj, 64 * kb, bar);
        } else if (qi < Q_G2) {
          const int g = qi < 6 ? qi - 2 : qi - 4;
          const int pass = g >= 14, st = g - 14 * pass;
          tma3d_mc(dst, rank ? &p.wu : &p.wg, 0, 32 * st, 4 * jj + 2 * pass, bar);
        } else if (qi < Q_OWN) {
          const int c = (qi - Q_G2) >> 2, st = (qi - Q_G2) & 3;
          int o = jj + 1 + 2 * c + rank;
          if (o >= 7) o -= 7;
          tma2d_mc(dst, &p.wd, 64 * o, 256 * jj + 64 * st, bar);
        } else if (qi < Q_P3) {
          tma2d_mc(dst, &p.wd, 64 * jj, 256 * jj + 128 * (qi - Q_OWN) + 64 * rank, bar);
        } else {
          const int kb = 2 * (qi - Q_P3) + rank;
          if (kb < 7) tma2d_mc(dst, &p.ct, 64 * kb, 64 * jj, bar);
        }
        rg.next();
      }
#pragma unroll 1
      for (int i = 0; i < NSTAGE; i++) { mbar_wait_cluster(BAR_EMPTY(sb, rg.slot), rg.phase ^ 1); rg.next(); }
    }
  } else if (warp == 1) {
    if (lane == 0) {
      uint32_t* const my_epoch = &g_epoch[blockIdx.x * 12 + 9];
      const uint32_t epoch = ld_relaxed(my_epoch) + 1;
      mbar_wait(BAR_XFREE(sb), 0);
      TL(1);
#pragma unroll 1
      for (int kb = 0; kb < 7; kb++) {
        wait_counter(&g_cnt_y[kb * 32], epoch * 32);
        fence_async();
        mbar_expect_tx(BAR_Y(sb, kb), 16384);
        tma3d(sb + SM_X + kb * 16384, &p.yt, 0, 64 * kb, 2 * mt, BAR_Y(sb, kb));
      }
      TL(2);
      *my_epoch = epoch;
    }
  } else {
    const int wg = warp - 2;
    if (wg == 1) {
      bar_sync(7, 160);
      if (lane == 0) { fence_gpu(); red_add(&g_cnt_x1[jj * 32], 1); }
      TL(1);
    }
#pragma unroll 1
    for (int c = 0; c < 3; c++) {
      bar_sync(1 + 3 * wg + c, 160);
      if (lane < 2) {
        int o = jj + 1 + 2 * c + lane;
        if (o >= 7) o -= 7;
        fence_gpu();
        red_add(&g_cnt_p[((mt * 7 + o) * 2 + wg) * 8 + c], 1);
      }
      TL(2 + c);
    }
  }
}

__device__ __forceinline__ void spectral_cta(uint32_t sb, uint8_t* smem, const Params& p, int sc,
                                             const __nv_bfloat16* __restrict__ x, const __nv_bfloat16* __restrict__ w_r,
                                             const __nv_bfloat16* __restrict__ w_i, const __nv_bfloat16* __restrict__ gate_w,
                                             const __nv_bfloat16* __restrict__ wd) {
  const int t384 = threadIdx.x, lane = t384 & 31, warp12 = t384 >> 5, wg = __shfl_sync(0xffffffffu, t384 >> 7, 0), tid = t384 & 127;
  const int warp = tid >> 5, q = lane & 3, r0 = 16 * warp + (lane >> 2);
  uint32_t* const my_epoch = &g_epoch[blockIdx.x * 12 + warp12];
  const uint32_t epoch = ld_relaxed(my_epoch) + 1;
  TL(1);
  const int kd0 = 1 + 12 * sc;
  if (sc < 19) {
    const uint32_t* wr32 = reinterpret_cast<const uint32_t*>(w_r);
    const uint32_t* wi32 = reinterpret_cast<const uint32_t*>(w_i);
    const int sub = lane & 7;
#pragma unroll 1
    for (int it0 = 0; it0 < 44; it0 += 11) {
      uint32_t vr[11], vi[11];
#pragma unroll
      for (int u = 0; u < 11; u++) {
        const int k = (it0 + u) * 48 + (t384 >> 3);
        const int e0 = k * DF_ + kd0;
        const int wi = (e0 >> 1) + sub;
        const bool ok = k < S_ && sub < 7 && wi < S_ * DF_ / 2;
        vr[u] = ok ? __ldg(wr32 + wi) : 0u;
        vi[u] = ok ? __ldg(wi32 + wi) : 0u;
      }
#pragma unroll
      for (int u = 0; u < 11; u++) {
        const int k = (it0 + u) * 48 + (t384 >> 3);
        const int c0 = 2 * sub - ((k * DF_ + kd0) & 1);
        const int k1 = k & 63, k2 = k >> 6;
        const uint32_t off = (k2 >> 3) * 2048 + (32 * (k1 >> 4) + 4 * (k1 & 7) + ((k2 >> 1) & 3)) * 16 + (2 * ((k1 >> 3) & 1) + (k2 & 1)) * 4;
        if (k < S_) {
          if (c0 >= 0 && c0 < 12) *reinterpret_cast<uint32_t*>(smem + SP_W + c0 * 8192 + off) = __byte_perm(vr[u], vi[u], 0x5410);
          if (c0 + 1 < 12) *reinterpret_cast<uint32_t*>(smem + SP_W + (c0 + 1) * 8192 + off) = __byte_perm(vr[u], vi[u], 0x7632);
        }
      }
    }
  } else {
    const uint16_t* wr16 = reinterpret_cast<const uint16_t*>(w_r);
    const uint16_t* wi16 = reinterpret_cast<const uint16_t*>(w_i);
#pragma unroll
    for (int u = 0; u < 11; u++) {
      const int idx = u * 384 + t384, k = idx >> 1, c = idx & 1;
      if (k < S_) {
        const uint32_t a = __ldg(wr16 + k * DF_ + c * 224), b = __ldg(wi16 + k * DF_ + c * 224);
        const int k1 = k & 63, k2 = k >> 6;
        const uint32_t off = (k2 >> 3) * 2048 + (32 * (k1 >> 4) + 4 * (k1 & 7) + ((k2 >> 1) & 3)) * 16 + (2 * ((k1 >> 3) & 1) + (k2 & 1)) * 4;
        *reinterpret_cast<uint32_t*>(smem + SP_W + c * 8192 + off) = a | (b << 16);
      }
    }
  }
  TL(2);
  if (t384 < 20) {
    const int ch = sc * 20 + t384;
    if (ch < 392) l2_prefetch(reinterpret_cast<const uint8_t*>(wd) + (size_t)ch * 4096, 4096);
  }
  {
    const uint4* gw4 = reinterpret_cast<const uint4*>(gate_w);
    const uint4 ga = __ldg(gw4 + lane), gb = lane < 24 ? __ldg(gw4 + 32 + lane) : make_uint4(0, 0, 0, 0);
    uint4 xa[9], xb[9];
#pragma unroll
    for (int u = 0; u < 9; u++) {
      const int row = u * 240 + sc * 12 + warp12;
      const uint4* xr = reinterpret_cast<const uint4*>(x + (size_t)row * D_);
      xa[u] = row < S_ ? __ldg(xr + lane) : make_uint4(0, 0, 0, 0);
      xb[u] = (row < S_ && lane < 24) ? __ldg(xr + 32 + lane) : make_uint4(0, 0, 0, 0);
    }
#pragma unroll
    for (int u = 0; u < 9; u++) {
      float s = 0.f;
      auto dot2 = [&](uint32_t a, uint32_t b) {
        const uint32_t pr = pack2(bf_lo(a) * bf_lo(b), bf_hi(a) * bf_hi(b));
        s += bf_lo(pr) + bf_hi(pr);
      };
      dot2(xa[u].x, ga.x); dot2(xa[u].y, ga.y); dot2(xa[u].z, ga.z); dot2(xa[u].w, ga.w);
      dot2(xb[u].x, gb.x); dot2(xb[u].y, gb.y); dot2(xb[u].z, gb.z); dot2(xb[u].w, gb.w);
#pragma unroll
      for (int o = 16; o > 0; o >>= 1) s += __shfl_xor_sync(0xffffffffu, s, o);
      const int row = u * 240 + sc * 12 + warp12;
      if (lane == 0 && row < S_) g_gate[row] = bf_round(1.f / (1.f + __expf(-bf_round(s))));
    }
  }
  for (int i = t384; i < 2048; i += 384) {
    const int e = i & 1, t = (i >> 1) & 127, v = i >> 8;
    const int k1 = 16 * (t >> 5) + ((t & 31) >> 2) + 8 * (v & 1), n2 = 8 * (t & 3) + 2 * (v >> 1) + e;
    float s, c;
    sincospif((float)(n2 * k1) * (1.f / 1024.f), &s, &c);
    *reinterpret_cast<float2*>(smem + SP_TW + v * 2048 + t * 16 + e * 8) = make_float2(c, s);
  }
  for (int i = t384; i < 1024; i += 384) {
    const int c = i >> 5, k2 = i & 31;
    const int n2 = 8 * ((c >> 1) & 3) + 2 * (c >> 3) + (c & 1);
    float s, co;
    sincospif((float)((n2 * k2) & 31) * (1.f / 16.f), &s, &co);
    auto put = [&](int row, int col, float v) {
      *reinterpret_cast<uint16_t*>(smem + SP_T + row * 128 + (((col >> 3) ^ (row & 7)) << 4) + (col & 7) * 2) = (uint16_t)(pack2(v, 0.f) & 0xffff);
    };
    put(c, k2, co); put(c, 32 + k2, -s); put(32 + c, k2, s); put(32 + c, 32 + k2, co);
  }
  uint32_t fc[16], fs[16];
#pragma unroll
  for (int i = 0; i < 16; i++) {
    const int m = r0 + 8 * (i & 1), k = 16 * (i >> 2) + 8 * ((i >> 1) & 1) + 2 * q;
    float s0, c0, s1, c1;
    sincospif((float)((m * k) & 63) * (1.f / 32.f), &s0, &c0);
    sincospif((float)((m * (k + 1)) & 63) * (1.f / 32.f), &s1, &c1);
    fc[i] = pack2(c0, c1);
    fs[i] = pack2(s0, s1);
  }
  fence_regs(fc); fence_regs(fs);
  fence_async_smem();
  __syncthreads();
  TL(3);
  const int nitem = sc < 18 ? 6 : (sc == 18 ? 4 : 1);
  if (tid == 0) {
#pragma unroll 1
    for (int rnd = 0; rnd < 2; rnd++) {
      const int item = wg + 3 * rnd;
      if (item >= nitem) break;
      const int ka = kd0 + 2 * item, kb = ka + 1;
      int ra, ia, rb, ib;
      if (sc < 19) { ra = 2 * ka; ia = ra + 1; rb = kb < 224 ? 2 * kb : D_; ib = kb < 224 ? rb + 1 : D_; }
      else { ra = 0; rb = 1; ia = D_; ib = D_; }
      wait_counter(&g_cnt_x1[(ra >> 6) * 32], epoch * 16);
      if (rb < D_) wait_counter(&g_cnt_x1[(rb >> 6) * 32], epoch * 16);
      fence_async();
      const uint32_t bar = BAR_FULL(sb, item), z = sb + SP_Z + item * 16384;
      mbar_expect_tx(bar, 16384);
      tma2d(z, &p.x1, 0, ra * 64, bar);
      tma2d(z + 4096, &p.x1, 0, rb * 64, bar);
      tma2d(z + 8192, &p.x1, 0, ia * 64, bar);
      tma2d(z + 12288, &p.x1, 0, ib * 64, bar);
    }
  }
  __syncwarp();
  TL(4);
  const float scale = (sc < 19 ? 2.f : 1.f) / (float)(S_ * D_);
  const uint64_t dT_n = mk_desc(sb + SP_T, 8192, 1024, 1);
#pragma unroll 1
  for (int rnd = 0; rnd < 2; rnd++) {
    const int item = wg + 3 * rnd;
    if (item >= nitem) break;
    const uint32_t z = sb + SP_Z + item * 16384;
    mbar_wait(BAR_FULL(sb, item), 0);
    TL(5 + 4 * rnd);
    float aR[32], aI[32];
    {
      const uint64_t dr = mk_desc(z, 4096, 512, 2), di = mk_desc(z + 8192, 4096, 512, 2);
      wg_fence();
#pragma unroll
      for (int kk = 0; kk < 4; kk++) {
        wgmma_rs_n64<1, 1>(aR, fc[4 * kk], fc[4 * kk + 1], fc[4 * kk + 2], fc[4 * kk + 3], dr + kk * 64, kk != 0);
        wgmma_rs_n64<1, 1>(aI, fc[4 * kk], fc[4 * kk + 1], fc[4 * kk + 2], fc[4 * kk + 3], di + kk * 64, kk != 0);
      }
#pragma unroll
      for (int kk = 0; kk < 4; kk++) {
        wgmma_rs_n64<1, 1>(aR, fs[4 * kk], fs[4 * kk + 1], fs[4 * kk + 2], fs[4 * kk + 3], di + kk * 64, 1);
        wgmma_rs_n64<-1, 1>(aI, fs[4 * kk], fs[4 * kk + 1], fs[4 * kk + 2], fs[4 * kk + 3], dr + kk * 64, 1);
      }
      wg_commit();
      wg_wait<0>();
      fence_regs(aR); fence_regs(aI);
    }
    uint32_t fa[16], fb[16];
#pragma unroll
    for (int v = 0; v < 8; v++) {
      const float4 tw = *reinterpret_cast<const float4*>(smem + SP_TW + v * 2048 + tid * 16);
      fa[v] = pack2(aR[2 * v] * tw.x + aI[2 * v] * tw.y, aR[2 * v + 1] * tw.z + aI[2 * v + 1] * tw.w);
      fa[8 + v] = pack2(aI[2 * v] * tw.x - aR[2 * v] * tw.y, aI[2 * v + 1] * tw.z - aR[2 * v + 1] * tw.w);
      fb[v] = pack2(aR[16 + 2 * v] * tw.x + aI[16 + 2 * v] * tw.y, aR[16 + 2 * v + 1] * tw.z + aI[16 + 2 * v + 1] * tw.w);
      fb[8 + v] = pack2(aI[16 + 2 * v] * tw.x - aR[16 + 2 * v] * tw.y, aI[16 + 2 * v + 1] * tw.z - aR[16 + 2 * v + 1] * tw.w);
    }
    fence_regs(fa); fence_regs(fb);
    wg_fence();
#pragma unroll
    for (int kk = 0; kk < 4; kk++) {
      wgmma_rs_n64<1, 1>(aR, fa[4 * kk], fa[4 * kk + 1], fa[4 * kk + 2], fa[4 * kk + 3], dT_n + kk * 128, kk != 0);
      wgmma_rs_n64<1, 1>(aI, fb[4 * kk], fb[4 * kk + 1], fb[4 * kk + 2], fb[4 * kk + 3], dT_n + kk * 128, kk != 0);
    }
    wg_commit();
    wg_wait<0>();
    fence_regs(aR); fence_regs(aI);
    TL(6 + 4 * rnd);
#pragma unroll
    for (int jb = 0; jb < 4; jb++) {
      const uint4 wa = *reinterpret_cast<const uint4*>(smem + SP_W + (2 * item) * 8192 + jb * 2048 + tid * 16);
      const uint4 wb = *reinterpret_cast<const uint4*>(smem + SP_W + (2 * item + 1) * 8192 + jb * 2048 + tid * 16);
      auto cm = [&](const float* a, uint32_t w0, uint32_t w1, int i, uint32_t& re, uint32_t& im) {
        const float r0_ = bf_lo(w0) * scale, i0 = bf_hi(w0) * scale, r1 = bf_lo(w1) * scale, i1 = bf_hi(w1) * scale;
        re = pack2(a[i] * r0_ - a[16 + i] * i0, a[i + 1] * r1 - a[16 + i + 1] * i1);
        im = pack2(a[i] * i0 + a[16 + i] * r0_, a[i + 1] * i1 + a[16 + i + 1] * r1);
      };
      cm(aR, wa.x, wa.y, 4 * jb, fa[2 * jb], fa[8 + 2 * jb]);
      cm(aR, wa.z, wa.w, 4 * jb + 2, fa[2 * jb + 1], fa[8 + 2 * jb + 1]);
      cm(aI, wb.x, wb.y, 4 * jb, fb[2 * jb], fb[8 + 2 * jb]);
      cm(aI, wb.z, wb.w, 4 * jb + 2, fb[2 * jb + 1], fb[8 + 2 * jb + 1]);
    }
    fence_regs(fa); fence_regs(fb);
    wg_fence();
#pragma unroll
    for (int kk = 0; kk < 4; kk++) {
      wgmma_rs_n64<1, 0>(aR, fa[4 * kk], fa[4 * kk + 1], fa[4 * kk + 2], fa[4 * kk + 3], dT_n + kk * 2, kk != 0);
      wgmma_rs_n64<1, 0>(aI, fb[4 * kk], fb[4 * kk + 1], fb[4 * kk + 2], fb[4 * kk + 3], dT_n + kk * 2, kk != 0);
    }
    wg_commit();
    wg_wait<0>();
    fence_regs(aR); fence_regs(aI);
#pragma unroll
    for (int v = 0; v < 8; v++) {
      const float4 tw = *reinterpret_cast<const float4*>(smem + SP_TW + v * 2048 + tid * 16);
      fa[v] = pack2(aR[2 * v] * tw.x - aR[16 + 2 * v] * tw.y, aR[2 * v + 1] * tw.z - aR[16 + 2 * v + 1] * tw.w);
      fb[v] = pack2(aR[16 + 2 * v] * tw.x + aR[2 * v] * tw.y, aR[16 + 2 * v + 1] * tw.z + aR[2 * v + 1] * tw.w);
      fa[8 + v] = pack2(aI[2 * v] * tw.x - aI[16 + 2 * v] * tw.y, aI[2 * v + 1] * tw.z - aI[16 + 2 * v + 1] * tw.w);
      fb[8 + v] = pack2(aI[16 + 2 * v] * tw.x + aI[2 * v] * tw.y, aI[16 + 2 * v + 1] * tw.z + aI[2 * v + 1] * tw.w);
    }
    bar_sync(1 + wg, 128);
    {
      const int row = 16 * warp + (lane & 7) + 8 * ((lane >> 3) & 1);
#pragma unroll
      for (int u = 0; u < 4; u++) {
        const uint32_t a = z + row * 128 + (((2 * u + (lane >> 4)) ^ (row & 7)) << 4);
        stmatrix_x4(a, fa[4 * u], fa[4 * u + 1], fa[4 * u + 2], fa[4 * u + 3]);
        stmatrix_x4(a + 8192, fb[4 * u], fb[4 * u + 1], fb[4 * u + 2], fb[4 * u + 3]);
      }
    }
    fence_async_smem();
    bar_sync(1 + wg, 128);
    TL(7 + 4 * rnd);
    {
      const uint64_t dr = mk_desc(z, 8192, 1024, 1), di = mk_desc(z + 8192, 8192, 1024, 1);
      wg_fence();
#pragma unroll
      for (int kk = 0; kk < 4; kk++) {
        wgmma_rs_n64<1, 1>(aR, fc[4 * kk], fc[4 * kk + 1], fc[4 * kk + 2], fc[4 * kk + 3], dr + kk * 128, kk != 0);
        wgmma_rs_n64<1, 1>(aI, fc[4 * kk], fc[4 * kk + 1], fc[4 * kk + 2], fc[4 * kk + 3], di + kk * 128, kk != 0);
      }
#pragma unroll
      for (int kk = 0; kk < 4; kk++) {
        wgmma_rs_n64<-1, 1>(aR, fs[4 * kk], fs[4 * kk + 1], fs[4 * kk + 2], fs[4 * kk + 3], di + kk * 128, 1);
        wgmma_rs_n64<1, 1>(aI, fs[4 * kk], fs[4 * kk + 1], fs[4 * kk + 2], fs[4 * kk + 3], dr + kk * 128, 1);
      }
      wg_commit();
      wg_wait<0>();
      fence_regs(aR); fence_regs(aI);
    }
    const int ka = kd0 + 2 * item, kb = ka + 1;
    int ra, ia, rb, ib;
    if (sc < 19) { ra = 2 * ka; ia = ra + 1; rb = kb < 224 ? 2 * kb : D_; ib = kb < 224 ? rb + 1 : D_; }
    else { ra = 0; rb = 1; ia = D_; ib = D_; }
#pragma unroll
    for (int h = 0; h < 2; h++) {
      const int off = 32 * (r0 + 8 * h) + 8 * q;
      auto st = [&](int jrow, const float* a) {
        if (jrow < D_)
          *reinterpret_cast<uint4*>(g_yt + (size_t)jrow * S_ + off) =
              make_uint4(pack2(a[2 * h], a[2 * h + 1]), pack2(a[4 + 2 * h], a[5 + 2 * h]), pack2(a[8 + 2 * h], a[9 + 2 * h]), pack2(a[12 + 2 * h], a[13 + 2 * h]));
      };
      st(ra, aR); st(rb, aR + 16); st(ia, aI); st(ib, aI + 16);
    }
    bar_sync(1 + wg, 128);
    if (tid == 0) {
      fence_gpu();
      red_add(&g_cnt_y[(ra >> 6) * 32], 1);
      if (sc < 19 && rb < D_) red_add(&g_cnt_y[(rb >> 6) * 32], 1);
    }
    TL(8 + 4 * rnd);
  }
  if (lane == 0) *my_epoch = epoch;
}

__global__ void __cluster_dims__(2, 1, 1) __launch_bounds__(384, 1)
fused_kernel(const __grid_constant__ Params p, const __nv_bfloat16* __restrict__ x, const __nv_bfloat16* __restrict__ w_r,
             const __nv_bfloat16* __restrict__ w_i, const __nv_bfloat16* __restrict__ gate_w,
             const __nv_bfloat16* __restrict__ wd, __nv_bfloat16* __restrict__ out) {
  extern __shared__ __align__(1024) uint8_t smem[];
  const uint32_t sb = smem_u32(smem);
  const int bid = blockIdx.x;
  TL(0);
  if (bid < NFFN) {
    const uint32_t rank = bid & 1;
    const int cl = bid >> 1, jj = cl % 7, mt = 2 * (cl / 7) + rank;
    if (threadIdx.x == 256) {
      for (int i = 0; i < NSTAGE; i++) {
        mbar_init(BAR_FULL(sb, i), 1);
        mbar_init(BAR_EMPTY(sb, i), 4);
        mbar_init(BAR_X(sb, i), 1);
        mbar_init(BAR_Y(sb, i), 1);
      }
      mbar_init(BAR_XFREE(sb), 2);
      asm volatile("fence.mbarrier_init.release.cluster;" ::: "memory");
      fence_async_smem();
      for (int kb = 0; kb < 7; kb++) {
        mbar_expect_tx(BAR_X(sb, kb), 16384);
        tma2d(sb + SM_X + kb * 16384, &p.x, 64 * kb, 128 * mt, BAR_X(sb, kb));
      }
    } else if (threadIdx.x == 288) {
      prefetch_tmap(&p.ct); prefetch_tmap(&p.wg); prefetch_tmap(&p.wu); prefetch_tmap(&p.wd); prefetch_tmap(&p.yt);
    }
    __syncwarp();
    asm volatile("barrier.cluster.arrive.relaxed.aligned;\nbarrier.cluster.wait.acquire.aligned;" ::: "memory");
    const int wg = __shfl_sync(0xffffffffu, threadIdx.x >> 7, 0);
    if (wg == 2) {
      asm volatile("setmaxnreg.dec.sync.aligned.u32 40;");
      ffn_producer(sb, p, (threadIdx.x >> 5) & 3, threadIdx.x & 31, mt, jj, rank);
    } else {
      asm volatile("setmaxnreg.inc.sync.aligned.u32 232;");
      ffn_consumer(sb, wg, threadIdx.x & 127, mt, jj, out);
    }
  } else {
    if (threadIdx.x == 0) {
      for (int i = 0; i < 6; i++) mbar_init(BAR_FULL(sb, i), 1);
      asm volatile("fence.mbarrier_init.release.cluster;" ::: "memory");
      prefetch_tmap(&p.x1);
    }
    spectral_cta(sb, smem, p, bid - NFFN, x, w_r, w_i, gate_w, wd);
  }
}

typedef CUresult (*EncodeFn)(CUtensorMap*, CUtensorMapDataType, cuuint32_t, void*, const cuuint64_t*, const cuuint64_t*,
                             const cuuint32_t*, const cuuint32_t*, CUtensorMapInterleave, CUtensorMapSwizzle,
                             CUtensorMapL2promotion, CUtensorMapFloatOOBfill);

void make_map(EncodeFn fn, CUtensorMap* m, const void* base, int rank, const cuuint64_t* dims, const cuuint64_t* strides,
              const cuuint32_t* box, CUtensorMapSwizzle sw) {
  const cuuint32_t es[3] = {1, 1, 1};
  fn(m, CU_TENSOR_MAP_DATA_TYPE_BFLOAT16, rank, const_cast<void*>(base), dims, strides, box, es,
     CU_TENSOR_MAP_INTERLEAVE_NONE, sw, CU_TENSOR_MAP_L2_PROMOTION_L2_256B, CU_TENSOR_MAP_FLOAT_OOB_FILL_NONE);
}

}

extern "C" void kernel_launch(void* const* d_in, const int* in_sizes, int n_in, void* d_out, int out_size) {
  const __nv_bfloat16* x = (const __nv_bfloat16*)d_in[0];
  const __nv_bfloat16* w_r = (const __nv_bfloat16*)d_in[1];
  const __nv_bfloat16* w_i = (const __nv_bfloat16*)d_in[2];
  const __nv_bfloat16* wg = (const __nv_bfloat16*)d_in[4];
  const __nv_bfloat16* wu = (const __nv_bfloat16*)d_in[5];
  const __nv_bfloat16* wd = (const __nv_bfloat16*)d_in[6];
  const __nv_bfloat16* gate_w = (const __nv_bfloat16*)d_in[7];

  void* fnp = nullptr;
  cudaDriverEntryPointQueryResult qr;
  cudaGetDriverEntryPoint("cuTensorMapEncodeTiled", &fnp, cudaEnableDefault, &qr);
  EncodeFn fn = (EncodeFn)fnp;
  void *ctab, *x1t, *yt;
  cudaGetSymbolAddress(&ctab, g_ctab);
  cudaGetSymbolAddress(&x1t, g_x1t);
  cudaGetSymbolAddress(&yt, g_yt);
  Params p;
  {
    const cuuint64_t d[2] = {D_, S_}, s[1] = {D_ * 2};
    const cuuint32_t b[2] = {64, 128};
    make_map(fn, &p.x, x, 2, d, s, b, CU_TENSOR_MAP_SWIZZLE_128B);
  }
  {
    const cuuint64_t d[3] = {64, D_, F_ / 64}, s[2] = {F_ * 2, 128};
    const cuuint32_t b[3] = {64, 32, 2};
    make_map(fn, &p.wg, wg, 3, d, s, b, CU_TENSOR_MAP_SWIZZLE_128B);
    make_map(fn, &p.wu, wu, 3, d, s, b, CU_TENSOR_MAP_SWIZZLE_128B);
  }
  {
    const cuuint64_t d[2] = {D_, F_}, s[1] = {D_ * 2};
    const cuuint32_t b[2] = {64, 64};
    make_map(fn, &p.wd, wd, 2, d, s, b, CU_TENSOR_MAP_SWIZZLE_128B);
  }
  {
    const cuuint64_t d[2] = {D_, D_}, s[1] = {D_ * 2};
    const cuuint32_t b[2] = {64, 64};
    make_map(fn, &p.ct, ctab, 2, d, s, b, CU_TENSOR_MAP_SWIZZLE_128B);
  }
  {
    const cuuint64_t d[2] = {32, D_ * 64}, s[1] = {64};
    const cuuint32_t b[2] = {32, 64};
    make_map(fn, &p.x1, x1t, 2, d, s, b, CU_TENSOR_MAP_SWIZZLE_64B);
  }
  {
    const cuuint64_t d[3] = {64, D_, S_ / 64}, s[2] = {S_ * 2, 128};
    const cuuint32_t b[3] = {64, 64, 2};
    make_map(fn, &p.yt, yt, 3, d, s, b, CU_TENSOR_MAP_SWIZZLE_128B);
  }
  cudaFuncSetAttribute(fused_kernel, cudaFuncAttributeMaxDynamicSharedMemorySize, SM_TOTAL);
  fused_kernel<<<NCTA, 384, SM_TOTAL, cudaStreamPerThread>>>(p, x, w_r, w_i, gate_w, wd, (__nv_bfloat16*)d_out);
}
```

```cpp
#include <cuda_runtime.h>
#include <cuda_bf16.h>
#include <cuda.h>
#include <stdint.h>

namespace {

constexpr int S_ = 2048, D_ = 448, F_ = 1792, DF_ = 225;
constexpr int NFFN = 112, NSPEC = 20, NCTA = NFFN + NSPEC;
constexpr int NSTAGE = 7, STAGE_BYTES = 16384;
constexpr int SM_X = 0, SM_RING = 114688, SM_BAR = 229376, SM_TOTAL = SM_BAR + 512;
constexpr int SP_Z = 0, SP_W = 98304, SP_TW = 196608, SP_T = 212992;
constexpr uint32_t SPIN_LIMIT = 1u << 20;

namespace tab {
constexpr double PI = 3.14159265358979323846264338327950288;
constexpr double csin(double x) {
  double t = x, s = x;
  for (int i = 1; i < 20; i++) { t = -t * x * x / ((2 * i) * (2 * i + 1)); s += t; }
  return s;
}
constexpr double ccos(double x) {
  double t = 1, s = 1;
  for (int i = 1; i < 20; i++) { t = -t * x * x / ((2 * i - 1) * (2 * i)); s += t; }
  return s;
}
constexpr uint32_t to_bf16(double v) {
  uint32_t sign = v < 0 ? 0x8000u : 0u;
  double a = v < 0 ? -v : v;
  if (a < 1e-12) return 0;
  int e = 0;
  while (a >= 2.0) { a /= 2; e++; }
  while (a < 1.0) { a *= 2; e--; }
  double m = a * 128.0;
  int mi = (int)m;
  double fr = m - mi;
  if (fr > 0.5 || (fr == 0.5 && (mi & 1))) mi++;
  if (mi == 256) { mi = 128; e++; }
  return sign | (uint32_t)((e + 127) << 7) | (uint32_t)(mi - 128);
}
struct Base { uint32_t v[448]; };
constexpr Base make_base() {
  Base b{};
  for (int m = 0; m < 448; m++) {
    int mm = m > 224 ? m - 448 : m;
    double ang = 2 * PI * mm / 448.0;
    b.v[m] = to_bf16(ccos(ang)) | (to_bf16(-csin(ang)) << 16);
  }
  return b;
}
constexpr Base base = make_base();
struct Row { uint32_t v[224]; };
constexpr Row make_row(int d) {
  Row r{};
  r.v[0] = 0x3f80u | ((d & 1) ? 0xbf800000u : 0x3f800000u);
  int m = 0;
  for (int c = 1; c < 224; c++) { m += d; if (m >= 448) m -= 448; r.v[c] = base.v[m]; }
  return r;
}
struct Table { Row r[448]; };
constexpr Table make_table() {
  Table t{};
  for (int d = 0; d < 448; d++) t.r[d] = make_row(d);
  return t;
}
struct Cs { double c[2048], s[2048]; };
constexpr Cs make_cs() {
  Cs t{};
  for (int m = 0; m <= 256; m++) {
    const double a = 2 * PI * m / 2048.0, c = ccos(a), s = csin(a);
    t.c[m] = c; t.s[m] = s;
    t.c[512 - m] = s; t.s[512 - m] = c;
  }
  for (int m = 513; m < 2048; m++) { t.c[m] = -t.s[m - 512]; t.s[m] = t.c[m - 512]; }
  return t;
}
constexpr Cs cs = make_cs();
struct Spec {
  float tw[4096];
  uint16_t t32[4096];
  uint32_t f64[4096];
};
constexpr Spec make_spec() {
  Spec t{};
  for (int i = 0; i < 2048; i++) {
    const int e = i & 1, th = (i >> 1) & 127, v = i >> 8;
    const int k1 = 16 * (th >> 5) + ((th & 31) >> 2) + 8 * (v & 1), n2 = 8 * (th & 3) + 2 * (v >> 1) + e;
    t.tw[2 * i] = (float)cs.c[n2 * k1];
    t.tw[2 * i + 1] = (float)cs.s[n2 * k1];
  }
  for (int row = 0; row < 64; row++)
    for (int col = 0; col < 64; col++) {
      const int c = row & 31, k2 = col & 31, n2 = 8 * ((c >> 1) & 3) + 2 * (c >> 3) + (c & 1), m = 64 * ((n2 * k2) & 31);
      const double v = (row >> 5) == (col >> 5) ? cs.c[m] : (row < 32 ? -cs.s[m] : cs.s[m]);
      t.t32[row * 64 + (((col >> 3) ^ (row & 7)) << 3) + (col & 7)] = (uint16_t)to_bf16(v);
    }
  for (int th = 0; th < 128; th++)
    for (int i = 0; i < 16; i++) {
      const int m = 16 * (th >> 5) + ((th & 31) >> 2) + 8 * (i & 1), k = 16 * (i >> 2) + 8 * ((i >> 1) & 1) + 2 * (th & 3);
      const int a0 = 32 * ((m * k) & 63), a1 = 32 * ((m * (k + 1)) & 63);
      t.f64[((i >> 2) * 128 + th) * 4 + (i & 3)] = to_bf16(cs.c[a0]) | (to_bf16(cs.c[a1]) << 16);
      t.f64[((4 + (i >> 2)) * 128 + th) * 4 + (i & 3)] = to_bf16(cs.s[a0]) | (to_bf16(cs.s[a1]) << 16);
    }
  return t;
}
}
}

__device__ __align__(1024) const tab::Table g_ctab = tab::make_table();
__device__ __align__(1024) const tab::Spec g_spec = tab::make_spec();

__device__ __align__(1024) __nv_bfloat16 g_x1t[D_ * S_];
__device__ __align__(1024) __nv_bfloat16 g_yt[D_ * S_];
__device__ __align__(1024) uint4 g_part[16 * 7 * 6 * 2 * 4 * 128];
__device__ __align__(1024) uint4 g_wt[114 * 1024];
__device__ float g_gate[S_];
__device__ uint32_t g_cnt_w[32];
__device__ uint32_t g_cnt_x1[7 * 32];
__device__ uint32_t g_cnt_y[7 * 32];
__device__ uint32_t g_cnt_p[16 * 7 * 2 * 8];
__device__ uint32_t g_epoch[NCTA * 12];
#define TL(i)

namespace {

struct Params {
  CUtensorMap x, wg, wu, wd, ct, x1, yt;
};

__device__ __forceinline__ uint32_t smem_u32(const void* p) { return (uint32_t)__cvta_generic_to_shared(p); }
__device__ __forceinline__ void mbar_init(uint32_t bar, uint32_t cnt) {
  asm volatile("mbarrier.init.shared::cta.b64 [%0], %1;" ::"r"(bar), "r"(cnt) : "memory");
}
__device__ __forceinline__ void mbar_expect_tx(uint32_t bar, uint32_t bytes) {
  asm volatile("mbarrier.arrive.expect_tx.shared::cta.b64 _, [%0], %1;" ::"r"(bar), "r"(bytes) : "memory");
}
__device__ __forceinline__ void mbar_arrive(uint32_t bar) {
  asm volatile("mbarrier.arrive.shared::cta.b64 _, [%0];" ::"r"(bar) : "memory");
}
__device__ __forceinline__ void mbar_arrive_cluster(uint32_t bar, uint32_t cta) {
  asm volatile("{\n.reg .b32 ra;\nmapa.shared::cluster.u32 ra, %0, %1;\n"
               "mbarrier.arrive.shared::cluster.b64 _, [ra];\n}" ::"r"(bar), "r"(cta) : "memory");
}
__device__ __forceinline__ void mbar_wait(uint32_t bar, uint32_t parity) {
  uint32_t ok, n = 0;
  do {
    asm volatile("{\n.reg .pred p;\nmbarrier.try_wait.parity.shared::cta.b64 p, [%1], %2;\nselp.u32 %0, 1, 0, p;\n}"
                 : "=r"(ok) : "r"(bar), "r"(parity) : "memory");
  } while (!ok && ++n < SPIN_LIMIT);
}
__device__ __forceinline__ void mbar_wait_cluster(uint32_t bar, uint32_t parity) {
  uint32_t ok, n = 0;
  do {
    asm volatile("{\n.reg .pred p;\nmbarrier.try_wait.parity.acquire.cluster.shared::cta.b64 p, [%1], %2;\nselp.u32 %0, 1, 0, p;\n}"
                 : "=r"(ok) : "r"(bar), "r"(parity) : "memory");
  } while (!ok && ++n < SPIN_LIMIT);
}
__device__ __forceinline__ void tma2d(uint32_t dst, const CUtensorMap* m, int c0, int c1, uint32_t bar) {
  asm volatile("cp.async.bulk.tensor.2d.shared::cluster.global.mbarrier::complete_tx::bytes [%0], [%1, {%3, %4}], [%2];"
               ::"r"(dst), "l"(m), "r"(bar), "r"(c0), "r"(c1) : "memory");
}
__device__ __forceinline__ void tma3d(uint32_t dst, const CUtensorMap* m, int c0, int c1, int c2, uint32_t bar) {
  asm volatile("cp.async.bulk.tensor.3d.shared::cluster.global.mbarrier::complete_tx::bytes [%0], [%1, {%3, %4, %5}], [%2];"
               ::"r"(dst), "l"(m), "r"(bar), "r"(c0), "r"(c1), "r"(c2) : "memory");
}
__device__ __forceinline__ void tma2d_mc(uint32_t dst, const CUtensorMap* m, int c0, int c1, uint32_t bar) {
  asm volatile("cp.async.bulk.tensor.2d.shared::cluster.global.mbarrier::complete_tx::bytes.multicast::cluster [%0], [%1, {%3, %4}], [%2], %5;"
               ::"r"(dst), "l"(m), "r"(bar), "r"(c0), "r"(c1), "h"((uint16_t)3) : "memory");
}
__device__ __forceinline__ void tma3d_mc(uint32_t dst, const CUtensorMap* m, int c0, int c1, int c2, uint32_t bar) {
  asm volatile("cp.async.bulk.tensor.3d.shared::cluster.global.mbarrier::complete_tx::bytes.multicast::cluster [%0], [%1, {%3, %4, %5}], [%2], %6;"
               ::"r"(dst), "l"(m), "r"(bar), "r"(c0), "r"(c1), "r"(c2), "h"((uint16_t)3) : "memory");
}
__device__ __forceinline__ void bulk_g2s(uint32_t dst, const void* src, uint32_t bytes, uint32_t bar) {
  asm volatile("cp.async.bulk.shared::cluster.global.mbarrier::complete_tx::bytes [%0], [%1], %2, [%3];"
               ::"r"(dst), "l"(src), "r"(bytes), "r"(bar) : "memory");
}
__device__ __forceinline__ void prefetch_tmap(const CUtensorMap* m) {
  asm volatile("prefetch.tensormap [%0];" ::"l"(m) : "memory");
}
__device__ __forceinline__ void l2_prefetch(const void* p, uint32_t bytes) {
  asm volatile("cp.async.bulk.prefetch.L2.global [%0], %1;" ::"l"(p), "r"(bytes) : "memory");
}
__device__ __forceinline__ void wg_fence() { asm volatile("wgmma.fence.sync.aligned;" ::: "memory"); }
__device__ __forceinline__ void wg_commit() { asm volatile("wgmma.commit_group.sync.aligned;" ::: "memory"); }
template <int N> __device__ __forceinline__ void wg_wait() { asm volatile("wgmma.wait_group.sync.aligned %0;" ::"n"(N) : "memory"); }
template <int N> __device__ __forceinline__ void fence_regs(float (&d)[N]) {
#pragma unroll
  for (int i = 0; i < N; i++) asm volatile("" : "+f"(d[i])::"memory");
}
template <int N> __device__ __forceinline__ void fence_regs(uint32_t (&d)[N]) {
#pragma unroll
  for (int i = 0; i < N; i++) asm volatile("" : "+r"(d[i])::"memory");
}
__device__ __forceinline__ void bar_sync(int id, int n) { asm volatile("bar.sync %0, %1;" ::"r"(id), "r"(n) : "memory"); }
__device__ __forceinline__ void bar_arrive(int id, int n) { asm volatile("bar.arrive %0, %1;" ::"r"(id), "r"(n) : "memory"); }
__device__ __forceinline__ void fence_gpu() { asm volatile("fence.acq_rel.gpu;" ::: "memory"); }
__device__ __forceinline__ void fence_async() { asm volatile("fence.proxy.async;" ::: "memory"); }
__device__ __forceinline__ void fence_async_smem() { asm volatile("fence.proxy.async.shared::cta;" ::: "memory"); }
__device__ __forceinline__ void red_add(uint32_t* p, uint32_t v) {
  asm volatile("red.relaxed.gpu.global.add.u32 [%0], %1;" ::"l"(p), "r"(v) : "memory");
}
__device__ __forceinline__ uint32_t ld_relaxed(const uint32_t* p) {
  uint32_t v;
  asm volatile("ld.relaxed.gpu.global.u32 %0, [%1];" : "=r"(v) : "l"(p) : "memory");
  return v;
}
__device__ __forceinline__ void wait_counter(const uint32_t* p, uint32_t target) {
  uint32_t v, n = 0;
  while (true) {
    asm volatile("ld.acquire.gpu.global.u32 %0, [%1];" : "=r"(v) : "l"(p) : "memory");
    if ((int32_t)(v - target) >= 0 || ++n > SPIN_LIMIT) break;
  }
}
__device__ __forceinline__ uint4 ld_cg(const uint4* p) {
  uint4 v;
  asm volatile("ld.global.cg.v4.u32 {%0, %1, %2, %3}, [%4];" : "=r"(v.x), "=r"(v.y), "=r"(v.z), "=r"(v.w) : "l"(p) : "memory");
  return v;
}
__device__ __forceinline__ uint32_t pack2(float lo, float hi) {
  uint32_t r;
  asm("cvt.rn.bf16x2.f32 %0, %1, %2;" : "=r"(r) : "f"(hi), "f"(lo));
  return r;
}
__device__ __forceinline__ float bf_lo(uint32_t v) { return __uint_as_float(v << 16); }
__device__ __forceinline__ float bf_hi(uint32_t v) { return __uint_as_float(v & 0xffff0000u); }
__device__ __forceinline__ float bf_round(float v) { return bf_lo(pack2(v, 0.f)); }
__device__ __forceinline__ float tanh_fast(float v) {
  float r;
  asm("tanh.approx.f32 %0, %1;" : "=f"(r) : "f"(v));
  return r;
}
__device__ __forceinline__ uint64_t mk_desc(uint32_t addr, uint32_t lbo, uint32_t sbo, uint32_t mode) {
  return (uint64_t)((addr & 0x3FFFF) >> 4) | ((uint64_t)(lbo >> 4) << 16) | ((uint64_t)(sbo >> 4) << 32) | ((uint64_t)mode << 62);
}
__device__ __forceinline__ void stmatrix_x4(uint32_t addr, uint32_t r0, uint32_t r1, uint32_t r2, uint32_t r3) {
  asm volatile("stmatrix.sync.aligned.m8n8.x4.shared.b16 [%0], {%1, %2, %3, %4};" ::"r"(addr), "r"(r0), "r"(r1), "r"(r2), "r"(r3) : "memory");
}

template <int TA, int TB>
__device__ __forceinline__ void wgmma_ss_n256(float (&d)[128], uint64_t da, uint64_t db, int sd) {
  asm volatile("{\n.reg .pred p;\nsetp.ne.b32 p, %130, 0;\n"
      "wgmma.mma_async.sync.aligned.m64n256k16.f32.bf16.bf16 {"
      "%0, %1, %2, %3, %4, %5, %6, %7, %8, %9, %10, %11, %12, %13, %14, %15, %16, %17, %18, %19, %20, %21, %22, %23, "
      "%24, %25, %26, %27, %28, %29, %30, %31, %32, %33, %34, %35, %36, %37, %38, %39, %40, %41, %42, %43, %44, %45, "
      "%46, %47, %48, %49, %50, %51, %52, %53, %54, %55, %56, %57, %58, %59, %60, %61, %62, %63, %64, %65, %66, %67, "
      "%68, %69, %70, %71, %72, %73, %74, %75, %76, %77, %78, %79, %80, %81, %82, %83, %84, %85, %86, %87, %88, %89, "
      "%90, %91, %92, %93, %94, %95, %96, %97, %98, %99, %100, %101, %102, %103, %104, %105, %106, %107, %108, %109, "
      "%110, %111, %112, %113, %114, %115, %116, %117, %118, %119, %120, %121, %122, %123, %124, %125, %126, %127"
      "}, %128, %129, p, 1, 1, %131, %132;\n}\n"
      : "+f"(d[0]), "+f"(d[1]), "+f"(d[2]), "+f"(d[3]), "+f"(d[4]), "+f"(d[5]), "+f"(d[6]), "+f"(d[7]), "+f"(d[8]),
        "+f"(d[9]), "+f"(d[10]), "+f"(d[11]), "+f"(d[12]), "+f"(d[13]), "+f"(d[14]), "+f"(d[15]), "+f"(d[16]),
        "+f"(d[17]), "+f"(d[18]), "+f"(d[19]), "+f"(d[20]), "+f"(d[21]), "+f"(d[22]), "+f"(d[23]), "+f"(d[24]),
        "+f"(d[25]), "+f"(d[26]), "+f"(d[27]), "+f"(d[28]), "+f"(d[29]), "+f"(d[30]), "+f"(d[31]), "+f"(d[32]),
        "+f"(d[33]), "+f"(d[34]), "+f"(d[35]), "+f"(d[36]), "+f"(d[37]), "+f"(d[38]), "+f"(d[39]), "+f"(d[40]),
        "+f"(d[41]), "+f"(d[42]), "+f"(d[43]), "+f"(d[44]), "+f"(d[45]), "+f"(d[46]), "+f"(d[47]), "+f"(d[48]),
        "+f"(d[49]), "+f"(d[50]), "+f"(d[51]), "+f"(d[52]), "+f"(d[53]), "+f"(d[54]), "+f"(d[55]), "+f"(d[56]),
        "+f"(d[57]), "+f"(d[58]), "+f"(d[59]), "+f"(d[60]), "+f"(d[61]), "+f"(d[62]), "+f"(d[63]), "+f"(d[64]),
        "+f"(d[65]), "+f"(d[66]), "+f"(d[67]), "+f"(d[68]), "+f"(d[69]), "+f"(d[70]), "+f"(d[71]), "+f"(d[72]),
        "+f"(d[73]), "+f"(d[74]), "+f"(d[75]), "+f"(d[76]), "+f"(d[77]), "+f"(d[78]), "+f"(d[79]), "+f"(d[80]),
        "+f"(d[81]), "+f"(d[82]), "+f"(d[83]), "+f"(d[84]), "+f"(d[85]), "+f"(d[86]), "+f"(d[87]), "+f"(d[88]),
        "+f"(d[89]), "+f"(d[90]), "+f"(d[91]), "+f"(d[92]), "+f"(d[93]), "+f"(d[94]), "+f"(d[95]), "+f"(d[96]),
        "+f"(d[97]), "+f"(d[98]), "+f"(d[99]), "+f"(d[100]), "+f"(d[101]), "+f"(d[102]), "+f"(d[103]), "+f"(d[104]),
        "+f"(d[105]), "+f"(d[106]), "+f"(d[107]), "+f"(d[108]), "+f"(d[109]), "+f"(d[110]), "+f"(d[111]),
        "+f"(d[112]), "+f"(d[113]), "+f"(d[114]), "+f"(d[115]), "+f"(d[116]), "+f"(d[117]), "+f"(d[118]),
        "+f"(d[119]), "+f"(d[120]), "+f"(d[121]), "+f"(d[122]), "+f"(d[123]), "+f"(d[124]), "+f"(d[125]),
        "+f"(d[126]), "+f"(d[127])
      : "l"(da), "l"(db), "r"(sd), "n"(TA), "n"(TB));
}
template <int TA, int TB>
__device__ __forceinline__ void wgmma_ss_n128(float (&d)[64], uint64_t da, uint64_t db, int sd) {
  asm volatile("{\n.reg .pred p;\nsetp.ne.b32 p, %66, 0;\n"
      "wgmma.mma_async.sync.aligned.m64n128k16.f32.bf16.bf16 {"
      "%0, %1, %2, %3, %4, %5, %6, %7, %8, %9, %10, %11, %12, %13, %14, %15, %16, %17, %18, %19, %20, %21, %22, %23, "
      "%24, %25, %26, %27, %28, %29, %30, %31, %32, %33, %34, %35, %36, %37, %38, %39, %40, %41, %42, %43, %44, %45, "
      "%46, %47, %48, %49, %50, %51, %52, %53, %54, %55, %56, %57, %58, %59, %60, %61, %62, %63"
      "}, %64, %65, p, 1, 1, %67, %68;\n}\n"
      : "+f"(d[0]), "+f"(d[1]), "+f"(d[2]), "+f"(d[3]), "+f"(d[4]), "+f"(d[5]), "+f"(d[6]), "+f"(d[7]), "+f"(d[8]),
        "+f"(d[9]), "+f"(d[10]), "+f"(d[11]), "+f"(d[12]), "+f"(d[13]), "+f"(d[14]), "+f"(d[15]), "+f"(d[16]),
        "+f"(d[17]), "+f"(d[18]), "+f"(d[19]), "+f"(d[20]), "+f"(d[21]), "+f"(d[22]), "+f"(d[23]), "+f"(d[24]),
        "+f"(d[25]), "+f"(d[26]), "+f"(d[27]), "+f"(d[28]), "+f"(d[29]), "+f"(d[30]), "+f"(d[31]), "+f"(d[32]),
        "+f"(d[33]), "+f"(d[34]), "+f"(d[35]), "+f"(d[36]), "+f"(d[37]), "+f"(d[38]), "+f"(d[39]), "+f"(d[40]),
        "+f"(d[41]), "+f"(d[42]), "+f"(d[43]), "+f"(d[44]), "+f"(d[45]), "+f"(d[46]), "+f"(d[47]), "+f"(d[48]),
        "+f"(d[49]), "+f"(d[50]), "+f"(d[51]), "+f"(d[52]), "+f"(d[53]), "+f"(d[54]), "+f"(d[55]), "+f"(d[56]),
        "+f"(d[57]), "+f"(d[58]), "+f"(d[59]), "+f"(d[60]), "+f"(d[61]), "+f"(d[62]), "+f"(d[63])
      : "l"(da), "l"(db), "r"(sd), "n"(TA), "n"(TB));
}
template <int TA, int TB>
__device__ __forceinline__ void wgmma_ss_n64(float (&d)[32], uint64_t da, uint64_t db, int sd) {
  asm volatile("{\n.reg .pred p;\nsetp.ne.b32 p, %34, 0;\n"
      "wgmma.mma_async.sync.aligned.m64n64k16.f32.bf16.bf16 {"
      "%0, %1, %2, %3, %4, %5, %6, %7, %8, %9, %10, %11, %12, %13, %14, %15, %16, %17, %18, %19, %20, %21, %22, %23, "
      "%24, %25, %26, %27, %28, %29, %30, %31"
      "}, %32, %33, p, 1, 1, %35, %36;\n}\n"
      : "+f"(d[0]), "+f"(d[1]), "+f"(d[2]), "+f"(d[3]), "+f"(d[4]), "+f"(d[5]), "+f"(d[6]), "+f"(d[7]), "+f"(d[8]),
        "+f"(d[9]), "+f"(d[10]), "+f"(d[11]), "+f"(d[12]), "+f"(d[13]), "+f"(d[14]), "+f"(d[15]), "+f"(d[16]),
        "+f"(d[17]), "+f"(d[18]), "+f"(d[19]), "+f"(d[20]), "+f"(d[21]), "+f"(d[22]), "+f"(d[23]), "+f"(d[24]),
        "+f"(d[25]), "+f"(d[26]), "+f"(d[27]), "+f"(d[28]), "+f"(d[29]), "+f"(d[30]), "+f"(d[31])
      : "l"(da), "l"(db), "r"(sd), "n"(TA), "n"(TB));
}
template <int SA, int TB>
__device__ __forceinline__ void wgmma_rs_n64(float (&d)[32], uint32_t a0, uint32_t a1, uint32_t a2, uint32_t a3, uint64_t db, int sd) {
  asm volatile("{\n.reg .pred p;\nsetp.ne.b32 p, %37, 0;\n"
      "wgmma.mma_async.sync.aligned.m64n64k16.f32.bf16.bf16 {"
      "%0, %1, %2, %3, %4, %5, %6, %7, %8, %9, %10, %11, %12, %13, %14, %15, %16, %17, %18, %19, %20, %21, %22, %23, "
      "%24, %25, %26, %27, %28, %29, %30, %31"
      "}, {%32, %33, %34, %35}, %36, p, %38, 1, %39;\n}\n"
      : "+f"(d[0]), "+f"(d[1]), "+f"(d[2]), "+f"(d[3]), "+f"(d[4]), "+f"(d[5]), "+f"(d[6]), "+f"(d[7]), "+f"(d[8]),
        "+f"(d[9]), "+f"(d[10]), "+f"(d[11]), "+f"(d[12]), "+f"(d[13]), "+f"(d[14]), "+f"(d[15]), "+f"(d[16]),
        "+f"(d[17]), "+f"(d[18]), "+f"(d[19]), "+f"(d[20]), "+f"(d[21]), "+f"(d[22]), "+f"(d[23]), "+f"(d[24]),
        "+f"(d[25]), "+f"(d[26]), "+f"(d[27]), "+f"(d[28]), "+f"(d[29]), "+f"(d[30]), "+f"(d[31])
      : "r"(a0), "r"(a1), "r"(a2), "r"(a3), "l"(db), "r"(sd), "n"(SA), "n"(TB));
}

__device__ __forceinline__ uint32_t BAR_FULL(uint32_t sb, int i) { return sb + SM_BAR + 8 * i; }
__device__ __forceinline__ uint32_t BAR_EMPTY(uint32_t sb, int i) { return sb + SM_BAR + 64 + 8 * i; }
__device__ __forceinline__ uint32_t BAR_X(uint32_t sb, int i) { return sb + SM_BAR + 128 + 8 * i; }
__device__ __forceinline__ uint32_t BAR_Y(uint32_t sb, int i) { return sb + SM_BAR + 192 + 8 * i; }
__device__ __forceinline__ uint32_t BAR_XFREE(uint32_t sb) { return sb + SM_BAR + 256; }

#define CMASK 0x194u
#define SKEW 3
constexpr int Q_G1B = 18, Q_G2 = 32, Q_P3 = 46, Q_END = 50;

struct Ring {
  uint32_t slot, phase;
  __device__ __forceinline__ void next() { if (++slot == NSTAGE) { slot = 0; phase ^= 1; } }
};

__device__ __forceinline__ void release_slot(uint32_t sb, uint32_t slot, int tid, int times) {
  if (tid < 2 * times) mbar_arrive_cluster(BAR_EMPTY(sb, slot), tid & 1);
}

template <int NT> struct Slab {
  static constexpr int IT = (904 + NT - 1) / NT;
  uint32_t v[IT][8];
  __device__ __forceinline__ void load(const __nv_bfloat16* w_r, const __nv_bfloat16* w_i, int sl, int t) {
    const uint16_t* wr = reinterpret_cast<const uint16_t*>(w_r) + (16 * sl + (t & 7)) * DF_ + 2 * (t >> 3);
    const uint16_t* wi = reinterpret_cast<const uint16_t*>(w_i) + (16 * sl + (t & 7)) * DF_ + 2 * (t >> 3);
#pragma unroll
    for (int i = 0; i < IT; i++) {
      const int c = t + NT * i, o = NT / 4 * i;
      const bool a = c < 904, b = c < 896;
#pragma unroll
      for (int h = 0; h < 2; h++) {
        v[i][4 * h + 0] = a ? __ldg(wr + o + h * 8 * DF_) : 0;
        v[i][4 * h + 1] = b ? __ldg(wr + o + h * 8 * DF_ + 1) : 0;
        v[i][4 * h + 2] = a ? __ldg(wi + o + h * 8 * DF_) : 0;
        v[i][4 * h + 3] = b ? __ldg(wi + o + h * 8 * DF_ + 1) : 0;
      }
    }
  }
  __device__ __forceinline__ void store(int sl, int t) {
    uint4* dst = g_wt + (t >> 3) * 1024 + sl * 8 + ((t & 7) ^ ((sl >> 2) & 6));
#pragma unroll
    for (int i = 0; i < IT; i++)
      if (t + NT * i < 904)
        dst[NT / 8 * i * 1024] = make_uint4(v[i][0] | (v[i][1] << 16), v[i][2] | (v[i][3] << 16), v[i][4] | (v[i][5] << 16), v[i][6] | (v[i][7] << 16));
  }
};

__device__ __forceinline__ void ffn_consumer(uint32_t sb, int wg, int tid, int mt, int jj, __nv_bfloat16* __restrict__ out) {
  const int lane = tid & 31, warp = tid >> 5, q = lane & 3, r0 = 16 * warp + (lane >> 2);
  uint32_t* const my_epoch = &g_epoch[blockIdx.x * 12 + (threadIdx.x >> 5)];
  const uint32_t epoch = ld_relaxed(my_epoch) + 1;
  Ring rg{0, 0};
  uint32_t u[64];
  float acc[128];
  uint32_t prev = 0, cmask = CMASK;
  int st = 0;
  auto g1_stage = [&](uint32_t slot, int s) {
    const uint64_t da = mk_desc(sb + SM_X + (s >> 1) * 16384 + wg * 8192 + (s & 1) * 64, 16, 1024, 1);
    const uint64_t db = mk_desc(sb + SM_RING + slot * STAGE_BYTES, 4096, 1024, 1);
    wg_fence();
    wgmma_ss_n256<0, 1>(acc, da, db, s != 0);
    wgmma_ss_n256<0, 1>(acc, da + 2, db + 128, 1);
    wg_commit();
  };
  if (wg == 1) {
    float ap[64];
    constexpr int NPRE = 33 - __builtin_clz(CMASK);
#pragma unroll
    for (int qi = 0; qi < NPRE; qi++) {
      const int slot = qi % NSTAGE, nc = __builtin_popcount(CMASK & ((1u << qi) - 1));
      mbar_wait(BAR_FULL(sb, slot), (qi / NSTAGE) & 1);
      if ((CMASK >> qi) & 1) {
#pragma unroll
        for (int kb = 2 * nc; kb < 2 * nc + 2 && kb < 7; kb++) {
          const uint64_t da = mk_desc(sb + SM_RING + slot * STAGE_BYTES + (kb & 1) * 8192, 8192, 1024, 1);
          const uint64_t db = mk_desc(sb + SM_X + kb * 16384, 16, 1024, 1);
          mbar_wait(BAR_X(sb, kb), 0);
          TL(16 + kb);
          wg_fence();
#pragma unroll
          for (int kk = 0; kk < 4; kk++) wgmma_ss_n128<1, 0>(ap, da + kk * 128, db + kk * 2, (kb | kk) != 0);
          wg_commit();
        }
      } else {
        if (((qi - nc) & 1) == 0 && qi - nc >= 4 * nc) mbar_wait(BAR_X(sb, (qi - nc) >> 1), 0);
        TL(32 + qi - nc);
        g1_stage(slot, qi - nc);
      }
      if (qi > 0) {
        wg_wait<1>();
        release_slot(sb, (qi - 1) % NSTAGE, tid, ((CMASK >> (qi - 1)) & 1) ? 2 : 1);
      }
    }
    fence_regs(ap);
    TL(2);
#pragma unroll
    for (int h = 0; h < 2; h++) {
      uint4* dst = reinterpret_cast<uint4*>(g_x1t + (size_t)(64 * jj + r0 + 8 * h) * S_ + 128 * mt + 8 * q);
#pragma unroll
      for (int t = 0; t < 4; t++)
        dst[4 * t] = make_uint4(pack2(ap[16 * t + 2 * h], ap[16 * t + 2 * h + 1]), pack2(ap[16 * t + 4 + 2 * h], ap[16 * t + 5 + 2 * h]),
                                pack2(ap[16 * t + 8 + 2 * h], ap[16 * t + 9 + 2 * h]), pack2(ap[16 * t + 12 + 2 * h], ap[16 * t + 13 + 2 * h]));
    }
    bar_arrive(7, 160);
    st = NPRE - 4; cmask = 0; prev = (NPRE - 1) % NSTAGE;
    rg.slot = NPRE % NSTAGE; rg.phase = (NPRE / NSTAGE) & 1;
  }
#pragma unroll 1
  for (int pass = 0; pass < 2; pass++) {
#pragma unroll 1
    for (; st < 14; st++) {
      while (cmask & 1) { cmask >>= 1; rg.next(); }
      cmask >>= 1;
      if (pass == 0 && (st & 1) == 0) mbar_wait(BAR_X(sb, st >> 1), 0);
      if (st == 14 - SKEW && wg == 1) bar_sync(9 + pass, 256);
      mbar_wait(BAR_FULL(sb, rg.slot), rg.phase);
      TL(32 + 14 * pass + st);
      g1_stage(rg.slot, st);
      wg_wait<1>();
      if (st > 0) release_slot(sb, prev, tid, 1);
      prev = rg.slot;
      rg.next();
    }
    st = 0;
    if (wg == 0) bar_arrive(9 + pass, 256);
    wg_wait<0>();
    fence_regs(acc);
    release_slot(sb, prev, tid, 1);
    if (pass == 1 && tid == 0) mbar_arrive(BAR_XFREE(sb));
    TL(3 + 2 * pass);
#pragma unroll
    for (int i = 0; i < 32; i++) {
      const float g0 = 0.5f * acc[2 * i], g1 = 0.5f * acc[2 * i + 1];
      const float s0 = fmaf(g0, tanh_fast(g0), g0), s1 = fmaf(g1, tanh_fast(g1), g1);
      u[32 + i] = pack2(s0 * acc[64 + 2 * i], s1 * acc[64 + 2 * i + 1]);
    }
    if (pass == 0) {
#pragma unroll
      for (int i = 0; i < 32; i++) u[i] = u[32 + i];
    }
    TL(4 + 2 * pass);
  }
  fence_regs(u);
  float accA[32], accB[32];
  rg.slot = Q_G2 % NSTAGE; rg.phase = (Q_G2 / NSTAGE) & 1;
  auto stage = [&](float (&acc)[32], int st) {
    mbar_wait(BAR_FULL(sb, rg.slot), rg.phase);
    const uint64_t db = mk_desc(sb + SM_RING + rg.slot * STAGE_BYTES, 8192, 1024, 1);
    wg_fence();
#pragma unroll
    for (int kk = 0; kk < 8; kk++) {
      const uint32_t* a = u + 32 * st + 4 * kk;
      wgmma_rs_n64<1, 1>(acc, a[0], a[1], a[2], a[3], db + kk * 128, (st | kk) != 0);
    }
    wg_commit();
  };
  auto retire = [&](bool rel) {
    wg_wait<1>();
    if (rel) release_slot(sb, prev, tid, 1);
    prev = rg.slot;
    rg.next();
  };
  auto put = [&](float (&acc)[32], int c) {
    fence_regs(acc);
    int o = jj + 1 + c;
    if (o >= 7) o -= 7;
    uint4* dst = g_part + ((((mt * 7 + o) * 6 + c) * 2 + wg) * 4) * 128 + tid;
#pragma unroll
    for (int v = 0; v < 4; v++) {
      const float* a = acc + 8 * v;
      dst[v * 128] = make_uint4(pack2(a[0], a[1]), pack2(a[2], a[3]), pack2(a[4], a[5]), pack2(a[6], a[7]));
    }
  };
#pragma unroll
  for (int c2 = 0; c2 < 4; c2++) {
    stage(accA, 0);
    retire(c2 == 1 || c2 == 2);
    stage(accA, 1);
    if (c2 > 0) { put(accB, 2 * c2 - 1); bar_arrive(3 * wg + c2, 160); }
    TL(7 + c2);
    if (c2 == 3) break;
    retire(true);
    stage(accB, 0);
    retire(true);
    stage(accB, 1);
    put(accA, 2 * c2);
    retire(true);
  }
  rg.next();
#pragma unroll 1
  for (int kb = 0; kb < 7; kb++) {
    if ((kb & 1) == 0) mbar_wait(BAR_FULL(sb, rg.slot), rg.phase);
    mbar_wait(BAR_Y(sb, kb), 0);
    const uint64_t da = mk_desc(sb + SM_X + kb * 16384 + wg * 8192, 8192, 1024, 1);
    const uint64_t db = mk_desc(sb + SM_RING + rg.slot * STAGE_BYTES + (kb & 1) * 8192, 16, 1024, 1);
    wg_fence();
#pragma unroll
    for (int kk = 0; kk < 4; kk++) wgmma_ss_n64<1, 0>(accB, da + kk * 128, db + kk * 2, (kb | kk) != 0);
    wg_commit();
    if (kb & 1) rg.next();
  }
  TL(11);
  const int row = 128 * mt + 64 * wg + r0;
  const float ga0 = __ldcg(&g_gate[row]), ga1 = __ldcg(&g_gate[row + 8]);
  float sum[32];
#pragma unroll
  for (int i = 0; i < 32; i++) sum[i] = 0.f;
  const uint4* src = g_part + (((mt * 7 + jj) * 6 * 2 + wg) * 4) * 128 + tid;
#pragma unroll 1
  for (int c = 0; c < 3; c++) {
    if (lane == 0) wait_counter(&g_cnt_p[((mt * 7 + jj) * 2 + wg) * 8 + c], epoch * 2);
    __syncwarp();
    TL(24 + c);
    uint4 pv[8];
#pragma unroll
    for (int i = 0; i < 8; i++) pv[i] = ld_cg(src + ((2 * c + (i >> 2)) * 8 + (i & 3)) * 128);
#pragma unroll
    for (int i = 0; i < 8; i++) {
      const int v = i & 3;
      sum[8 * v + 0] += bf_lo(pv[i].x); sum[8 * v + 1] += bf_hi(pv[i].x);
      sum[8 * v + 2] += bf_lo(pv[i].y); sum[8 * v + 3] += bf_hi(pv[i].y);
      sum[8 * v + 4] += bf_lo(pv[i].z); sum[8 * v + 5] += bf_hi(pv[i].z);
      sum[8 * v + 6] += bf_lo(pv[i].w); sum[8 * v + 7] += bf_hi(pv[i].w);
    }
  }
  TL(12);
  wg_wait<0>();
  fence_regs(accA);
  fence_regs(accB);
  TL(13);
  const float gb0 = bf_round(1.f - ga0), gb1 = bf_round(1.f - ga1);
  const float gs0 = ga0 * (2.f / (float)(S_ * D_)), gs1 = ga1 * (2.f / (float)(S_ * D_));
  uint32_t* o0 = reinterpret_cast<uint32_t*>(out + (size_t)row * D_ + 64 * jj + 2 * q);
  uint32_t* o1 = o0 + 8 * D_ / 2;
#pragma unroll
  for (int jb = 0; jb < 8; jb++) {
    o0[4 * jb] = pack2(fmaf(gs0, accB[4 * jb], gb0 * (accA[4 * jb] + sum[4 * jb])),
                       fmaf(gs0, accB[4 * jb + 1], gb0 * (accA[4 * jb + 1] + sum[4 * jb + 1])));
    o1[4 * jb] = pack2(fmaf(gs1, accB[4 * jb + 2], gb1 * (accA[4 * jb + 2] + sum[4 * jb + 2])),
                       fmaf(gs1, accB[4 * jb + 3], gb1 * (accA[4 * jb + 3] + sum[4 * jb + 3])));
  }
  if (lane == 0) *my_epoch = epoch;
  TL(14);
}

__device__ __forceinline__ void ffn_producer(uint32_t sb, const Params& p, int warp, int lane, int mt, int jj, uint32_t rank) {
  if (warp < 2) {
    if (lane == 0) {
      uint32_t slot = warp, phase = 1;
#pragma unroll 1
      for (int qi = warp; qi < Q_END; qi += 2) {
        const CUtensorMap* m;
        int c0, c1, c2 = -1;
        bool half = false;
        if (qi < Q_G2) {
          const int nc = __popc(CMASK & ((1u << qi) - 1));
          if ((CMASK >> qi) & 1) {
            m = &p.ct; c0 = 64 * jj; c1 = 128 * nc + 64 * rank; half = nc == 3;
          } else {
            const int pass = qi >= Q_G1B;
            m = rank ? &p.wu : &p.wg; c0 = 0; c1 = 32 * (qi - nc - 14 * pass); c2 = 4 * jj + 2 * pass;
          }
        } else if (qi < Q_P3) {
          int o = jj + 1 + ((qi - Q_G2) >> 1);
          if (o >= 7) o -= 7;
          m = &p.wd; c0 = 64 * o; c1 = 256 * jj + 128 * (qi & 1) + 64 * rank;
        } else {
          m = &p.ct; c0 = 128 * (qi - Q_P3) + 64 * rank; c1 = 64 * jj; half = qi == Q_END - 1;
        }
        const uint32_t bar = BAR_FULL(sb, slot);
        const uint32_t dst = sb + SM_RING + slot * STAGE_BYTES + rank * 8192;
        if (qi >= NSTAGE) mbar_wait_cluster(BAR_EMPTY(sb, slot), phase);
        TL(10 + qi);
        mbar_expect_tx(bar, half ? 8192 : 16384);
        if (c2 >= 0) tma3d_mc(dst, m, c0, c1, c2, bar);
        else if (!(half && rank)) tma2d_mc(dst, m, c0, c1, bar);
        slot += 2;
        if (slot >= NSTAGE) { slot -= NSTAGE; phase ^= 1; }
      }
    }
  } else {
    const int wg = warp - 2;
    if (wg == 0) {
      if (lane == 0) {
#pragma unroll 1
        for (int kb = 1; kb < 7; kb++) {
          mbar_expect_tx(BAR_X(sb, kb), 16384);
          tma2d(sb + SM_X + kb * 16384, &p.x, 64 * kb, 128 * mt, BAR_X(sb, kb));
        }
      }
      TL(2);
      uint32_t* const my_epoch = &g_epoch[blockIdx.x * 12 + 10];
      const uint32_t epoch = ld_relaxed(my_epoch) + 1;
      mbar_wait(BAR_XFREE(sb), 0);
      TL(3);
      bool todo = lane < 7;
      uint32_t n = 0;
      while (__any_sync(0xffffffffu, todo)) {
        if (todo) {
          uint32_t v;
          asm volatile("ld.acquire.gpu.global.u32 %0, [%1];" : "=r"(v) : "l"(&g_cnt_y[lane * 32]) : "memory");
          if ((int32_t)(v - epoch * (lane ? 16 : 17)) >= 0 || ++n > SPIN_LIMIT) {
            fence_async();
            mbar_expect_tx(BAR_Y(sb, lane), 16384);
            tma3d(sb + SM_X + lane * 16384, &p.yt, 0, 64 * lane, 2 * mt, BAR_Y(sb, lane));
            todo = false;
          }
        }
      }
      TL(4);
      if (lane == 0) *my_epoch = epoch;
    } else {
      bar_sync(8, 288);
      if (lane == 0) { fence_gpu(); red_add(&g_cnt_w[0], 1); }
      TL(2);
      bar_sync(7, 160);
      if (lane == 0) { fence_gpu(); red_add(&g_cnt_x1[jj * 32], 1); }
      TL(3);
    }
#pragma unroll 1
    for (int c = 0; c < 3; c++) {
      bar_sync(1 + 3 * wg + c, 160);
      if (lane < 2) {
        int o = jj + 1 + 2 * c + lane;
        if (o >= 7) o -= 7;
        fence_gpu();
        red_add(&g_cnt_p[((mt * 7 + o) * 2 + wg) * 8 + c], 1);
      }
      TL(5 + c);
    }
  }
}

__device__ __forceinline__ void spectral_cta(uint32_t sb, uint8_t* smem, const Params& p, int sc,
                                             const __nv_bfloat16* __restrict__ x, const __nv_bfloat16* __restrict__ w_r,
                                             const __nv_bfloat16* __restrict__ w_i, const __nv_bfloat16* __restrict__ gate_w,
                                             const __nv_bfloat16* __restrict__ wgt, const __nv_bfloat16* __restrict__ wup,
                                             const __nv_bfloat16* __restrict__ wd) {
  const int t384 = threadIdx.x, lane = t384 & 31, warp12 = t384 >> 5, wg = __shfl_sync(0xffffffffu, t384 >> 7, 0), tid = t384 & 127;
  const int warp = tid >> 5, q = lane & 3, r0 = 16 * warp + (lane >> 2);
  uint32_t* const my_epoch = &g_epoch[blockIdx.x * 12 + warp12];
  const uint32_t epoch = ld_relaxed(my_epoch) + 1;
  if (sc < 16) {
    Slab<384> sl;
    sl.load(w_r, w_i, NFFN + sc, t384);
    sl.store(NFFN + sc, t384);
  }
  if (t384 == 0) {
    for (int i = 0; i < 6; i++) { mbar_init(BAR_FULL(sb, i), 1); mbar_init(BAR_EMPTY(sb, i), 1); }
    mbar_init(BAR_X(sb, 0), 1);
    asm volatile("fence.mbarrier_init.release.cluster;" ::: "memory");
    fence_async_smem();
    mbar_expect_tx(BAR_X(sb, 0), 24576);
    bulk_g2s(sb + SP_TW, &g_spec, 24576, BAR_X(sb, 0));
    prefetch_tmap(&p.x1);
  }
  __syncthreads();
  if (t384 == 0 && sc < 16) { fence_gpu(); red_add(&g_cnt_w[0], 1); }
  TL(1);
  if (sc < 19) {
    const uint4* gw4 = reinterpret_cast<const uint4*>(gate_w);
    const uint4 ga = __ldg(gw4 + lane), gb = lane < 24 ? __ldg(gw4 + 32 + lane) : make_uint4(0, 0, 0, 0);
    uint4 xa[9], xb[9];
#pragma unroll
    for (int u = 0; u < 9; u++) {
      const int row = u * 228 + sc * 12 + warp12;
      const uint4* xr = reinterpret_cast<const uint4*>(x + (size_t)row * D_);
      xa[u] = row < S_ ? __ldg(xr + lane) : make_uint4(0, 0, 0, 0);
      xb[u] = (row < S_ && lane < 24) ? __ldg(xr + 32 + lane) : make_uint4(0, 0, 0, 0);
    }
#pragma unroll
    for (int u = 0; u < 9; u++) {
      float s = 0.f;
      auto dot2 = [&](uint32_t a, uint32_t b) {
        const uint32_t pr = pack2(bf_lo(a) * bf_lo(b), bf_hi(a) * bf_hi(b));
        s += bf_lo(pr) + bf_hi(pr);
      };
      dot2(xa[u].x, ga.x); dot2(xa[u].y, ga.y); dot2(xa[u].z, ga.z); dot2(xa[u].w, ga.w);
      dot2(xb[u].x, gb.x); dot2(xb[u].y, gb.y); dot2(xb[u].z, gb.z); dot2(xb[u].w, gb.w);
#pragma unroll
      for (int o = 16; o > 0; o >>= 1) s += __shfl_xor_sync(0xffffffffu, s, o);
      const int row = u * 228 + sc * 12 + warp12;
      if (lane == 0 && row < S_) g_gate[row] = bf_round(1.f / (1.f + __expf(-bf_round(s))));
    }
  }
  TL(2);
  if (t384 < 45) {
    const int i = t384 * 20 + sc;
    if (i < 896) l2_prefetch(((i & 1) ? wup : wgt) + (size_t)(i >> 1) * F_, F_ * 2);
  } else if (t384 >= 64 && t384 < 84) {
    const int ch = (t384 - 64) * 20 + sc;
    if (ch < 392) l2_prefetch(reinterpret_cast<const uint8_t*>(wd) + (size_t)ch * 4096, 4096);
  }
  if (sc == 19) { if (lane == 0) *my_epoch = epoch; mbar_wait(BAR_X(sb, 0), 0); return; }
  uint32_t fc[16], fs[16];
#pragma unroll
  for (int i = 0; i < 4; i++) {
    const uint4 a = __ldg(reinterpret_cast<const uint4*>(g_spec.f64) + i * 128 + tid);
    const uint4 b = __ldg(reinterpret_cast<const uint4*>(g_spec.f64) + (4 + i) * 128 + tid);
    fc[4 * i] = a.x; fc[4 * i + 1] = a.y; fc[4 * i + 2] = a.z; fc[4 * i + 3] = a.w;
    fs[4 * i] = b.x; fs[4 * i + 1] = b.y; fs[4 * i + 2] = b.z; fs[4 * i + 3] = b.w;
  }
  __syncthreads();
  const int nrnd = (sc == 18 && wg == 2) ? 1 : 2;
  if (tid == 32) {
    wait_counter(&g_cnt_w[0], epoch * 128);
    fence_async();
    for (int rnd = 0; rnd < nrnd; rnd++) {
      const int item = wg + 3 * rnd;
      mbar_expect_tx(BAR_EMPTY(sb, item), 16384);
      bulk_g2s(sb + SP_W + item * 16384, g_wt + (6 * sc + item) * 1024, 16384, BAR_EMPTY(sb, item));
    }
  } else if (tid == 0) {
#pragma unroll 1
    for (int rnd = 0; rnd < nrnd; rnd++) {
      const int item = wg + 3 * rnd, pr = 6 * sc + item;
      const int ra = pr < 112 ? 4 * pr : 1;
      wait_counter(&g_cnt_x1[(ra >> 6) * 32], epoch * 16);
      fence_async();
      const uint32_t bar = BAR_FULL(sb, item), z = sb + SP_Z + item * 16384;
      mbar_expect_tx(bar, 16384);
      tma2d(z, &p.x1, 0, ra * 64, bar);
      tma2d(z + 4096, &p.x1, 0, (4 * pr + 2) * 64, bar);
      tma2d(z + 8192, &p.x1, 0, (pr ? 4 * pr + 1 : D_) * 64, bar);
      tma2d(z + 12288, &p.x1, 0, (4 * pr + 3) * 64, bar);
    }
  }
  __syncwarp();
  fence_regs(fc); fence_regs(fs);
  mbar_wait(BAR_X(sb, 0), 0);
  TL(3);
  const uint64_t dT_n = mk_desc(sb + SP_T, 8192, 1024, 1);
#pragma unroll 1
  for (int rnd = 0; rnd < nrnd; rnd++) {
    const int item = wg + 3 * rnd, pr = 6 * sc + item;
    const uint32_t z = sb + SP_Z + item * 16384;
    mbar_wait(BAR_FULL(sb, item), 0);
    TL(4 + 8 * rnd);
    if (rnd == 0 && wg > 0) bar_sync(3 + wg, 256);
    float aR[32], aI[32];
    {
      const uint64_t dr = mk_desc(z, 4096, 512, 2), di = mk_desc(z + 8192, 4096, 512, 2);
      wg_fence();
#pragma unroll
      for (int kk = 0; kk < 4; kk++) {
        wgmma_rs_n64<1, 1>(aR, fc[4 * kk], fc[4 * kk + 1], fc[4 * kk + 2], fc[4 * kk + 3], dr + kk * 64, kk != 0);
        wgmma_rs_n64<1, 1>(aI, fc[4 * kk], fc[4 * kk + 1], fc[4 * kk + 2], fc[4 * kk + 3], di + kk * 64, kk != 0);
      }
#pragma unroll
      for (int kk = 0; kk < 4; kk++) {
        wgmma_rs_n64<1, 1>(aR, fs[4 * kk], fs[4 * kk + 1], fs[4 * kk + 2], fs[4 * kk + 3], di + kk * 64, 1);
        wgmma_rs_n64<-1, 1>(aI, fs[4 * kk], fs[4 * kk + 1], fs[4 * kk + 2], fs[4 * kk + 3], dr + kk * 64, 1);
      }
      wg_commit();
      if (rnd == 0 && wg < 2) bar_arrive(4 + wg, 256);
      if (rnd == 1 && tid == 0) { fence_gpu(); red_add(&g_cnt_y[((pr - 3) >> 4) * 32], 1); }
      wg_wait<0>();
      fence_regs(aR); fence_regs(aI);
    }
    TL(5 + 8 * rnd);
    uint32_t fa[16], fb[16];
#pragma unroll
    for (int v = 0; v < 8; v++) {
      const float4 tw = *reinterpret_cast<const float4*>(smem + SP_TW + v * 2048 + tid * 16);
      fa[v] = pack2(aR[2 * v] * tw.x + aI[2 * v] * tw.y, aR[2 * v + 1] * tw.z + aI[2 * v + 1] * tw.w);
      fa[8 + v] = pack2(aI[2 * v] * tw.x - aR[2 * v] * tw.y, aI[2 * v + 1] * tw.z - aR[2 * v + 1] * tw.w);
      fb[v] = pack2(aR[16 + 2 * v] * tw.x + aI[16 + 2 * v] * tw.y, aR[16 + 2 * v + 1] * tw.z + aI[16 + 2 * v + 1] * tw.w);
      fb[8 + v] = pack2(aI[16 + 2 * v] * tw.x - aR[16 + 2 * v] * tw.y, aI[16 + 2 * v + 1] * tw.z - aR[16 + 2 * v + 1] * tw.w);
    }
    fence_regs(fa); fence_regs(fb);
    wg_fence();
#pragma unroll
    for (int kk = 0; kk < 4; kk++) {
      wgmma_rs_n64<1, 1>(aR, fa[4 * kk], fa[4 * kk + 1], fa[4 * kk + 2], fa[4 * kk + 3], dT_n + kk * 128, kk != 0);
      wgmma_rs_n64<1, 1>(aI, fb[4 * kk], fb[4 * kk + 1], fb[4 * kk + 2], fb[4 * kk + 3], dT_n + kk * 128, kk != 0);
    }
    wg_commit();
    mbar_wait(BAR_EMPTY(sb, item), 0);
    wg_wait<0>();
    fence_regs(aR); fence_regs(aI);
    TL(6 + 8 * rnd);
    {
      const uint8_t* wp = smem + SP_W + item * 16384 + q * 1024 + warp * 128 + (((lane >> 2) ^ (2 * q)) << 4);
#pragma unroll
      for (int jb = 0; jb < 4; jb++) {
        const uint4 w0 = *reinterpret_cast<const uint4*>(wp + jb * 4096), w1 = *reinterpret_cast<const uint4*>(wp + jb * 4096 + 512);
        auto cm = [&](const float* a, float r0_, float i0, float r1, float i1, uint32_t& re, uint32_t& im) {
          re = pack2(a[0] * r0_ - a[16] * i0, a[1] * r1 - a[17] * i1);
          im = pack2(a[0] * i0 + a[16] * r0_, a[1] * i1 + a[17] * r1);
        };
        cm(aR + 4 * jb, bf_lo(w0.x), bf_lo(w0.y), bf_lo(w1.x), bf_lo(w1.y), fa[2 * jb], fa[8 + 2 * jb]);
        cm(aR + 4 * jb + 2, bf_lo(w0.z), bf_lo(w0.w), bf_lo(w1.z), bf_lo(w1.w), fa[2 * jb + 1], fa[9 + 2 * jb]);
        cm(aI + 4 * jb, bf_hi(w0.x), bf_hi(w0.y), bf_hi(w1.x), bf_hi(w1.y), fb[2 * jb], fb[8 + 2 * jb]);
        cm(aI + 4 * jb + 2, bf_hi(w0.z), bf_hi(w0.w), bf_hi(w1.z), bf_hi(w1.w), fb[2 * jb + 1], fb[9 + 2 * jb]);
      }
    }
    fence_regs(fa); fence_regs(fb);
    wg_fence();
#pragma unroll
    for (int kk = 0; kk < 4; kk++) {
      wgmma_rs_n64<1, 0>(aR, fa[4 * kk], fa[4 * kk + 1], fa[4 * kk + 2], fa[4 * kk + 3], dT_n + kk * 2, kk != 0);
      wgmma_rs_n64<1, 0>(aI, fb[4 * kk], fb[4 * kk + 1], fb[4 * kk + 2], fb[4 * kk + 3], dT_n + kk * 2, kk != 0);
    }
    wg_commit();
    wg_wait<0>();
    fence_regs(aR); fence_regs(aI);
    TL(7 + 8 * rnd);
#pragma unroll
    for (int v = 0; v < 8; v++) {
      const float4 tw = *reinterpret_cast<const float4*>(smem + SP_TW + v * 2048 + tid * 16);
      fa[v] = pack2(aR[2 * v] * tw.x - aR[16 + 2 * v] * tw.y, aR[2 * v + 1] * tw.z - aR[16 + 2 * v + 1] * tw.w);
      fb[v] = pack2(aR[16 + 2 * v] * tw.x + aR[2 * v] * tw.y, aR[16 + 2 * v + 1] * tw.z + aR[2 * v + 1] * tw.w);
      fa[8 + v] = pack2(aI[2 * v] * tw.x - aI[16 + 2 * v] * tw.y, aI[2 * v + 1] * tw.z - aI[16 + 2 * v + 1] * tw.w);
      fb[8 + v] = pack2(aI[16 + 2 * v] * tw.x + aI[2 * v] * tw.y, aI[16 + 2 * v + 1] * tw.z + aI[2 * v + 1] * tw.w);
    }
    bar_sync(1 + wg, 128);
    {
      const int row = 16 * warp + (lane & 7) + 8 * ((lane >> 3) & 1);
#pragma unroll
      for (int u = 0; u < 4; u++) {
        const uint32_t a = z + row * 128 + (((2 * u + (lane >> 4)) ^ (row & 7)) << 4);
        stmatrix_x4(a, fa[4 * u], fa[4 * u + 1], fa[4 * u + 2], fa[4 * u + 3]);
        stmatrix_x4(a + 8192, fb[4 * u], fb[4 * u + 1], fb[4 * u + 2], fb[4 * u + 3]);
      }
    }
    fence_async_smem();
    bar_sync(1 + wg, 128);
    TL(8 + 8 * rnd);
    {
      const uint64_t dr = mk_desc(z, 8192, 1024, 1), di = mk_desc(z + 8192, 8192, 1024, 1);
      wg_fence();
#pragma unroll
      for (int kk = 0; kk < 4; kk++) {
        wgmma_rs_n64<1, 1>(aR, fc[4 * kk], fc[4 * kk + 1], fc[4 * kk + 2], fc[4 * kk + 3], dr + kk * 128, kk != 0);
        wgmma_rs_n64<1, 1>(aI, fc[4 * kk], fc[4 * kk + 1], fc[4 * kk + 2], fc[4 * kk + 3], di + kk * 128, kk != 0);
      }
#pragma unroll
      for (int kk = 0; kk < 4; kk++) {
        wgmma_rs_n64<-1, 1>(aR, fs[4 * kk], fs[4 * kk + 1], fs[4 * kk + 2], fs[4 * kk + 3], di + kk * 128, 1);
        wgmma_rs_n64<1, 1>(aI, fs[4 * kk], fs[4 * kk + 1], fs[4 * kk + 2], fs[4 * kk + 3], dr + kk * 128, 1);
      }
      wg_commit();
      wg_wait<0>();
      fence_regs(aR); fence_regs(aI);
    }
    TL(9 + 8 * rnd);
    const bool edge = pr == 0 || pr == 112;
    if (edge) {
#pragma unroll
      for (int i = 0; i < 16; i++) aR[i] *= 0.5f;
    }
#pragma unroll
    for (int h = 0; h < 2; h++) {
      __nv_bfloat16* dst = g_yt + (size_t)(4 * pr) * S_ + 32 * (r0 + 8 * h) + 8 * q;
      auto st = [&](bool ok, int jrow, const float* a) {
        if (ok)
          *reinterpret_cast<uint4*>(dst + jrow * S_) =
              make_uint4(pack2(a[2 * h], a[2 * h + 1]), pack2(a[4 + 2 * h], a[5 + 2 * h]), pack2(a[8 + 2 * h], a[9 + 2 * h]), pack2(a[12 + 2 * h], a[13 + 2 * h]));
      };
      st(true, pr < 112 ? 0 : 1 - D_, aR); st(!edge, 1, aI); st(pr < 112, 2, aR + 16); st(pr < 112, 3, aI + 16);
    }
    bar_sync(1 + wg, 128);
    if (rnd == nrnd - 1 && tid == 0) { fence_gpu(); red_add(&g_cnt_y[(pr < 112 ? pr >> 4 : 0) * 32], 1); }
    TL(10 + 8 * rnd);
  }
  if (lane == 0) *my_epoch = epoch;
}

__global__ void __cluster_dims__(2, 1, 1) __launch_bounds__(384, 1)
fused_kernel(const __grid_constant__ Params p, const __nv_bfloat16* __restrict__ x, const __nv_bfloat16* __restrict__ w_r,
             const __nv_bfloat16* __restrict__ w_i, const __nv_bfloat16* __restrict__ gate_w, const __nv_bfloat16* __restrict__ wgt,
             const __nv_bfloat16* __restrict__ wup, const __nv_bfloat16* __restrict__ wd, __nv_bfloat16* __restrict__ out) {
  extern __shared__ __align__(1024) uint8_t smem[];
  const uint32_t sb = smem_u32(smem);
  const int bid = blockIdx.x;
  TL(0);
  if (bid < NFFN) {
    const uint32_t rank = bid & 1;
    const int cl = bid >> 1, jj = cl % 7, mt = 2 * (cl / 7) + rank;
    const int wg = __shfl_sync(0xffffffffu, threadIdx.x >> 7, 0);
    if (wg == 2) {
      const int warp = (threadIdx.x >> 5) & 3, lane = threadIdx.x & 31;
      if (warp == 0) {
        if (lane < 16) mbar_init(sb + SM_BAR + 8 * lane, lane < 8 ? 1 : 4);
        asm volatile("fence.mbarrier_init.release.cluster;" ::: "memory");
      } else if (warp == 2) {
        if (lane < 17) mbar_init(sb + SM_BAR + 128 + 8 * lane, lane < 16 ? 1 : 2);
        asm volatile("fence.mbarrier_init.release.cluster;" ::: "memory");
      } else if (lane < 5) {
        prefetch_tmap(warp == 1 ? (lane == 0 ? (rank ? &p.wu : &p.wg) : &p.ct) : (lane == 0 ? &p.wd : &p.yt));
      }
      __syncwarp();
      asm volatile("barrier.cluster.arrive.relaxed.aligned;" ::: "memory");
      if (threadIdx.x == 320) {
        mbar_expect_tx(BAR_X(sb, 0), 16384);
        tma2d(sb + SM_X, &p.x, 0, 128 * mt, BAR_X(sb, 0));
      }
      __syncwarp();
      asm volatile("barrier.cluster.wait.acquire.aligned;" ::: "memory");
      TL(1);
      asm volatile("setmaxnreg.dec.sync.aligned.u32 40;");
      ffn_producer(sb, p, warp, lane, mt, jj, rank);
    } else {
      asm volatile("barrier.cluster.arrive.relaxed.aligned;" ::: "memory");
      {
        Slab<256> sl;
        sl.load(w_r, w_i, bid, threadIdx.x);
        sl.store(bid, threadIdx.x);
      }
      bar_arrive(8, 288);
      asm volatile("barrier.cluster.wait.acquire.aligned;" ::: "memory");
      TL(1);
      asm volatile("setmaxnreg.inc.sync.aligned.u32 232;");
      ffn_consumer(sb, wg, threadIdx.x & 127, mt, jj, out);
    }
  } else {
    spectral_cta(sb, smem, p, bid - NFFN, x, w_r, w_i, gate_w, wgt, wup, wd);
  }
}

typedef CUresult (*EncodeFn)(CUtensorMap*, CUtensorMapDataType, cuuint32_t, void*, const cuuint64_t*, const cuuint64_t*,
                             const cuuint32_t*, const cuuint32_t*, CUtensorMapInterleave, CUtensorMapSwizzle,
                             CUtensorMapL2promotion, CUtensorMapFloatOOBfill);

void make_map(EncodeFn fn, CUtensorMap* m, const void* base, int rank, const cuuint64_t* dims, const cuuint64_t* strides,
              const cuuint32_t* box, CUtensorMapSwizzle sw) {
  const cuuint32_t es[3] = {1, 1, 1};
  fn(m, CU_TENSOR_MAP_DATA_TYPE_BFLOAT16, rank, const_cast<void*>(base), dims, strides, box, es,
     CU_TENSOR_MAP_INTERLEAVE_NONE, sw, CU_TENSOR_MAP_L2_PROMOTION_L2_256B, CU_TENSOR_MAP_FLOAT_OOB_FILL_NONE);
}

}

extern "C" void kernel_launch(void* const* d_in, const int* in_sizes, int n_in, void* d_out, int out_size) {
  const __nv_bfloat16* x = (const __nv_bfloat16*)d_in[0];
  const __nv_bfloat16* w_r = (const __nv_bfloat16*)d_in[1];
  const __nv_bfloat16* w_i = (const __nv_bfloat16*)d_in[2];
  const __nv_bfloat16* wg = (const __nv_bfloat16*)d_in[4];
  const __nv_bfloat16* wu = (const __nv_bfloat16*)d_in[5];
  const __nv_bfloat16* wd = (const __nv_bfloat16*)d_in[6];
  const __nv_bfloat16* gate_w = (const __nv_bfloat16*)d_in[7];

  void* fnp = nullptr;
  cudaDriverEntryPointQueryResult qr;
  cudaGetDriverEntryPoint("cuTensorMapEncodeTiled", &fnp, cudaEnableDefault, &qr);
  EncodeFn fn = (EncodeFn)fnp;
  void *ctab, *x1t, *yt;
  cudaGetSymbolAddress(&ctab, g_ctab);
  cudaGetSymbolAddress(&x1t, g_x1t);
  cudaGetSymbolAddress(&yt, g_yt);
  Params p;
  {
    const cuuint64_t d[2] = {D_, S_}, s[1] = {D_ * 2};
    const cuuint32_t b[2] = {64, 128};
    make_map(fn, &p.x, x, 2, d, s, b, CU_TENSOR_MAP_SWIZZLE_128B);
  }
  {
    const cuuint64_t d[3] = {64, D_, F_ / 64}, s[2] = {F_ * 2, 128};
    const cuuint32_t b[3] = {64, 32, 2};
    make_map(fn, &p.wg, wg, 3, d, s, b, CU_TENSOR_MAP_SWIZZLE_128B);
    make_map(fn, &p.wu, wu, 3, d, s, b, CU_TENSOR_MAP_SWIZZLE_128B);
  }
  {
    const cuuint64_t d[2] = {D_, F_}, s[1] = {D_ * 2};
    const cuuint32_t b[2] = {64, 64};
    make_map(fn, &p.wd, wd, 2, d, s, b, CU_TENSOR_MAP_SWIZZLE_128B);
  }
  {
    const cuuint64_t d[2] = {D_, D_}, s[1] = {D_ * 2};
    const cuuint32_t b[2] = {64, 64};
    make_map(fn, &p.ct, ctab, 2, d, s, b, CU_TENSOR_MAP_SWIZZLE_128B);
  }
  {
    const cuuint64_t d[2] = {32, D_ * 64}, s[1] = {64};
    const cuuint32_t b[2] = {32, 64};
    make_map(fn, &p.x1, x1t, 2, d, s, b, CU_TENSOR_MAP_SWIZZLE_64B);
  }
  {
    const cuuint64_t d[3] = {64, D_, S_ / 64}, s[2] = {S_ * 2, 128};
    const cuuint32_t b[3] = {64, 64, 2};
    make_map(fn, &p.yt, yt, 3, d, s, b, CU_TENSOR_MAP_SWIZZLE_128B);
  }
  cudaFuncSetAttribute(fused_kernel, cudaFuncAttributeMaxDynamicSharedMemorySize, SM_TOTAL);
  fused_kernel<<<NCTA, 384, SM_TOTAL, cudaStreamPerThread>>>(p, x, w_r, w_i, gate_w, wd, (__nv_bfloat16*)d_out);
}
```

```cpp
#include <cuda_runtime.h>
#include <cuda_bf16.h>
#include <cuda.h>
#include <stdint.h>
#include <stddef.h>

namespace {

constexpr int S_ = 2048, D_ = 448, F_ = 1792, DF_ = 225;
constexpr int NFFN = 112, NSPEC = 20, NCTA = NFFN + NSPEC;
constexpr int NSTAGE = 7, STAGE_BYTES = 16384;
constexpr int SM_X = 0, SM_RING = 114688, SM_BAR = 229376, SM_TOTAL = SM_BAR + 512;
constexpr int SP_Z = 0, SP_W = 98304, SP_G = 100864, SP_TW = 198656, SP_T = 215040, SLAB_BYTES = 16 * DF_ * 2;
constexpr uint32_t SPIN_LIMIT = 1u << 20;

namespace tab {
constexpr double PI = 3.14159265358979323846264338327950288;
constexpr double csin(double x) {
  double t = x, s = x;
  for (int i = 1; i < 20; i++) { t = -t * x * x / ((2 * i) * (2 * i + 1)); s += t; }
  return s;
}
constexpr double ccos(double x) {
  double t = 1, s = 1;
  for (int i = 1; i < 20; i++) { t = -t * x * x / ((2 * i - 1) * (2 * i)); s += t; }
  return s;
}
constexpr uint32_t to_bf16(double v) {
  uint32_t sign = v < 0 ? 0x8000u : 0u;
  double a = v < 0 ? -v : v;
  if (a < 1e-12) return 0;
  int e = 0;
  while (a >= 2.0) { a /= 2; e++; }
  while (a < 1.0) { a *= 2; e--; }
  double m = a * 128.0;
  int mi = (int)m;
  double fr = m - mi;
  if (fr > 0.5 || (fr == 0.5 && (mi & 1))) mi++;
  if (mi == 256) { mi = 128; e++; }
  return sign | (uint32_t)((e + 127) << 7) | (uint32_t)(mi - 128);
}
struct Base { uint32_t v[448]; };
constexpr Base make_base() {
  Base b{};
  for (int m = 0; m < 448; m++) {
    int mm = m > 224 ? m - 448 : m;
    double ang = 2 * PI * mm / 448.0;
    b.v[m] = to_bf16(ccos(ang)) | (to_bf16(-csin(ang)) << 16);
  }
  return b;
}
constexpr Base base = make_base();
struct Row { uint32_t v[224]; };
constexpr Row make_row(int d) {
  Row r{};
  r.v[0] = 0x3f80u | ((d & 1) ? 0xbf800000u : 0x3f800000u);
  int m = 0;
  for (int c = 1; c < 224; c++) { m += d; if (m >= 448) m -= 448; r.v[c] = base.v[m]; }
  return r;
}
struct Table { Row r[448]; };
constexpr Table make_table() {
  Table t{};
  for (int d = 0; d < 448; d++) t.r[d] = make_row(d);
  return t;
}
struct Cs { double c[2048], s[2048]; };
constexpr Cs make_cs() {
  Cs t{};
  for (int m = 0; m <= 256; m++) {
    const double a = 2 * PI * m / 2048.0, c = ccos(a), s = csin(a);
    t.c[m] = c; t.s[m] = s;
    t.c[512 - m] = s; t.s[512 - m] = c;
  }
  for (int m = 513; m < 2048; m++) { t.c[m] = -t.s[m - 512]; t.s[m] = t.c[m - 512]; }
  return t;
}
constexpr Cs cs = make_cs();
struct Spec {
  float tw[4096];
  uint16_t t32[4096];
  uint32_t f64[4096];
};
constexpr Spec make_spec() {
  Spec t{};
  for (int i = 0; i < 2048; i++) {
    const int e = i & 1, th = (i >> 1) & 127, v = i >> 8;
    const int k1 = 16 * (th >> 5) + ((th & 31) >> 2) + 8 * (v & 1), n2 = 8 * (th & 3) + 2 * (v >> 1) + e;
    t.tw[2 * i] = (float)cs.c[n2 * k1];
    t.tw[2 * i + 1] = (float)cs.s[n2 * k1];
  }
  for (int row = 0; row < 64; row++)
    for (int col = 0; col < 64; col++) {
      const int c = row & 31, k2 = col & 31, n2 = 8 * ((c >> 1) & 3) + 2 * (c >> 3) + (c & 1), m = 64 * ((n2 * k2) & 31);
      const double v = (row >> 5) == (col >> 5) ? cs.c[m] : (row < 32 ? -cs.s[m] : cs.s[m]);
      t.t32[row * 64 + (((col >> 3) ^ (row & 7)) << 3) + (col & 7)] = (uint16_t)to_bf16(v);
    }
  for (int th = 0; th < 128; th++)
    for (int i = 0; i < 16; i++) {
      const int m = 16 * (th >> 5) + ((th & 31) >> 2) + 8 * (i & 1), k = 16 * (i >> 2) + 8 * ((i >> 1) & 1) + 2 * (th & 3);
      const int a0 = 32 * ((m * k) & 63), a1 = 32 * ((m * (k + 1)) & 63);
      t.f64[((i >> 2) * 128 + th) * 4 + (i & 3)] = to_bf16(cs.c[a0]) | (to_bf16(cs.c[a1]) << 16);
      t.f64[((4 + (i >> 2)) * 128 + th) * 4 + (i & 3)] = to_bf16(cs.s[a0]) | (to_bf16(cs.s[a1]) << 16);
    }
  return t;
}
}
}

__device__ __align__(1024) const tab::Table g_ctab = tab::make_table();
__device__ __align__(1024) const tab::Spec g_spec = tab::make_spec();

struct Scratch {
  uint32_t cnt_w[32];
  uint32_t cnt_x1[7 * 32];
  uint32_t cnt_y[7 * 32];
  uint32_t cnt_p[16 * 7 * 2 * 8];
  uint32_t epoch[NCTA * 12 + 240];
  float gate[S_];
  __nv_bfloat16 x1t[D_ * S_];
  __nv_bfloat16 yt[D_ * S_];
  uint4 wt[114 * 1024];
  uint4 part[16 * 7 * 6 * 2 * 4 * 128];
};
static_assert(offsetof(Scratch, x1t) % 1024 == 0, "alignment");
__device__ __align__(1024) Scratch g_scratch;
#define TL(i)

namespace {

struct Params {
  Scratch* s;
  __nv_bfloat16* out;
  const __nv_bfloat16 *px, *w_r, *w_i, *gate_w, *pwg, *pwu, *pwd;
  const tab::Table* ctab;
  const tab::Spec* spec;
  CUtensorMap x, wg, wu, wd, ct, x1, yt;
};

__device__ __forceinline__ uint32_t smem_u32(const void* p) { return (uint32_t)__cvta_generic_to_shared(p); }
__device__ __forceinline__ void mbar_init(uint32_t bar, uint32_t cnt) {
  asm volatile("mbarrier.init.shared::cta.b64 [%0], %1;" ::"r"(bar), "r"(cnt) : "memory");
}
__device__ __forceinline__ void mbar_expect_tx(uint32_t bar, uint32_t bytes) {
  asm volatile("mbarrier.arrive.expect_tx.shared::cta.b64 _, [%0], %1;" ::"r"(bar), "r"(bytes) : "memory");
}
__device__ __forceinline__ void mbar_arrive(uint32_t bar) {
  asm volatile("mbarrier.arrive.shared::cta.b64 _, [%0];" ::"r"(bar) : "memory");
}
__device__ __forceinline__ void mbar_arrive_cluster(uint32_t bar, uint32_t cta) {
  asm volatile("{\n.reg .b32 ra;\nmapa.shared::cluster.u32 ra, %0, %1;\n"
               "mbarrier.arrive.shared::cluster.b64 _, [ra];\n}" ::"r"(bar), "r"(cta) : "memory");
}
__device__ __forceinline__ void mbar_wait(uint32_t bar, uint32_t parity) {
  uint32_t ok, n = 0;
  do {
    asm volatile("{\n.reg .pred p;\nmbarrier.try_wait.parity.shared::cta.b64 p, [%1], %2;\nselp.u32 %0, 1, 0, p;\n}"
                 : "=r"(ok) : "r"(bar), "r"(parity) : "memory");
  } while (!ok && ++n < SPIN_LIMIT);
}
__device__ __forceinline__ void mbar_wait_cluster(uint32_t bar, uint32_t parity) {
  uint32_t ok, n = 0;
  do {
    asm volatile("{\n.reg .pred p;\nmbarrier.try_wait.parity.acquire.cluster.shared::cta.b64 p, [%1], %2;\nselp.u32 %0, 1, 0, p;\n}"
                 : "=r"(ok) : "r"(bar), "r"(parity) : "memory");
  } while (!ok && ++n < SPIN_LIMIT);
}
__device__ __forceinline__ void tma2d(uint32_t dst, const CUtensorMap* m, int c0, int c1, uint32_t bar) {
  asm volatile("cp.async.bulk.tensor.2d.shared::cluster.global.mbarrier::complete_tx::bytes [%0], [%1, {%3, %4}], [%2];"
               ::"r"(dst), "l"(m), "r"(bar), "r"(c0), "r"(c1) : "memory");
}
__device__ __forceinline__ void tma3d(uint32_t dst, const CUtensorMap* m, int c0, int c1, int c2, uint32_t bar) {
  asm volatile("cp.async.bulk.tensor.3d.shared::cluster.global.mbarrier::complete_tx::bytes [%0], [%1, {%3, %4, %5}], [%2];"
               ::"r"(dst), "l"(m), "r"(bar), "r"(c0), "r"(c1), "r"(c2) : "memory");
}
__device__ __forceinline__ void tma2d_mc(uint32_t dst, const CUtensorMap* m, int c0, int c1, uint32_t bar) {
  asm volatile("cp.async.bulk.tensor.2d.shared::cluster.global.mbarrier::complete_tx::bytes.multicast::cluster [%0], [%1, {%3, %4}], [%2], %5;"
               ::"r"(dst), "l"(m), "r"(bar), "r"(c0), "r"(c1), "h"((uint16_t)3) : "memory");
}
__device__ __forceinline__ void tma3d_mc(uint32_t dst, const CUtensorMap* m, int c0, int c1, int c2, uint32_t bar) {
  asm volatile("cp.async.bulk.tensor.3d.shared::cluster.global.mbarrier::complete_tx::bytes.multicast::cluster [%0], [%1, {%3, %4, %5}], [%2], %6;"
               ::"r"(dst), "l"(m), "r"(bar), "r"(c0), "r"(c1), "r"(c2), "h"((uint16_t)3) : "memory");
}
__device__ __forceinline__ void bulk_g2s(uint32_t dst, const void* src, uint32_t bytes, uint32_t bar) {
  asm volatile("cp.async.bulk.shared::cluster.global.mbarrier::complete_tx::bytes [%0], [%1], %2, [%3];"
               ::"r"(dst), "l"(src), "r"(bytes), "r"(bar) : "memory");
}
__device__ __forceinline__ void prefetch_tmap(const CUtensorMap* m) {
  asm volatile("prefetch.tensormap [%0];" ::"l"(m) : "memory");
}
__device__ __forceinline__ void l2_prefetch(const void* p, uint32_t bytes) {
  asm volatile("cp.async.bulk.prefetch.L2.global [%0], %1;" ::"l"(p), "r"(bytes) : "memory");
}
__device__ __forceinline__ void wg_fence() { asm volatile("wgmma.fence.sync.aligned;" ::: "memory"); }
__device__ __forceinline__ void wg_commit() { asm volatile("wgmma.commit_group.sync.aligned;" ::: "memory"); }
template <int N> __device__ __forceinline__ void wg_wait() { asm volatile("wgmma.wait_group.sync.aligned %0;" ::"n"(N) : "memory"); }
template <int N> __device__ __forceinline__ void fence_regs(float (&d)[N]) {
#pragma unroll
  for (int i = 0; i < N; i++) asm volatile("" : "+f"(d[i])::"memory");
}
template <int N> __device__ __forceinline__ void fence_regs(uint32_t (&d)[N]) {
#pragma unroll
  for (int i = 0; i < N; i++) asm volatile("" : "+r"(d[i])::"memory");
}
__device__ __forceinline__ void bar_sync(int id, int n) { asm volatile("bar.sync %0, %1;" ::"r"(id), "r"(n) : "memory"); }
__device__ __forceinline__ void bar_arrive(int id, int n) { asm volatile("bar.arrive %0, %1;" ::"r"(id), "r"(n) : "memory"); }
__device__ __forceinline__ void fence_gpu() { asm volatile("fence.acq_rel.gpu;" ::: "memory"); }
__device__ __forceinline__ void fence_async() { asm volatile("fence.proxy.async;" ::: "memory"); }
__device__ __forceinline__ void fence_async_smem() { asm volatile("fence.proxy.async.shared::cta;" ::: "memory"); }
__device__ __forceinline__ void red_add(uint32_t* p, uint32_t v) {
  asm volatile("red.relaxed.gpu.global.add.u32 [%0], %1;" ::"l"(p), "r"(v) : "memory");
}
__device__ __forceinline__ uint32_t ld_relaxed(const uint32_t* p) {
  uint32_t v;
  asm volatile("ld.relaxed.gpu.global.u32 %0, [%1];" : "=r"(v) : "l"(p) : "memory");
  return v;
}
__device__ __forceinline__ void wait_counter(const uint32_t* p, uint32_t target) {
  uint32_t v, n = 0;
  while (true) {
    asm volatile("ld.acquire.gpu.global.u32 %0, [%1];" : "=r"(v) : "l"(p) : "memory");
    if ((int32_t)(v - target) >= 0 || ++n > SPIN_LIMIT) break;
  }
}
__device__ __forceinline__ uint4 ld_cg(const uint4* p) {
  uint4 v;
  asm volatile("ld.global.cg.v4.u32 {%0, %1, %2, %3}, [%4];" : "=r"(v.x), "=r"(v.y), "=r"(v.z), "=r"(v.w) : "l"(p) : "memory");
  return v;
}
__device__ __forceinline__ uint32_t pack2(float lo, float hi) {
  uint32_t r;
  asm("cvt.rn.bf16x2.f32 %0, %1, %2;" : "=r"(r) : "f"(hi), "f"(lo));
  return r;
}
__device__ __forceinline__ float bf_lo(uint32_t v) { return __uint_as_float(v << 16); }
__device__ __forceinline__ float bf_hi(uint32_t v) { return __uint_as_float(v & 0xffff0000u); }
__device__ __forceinline__ float bf_round(float v) { return bf_lo(pack2(v, 0.f)); }
__device__ __forceinline__ float tanh_fast(float v) {
  float r;
  asm("tanh.approx.f32 %0, %1;" : "=f"(r) : "f"(v));
  return r;
}
__device__ __forceinline__ uint64_t mk_desc(uint32_t addr, uint32_t lbo, uint32_t sbo, uint32_t mode) {
  return (uint64_t)((addr & 0x3FFFF) >> 4) | ((uint64_t)(lbo >> 4) << 16) | ((uint64_t)(sbo >> 4) << 32) | ((uint64_t)mode << 62);
}
__device__ __forceinline__ void stmatrix_x4(uint32_t addr, uint32_t r0, uint32_t r1, uint32_t r2, uint32_t r3) {
  asm volatile("stmatrix.sync.aligned.m8n8.x4.shared.b16 [%0], {%1, %2, %3, %4};" ::"r"(addr), "r"(r0), "r"(r1), "r"(r2), "r"(r3) : "memory");
}

template <int TA, int TB>
__device__ __forceinline__ void wgmma_ss_n256(float (&d)[128], uint64_t da, uint64_t db, int sd) {
  asm volatile("{\n.reg .pred p;\nsetp.ne.b32 p, %130, 0;\n"
      "wgmma.mma_async.sync.aligned.m64n256k16.f32.bf16.bf16 {"
      "%0, %1, %2, %3, %4, %5, %6, %7, %8, %9, %10, %11, %12, %13, %14, %15, %16, %17, %18, %19, %20, %21, %22, %23, "
      "%24, %25, %26, %27, %28, %29, %30, %31, %32, %33, %34, %35, %36, %37, %38, %39, %40, %41, %42, %43, %44, %45, "
      "%46, %47, %48, %49, %50, %51, %52, %53, %54, %55, %56, %57, %58, %59, %60, %61, %62, %63, %64, %65, %66, %67, "
      "%68, %69, %70, %71, %72, %73, %74, %75, %76, %77, %78, %79, %80, %81, %82, %83, %84, %85, %86, %87, %88, %89, "
      "%90, %91, %92, %93, %94, %95, %96, %97, %98, %99, %100, %101, %102, %103, %104, %105, %106, %107, %108, %109, "
      "%110, %111, %112, %113, %114, %115, %116, %117, %118, %119, %120, %121, %122, %123, %124, %125, %126, %127"
      "}, %128, %129, p, 1, 1, %131, %132;\n}\n"
      : "+f"(d[0]), "+f"(d[1]), "+f"(d[2]), "+f"(d[3]), "+f"(d[4]), "+f"(d[5]), "+f"(d[6]), "+f"(d[7]), "+f"(d[8]),
        "+f"(d[9]), "+f"(d[10]), "+f"(d[11]), "+f"(d[12]), "+f"(d[13]), "+f"(d[14]), "+f"(d[15]), "+f"(d[16]),
        "+f"(d[17]), "+f"(d[18]), "+f"(d[19]), "+f"(d[20]), "+f"(d[21]), "+f"(d[22]), "+f"(d[23]), "+f"(d[24]),
        "+f"(d[25]), "+f"(d[26]), "+f"(d[27]), "+f"(d[28]), "+f"(d[29]), "+f"(d[30]), "+f"(d[31]), "+f"(d[32]),
        "+f"(d[33]), "+f"(d[34]), "+f"(d[35]), "+f"(d[36]), "+f"(d[37]), "+f"(d[38]), "+f"(d[39]), "+f"(d[40]),
        "+f"(d[41]), "+f"(d[42]), "+f"(d[43]), "+f"(d[44]), "+f"(d[45]), "+f"(d[46]), "+f"(d[47]), "+f"(d[48]),
        "+f"(d[49]), "+f"(d[50]), "+f"(d[51]), "+f"(d[52]), "+f"(d[53]), "+f"(d[54]), "+f"(d[55]), "+f"(d[56]),
        "+f"(d[57]), "+f"(d[58]), "+f"(d[59]), "+f"(d[60]), "+f"(d[61]), "+f"(d[62]), "+f"(d[63]), "+f"(d[64]),
        "+f"(d[65]), "+f"(d[66]), "+f"(d[67]), "+f"(d[68]), "+f"(d[69]), "+f"(d[70]), "+f"(d[71]), "+f"(d[72]),
        "+f"(d[73]), "+f"(d[74]), "+f"(d[75]), "+f"(d[76]), "+f"(d[77]), "+f"(d[78]), "+f"(d[79]), "+f"(d[80]),
        "+f"(d[81]), "+f"(d[82]), "+f"(d[83]), "+f"(d[84]), "+f"(d[85]), "+f"(d[86]), "+f"(d[87]), "+f"(d[88]),
        "+f"(d[89]), "+f"(d[90]), "+f"(d[91]), "+f"(d[92]), "+f"(d[93]), "+f"(d[94]), "+f"(d[95]), "+f"(d[96]),
        "+f"(d[97]), "+f"(d[98]), "+f"(d[99]), "+f"(d[100]), "+f"(d[101]), "+f"(d[102]), "+f"(d[103]), "+f"(d[104]),
        "+f"(d[105]), "+f"(d[106]), "+f"(d[107]), "+f"(d[108]), "+f"(d[109]), "+f"(d[110]), "+f"(d[111]),
        "+f"(d[112]), "+f"(d[113]), "+f"(d[114]), "+f"(d[115]), "+f"(d[116]), "+f"(d[117]), "+f"(d[118]),
        "+f"(d[119]), "+f"(d[120]), "+f"(d[121]), "+f"(d[122]), "+f"(d[123]), "+f"(d[124]), "+f"(d[125]),
        "+f"(d[126]), "+f"(d[127])
      : "l"(da), "l"(db), "r"(sd), "n"(TA), "n"(TB));
}
template <int TA, int TB>
__device__ __forceinline__ void wgmma_ss_n128(float (&d)[64], uint64_t da, uint64_t db, int sd) {
  asm volatile("{\n.reg .pred p;\nsetp.ne.b32 p, %66, 0;\n"
      "wgmma.mma_async.sync.aligned.m64n128k16.f32.bf16.bf16 {"
      "%0, %1, %2, %3, %4, %5, %6, %7, %8, %9, %10, %11, %12, %13, %14, %15, %16, %17, %18, %19, %20, %21, %22, %23, "
      "%24, %25, %26, %27, %28, %29, %30, %31, %32, %33, %34, %35, %36, %37, %38, %39, %40, %41, %42, %43, %44, %45, "
      "%46, %47, %48, %49, %50, %51, %52, %53, %54, %55, %56, %57, %58, %59, %60, %61, %62, %63"
      "}, %64, %65, p, 1, 1, %67, %68;\n}\n"
      : "+f"(d[0]), "+f"(d[1]), "+f"(d[2]), "+f"(d[3]), "+f"(d[4]), "+f"(d[5]), "+f"(d[6]), "+f"(d[7]), "+f"(d[8]),
        "+f"(d[9]), "+f"(d[10]), "+f"(d[11]), "+f"(d[12]), "+f"(d[13]), "+f"(d[14]), "+f"(d[15]), "+f"(d[16]),
        "+f"(d[17]), "+f"(d[18]), "+f"(d[19]), "+f"(d[20]), "+f"(d[21]), "+f"(d[22]), "+f"(d[23]), "+f"(d[24]),
        "+f"(d[25]), "+f"(d[26]), "+f"(d[27]), "+f"(d[28]), "+f"(d[29]), "+f"(d[30]), "+f"(d[31]), "+f"(d[32]),
        "+f"(d[33]), "+f"(d[34]), "+f"(d[35]), "+f"(d[36]), "+f"(d[37]), "+f"(d[38]), "+f"(d[39]), "+f"(d[40]),
        "+f"(d[41]), "+f"(d[42]), "+f"(d[43]), "+f"(d[44]), "+f"(d[45]), "+f"(d[46]), "+f"(d[47]), "+f"(d[48]),
        "+f"(d[49]), "+f"(d[50]), "+f"(d[51]), "+f"(d[52]), "+f"(d[53]), "+f"(d[54]), "+f"(d[55]), "+f"(d[56]),
        "+f"(d[57]), "+f"(d[58]), "+f"(d[59]), "+f"(d[60]), "+f"(d[61]), "+f"(d[62]), "+f"(d[63])
      : "l"(da), "l"(db), "r"(sd), "n"(TA), "n"(TB));
}
template <int TA, int TB>
__device__ __forceinline__ void wgmma_ss_n64(float (&d)[32], uint64_t da, uint64_t db, int sd) {
  asm volatile("{\n.reg .pred p;\nsetp.ne.b32 p, %34, 0;\n"
      "wgmma.mma_async.sync.aligned.m64n64k16.f32.bf16.bf16 {"
      "%0, %1, %2, %3, %4, %5, %6, %7, %8, %9, %10, %11, %12, %13, %14, %15, %16, %17, %18, %19, %20, %21, %22, %23, "
      "%24, %25, %26, %27, %28, %29, %30, %31"
      "}, %32, %33, p, 1, 1, %35, %36;\n}\n"
      : "+f"(d[0]), "+f"(d[1]), "+f"(d[2]), "+f"(d[3]), "+f"(d[4]), "+f"(d[5]), "+f"(d[6]), "+f"(d[7]), "+f"(d[8]),
        "+f"(d[9]), "+f"(d[10]), "+f"(d[11]), "+f"(d[12]), "+f"(d[13]), "+f"(d[14]), "+f"(d[15]), "+f"(d[16]),
        "+f"(d[17]), "+f"(d[18]), "+f"(d[19]), "+f"(d[20]), "+f"(d[21]), "+f"(d[22]), "+f"(d[23]), "+f"(d[24]),
        "+f"(d[25]), "+f"(d[26]), "+f"(d[27]), "+f"(d[28]), "+f"(d[29]), "+f"(d[30]), "+f"(d[31])
      : "l"(da), "l"(db), "r"(sd), "n"(TA), "n"(TB));
}
template <int SA, int TB>
__device__ __forceinline__ void wgmma_rs_n64(float (&d)[32], uint32_t a0, uint32_t a1, uint32_t a2, uint32_t a3, uint64_t db, int sd) {
  asm volatile("{\n.reg .pred p;\nsetp.ne.b32 p, %37, 0;\n"
      "wgmma.mma_async.sync.aligned.m64n64k16.f32.bf16.bf16 {"
      "%0, %1, %2, %3, %4, %5, %6, %7, %8, %9, %10, %11, %12, %13, %14, %15, %16, %17, %18, %19, %20, %21, %22, %23, "
      "%24, %25, %26, %27, %28, %29, %30, %31"
      "}, {%32, %33, %34, %35}, %36, p, %38, 1, %39;\n}\n"
      : "+f"(d[0]), "+f"(d[1]), "+f"(d[2]), "+f"(d[3]), "+f"(d[4]), "+f"(d[5]), "+f"(d[6]), "+f"(d[7]), "+f"(d[8]),
        "+f"(d[9]), "+f"(d[10]), "+f"(d[11]), "+f"(d[12]), "+f"(d[13]), "+f"(d[14]), "+f"(d[15]), "+f"(d[16]),
        "+f"(d[17]), "+f"(d[18]), "+f"(d[19]), "+f"(d[20]), "+f"(d[21]), "+f"(d[22]), "+f"(d[23]), "+f"(d[24]),
        "+f"(d[25]), "+f"(d[26]), "+f"(d[27]), "+f"(d[28]), "+f"(d[29]), "+f"(d[30]), "+f"(d[31])
      : "r"(a0), "r"(a1), "r"(a2), "r"(a3), "l"(db), "r"(sd), "n"(SA), "n"(TB));
}

__device__ __forceinline__ uint32_t BAR_FULL(uint32_t sb, int i) { return sb + SM_BAR + 8 * i; }
__device__ __forceinline__ uint32_t BAR_EMPTY(uint32_t sb, int i) { return sb + SM_BAR + 64 + 8 * i; }
__device__ __forceinline__ uint32_t BAR_X(uint32_t sb, int i) { return sb + SM_BAR + 128 + 8 * i; }
__device__ __forceinline__ uint32_t BAR_Y(uint32_t sb, int i) { return sb + SM_BAR + 192 + 8 * i; }
__device__ __forceinline__ uint32_t BAR_XFREE(uint32_t sb) { return sb + SM_BAR + 256; }

#define CMASK 0x194u
#define XORDER 0, 1, 11, 2, 3, 12, 13, 4, 5, 14, 6, 15, 16
#define PFAT 3
#define SKEW 3
constexpr int Q_G1B = 18, Q_G2 = 32, Q_P3 = 46, Q_END = 50;

struct Ring {
  uint32_t slot, phase;
  __device__ __forceinline__ void next() { if (++slot == NSTAGE) { slot = 0; phase ^= 1; } }
};

__device__ __forceinline__ void release_slot(uint32_t sb, uint32_t slot, int tid, int times) {
  if (tid < 2 * times) mbar_arrive_cluster(BAR_EMPTY(sb, slot), tid & 1);
}

__device__ __forceinline__ void ffn_consumer(uint32_t sb, const uint8_t* smem, const Params& p, int bid, int wg, int tid, int mt, int jj) {
  const int lane = tid & 31, warp = tid >> 5, q = lane & 3, r0 = 16 * warp + (lane >> 2);
  uint32_t* const my_epoch = &p.s->epoch[blockIdx.x * 12 + (threadIdx.x >> 5)];
  const uint32_t epoch = ld_relaxed(my_epoch) + 1;
  Ring rg{0, 0};
  uint32_t u[64];
  float acc[128];
  uint32_t prev = 0, cmask = CMASK;
  int st = 0;
  auto g1_stage = [&](uint32_t slot, int s) {
    const uint64_t da = mk_desc(sb + SM_X + (s >> 1) * 16384 + wg * 8192 + (s & 1) * 64, 16, 1024, 1);
    const uint64_t db = mk_desc(sb + SM_RING + slot * STAGE_BYTES, 4096, 1024, 1);
    wg_fence();
    wgmma_ss_n256<0, 1>(acc, da, db, s != 0);
    wgmma_ss_n256<0, 1>(acc, da + 2, db + 128, 1);
    wg_commit();
  };
  if (wg == 1) {
    float ap[64];
    constexpr int QX = 32 - __builtin_clz(CMASK);
    constexpr int NPRE = QX + 4;
    uint4* const x1dst = reinterpret_cast<uint4*>(p.s->x1t + (size_t)(64 * jj + r0) * S_ + 128 * mt + 8 * q);
#pragma unroll
    for (int qi = 0; qi < NPRE; qi++) {
      const int slot = qi % NSTAGE, nc = __builtin_popcount(CMASK & ((1u << qi) - 1));
      if (qi == 0) TL(60);
      mbar_wait(BAR_FULL(sb, slot), (qi / NSTAGE) & 1);
      if (qi == 0) TL(61);
      if ((CMASK >> qi) & 1) {
#pragma unroll
        for (int kb = 2 * nc; kb < 2 * nc + 2 && kb < 7; kb++) {
          const uint64_t da = mk_desc(sb + SM_RING + slot * STAGE_BYTES + (kb & 1) * 8192, 8192, 1024, 1);
          const uint64_t db = mk_desc(sb + SM_X + kb * 16384, 16, 1024, 1);
          mbar_wait(BAR_X(sb, kb), 0);
          TL(16 + kb);
          wg_fence();
#pragma unroll
          for (int kk = 0; kk < 4; kk++) wgmma_ss_n128<1, 0>(ap, da + kk * 128, db + kk * 2, (kb | kk) != 0);
          wg_commit();
        }
      } else {
        if (((qi - nc) & 1) == 0 && qi - nc >= 4 * nc) mbar_wait(BAR_X(sb, (qi - nc) >> 1), 0);
        TL(32 + qi - nc);
        g1_stage(slot, qi - nc);
      }
      if (qi > 0) {
        wg_wait<1>();
        release_slot(sb, (qi - 1) % NSTAGE, tid, ((CMASK >> (qi - 1)) & 1) ? 2 : 1);
      }
      if (qi >= QX) {
        if (qi == QX) { fence_regs(ap); TL(2); }
        const int t = qi - QX;
#pragma unroll
        for (int h = 0; h < 2; h++)
          x1dst[h * S_ + 4 * t] = make_uint4(pack2(ap[16 * t + 2 * h], ap[16 * t + 2 * h + 1]), pack2(ap[16 * t + 4 + 2 * h], ap[16 * t + 5 + 2 * h]),
                                             pack2(ap[16 * t + 8 + 2 * h], ap[16 * t + 9 + 2 * h]), pack2(ap[16 * t + 12 + 2 * h], ap[16 * t + 13 + 2 * h]));
      }
    }
    bar_arrive(7, 160);
    st = NPRE - 4; cmask = 0; prev = (NPRE - 1) % NSTAGE;
    rg.slot = NPRE % NSTAGE; rg.phase = (NPRE / NSTAGE) & 1;
  }
#pragma unroll 1
  for (int pass = 0; pass < 2; pass++) {
#pragma unroll 1
    for (; st < 14; st++) {
      while (cmask & 1) { cmask >>= 1; rg.next(); }
      cmask >>= 1;
      if (pass == 0 && (st & 1) == 0) mbar_wait(BAR_X(sb, st >> 1), 0);
      if (st == 14 - SKEW && wg == 1) bar_sync(9 + pass, 256);
      mbar_wait(BAR_FULL(sb, rg.slot), rg.phase);
      TL(32 + 14 * pass + st);
      g1_stage(rg.slot, st);
      wg_wait<1>();
      if (st > 0) release_slot(sb, prev, tid, 1);
      prev = rg.slot;
      rg.next();
    }
    st = 0;
    if (wg == 0) bar_arrive(9 + pass, 256);
    wg_wait<0>();
    fence_regs(acc);
    release_slot(sb, prev, tid, 1);
    if (pass == 1 && tid == 0) mbar_arrive(BAR_XFREE(sb));
    TL(3 + 2 * pass);
#pragma unroll
    for (int i = 0; i < 32; i++) {
      const float g0 = 0.5f * acc[2 * i], g1 = 0.5f * acc[2 * i + 1];
      const float s0 = fmaf(g0, tanh_fast(g0), g0), s1 = fmaf(g1, tanh_fast(g1), g1);
      u[32 + i] = pack2(s0 * acc[64 + 2 * i], s1 * acc[64 + 2 * i + 1]);
    }
    if (pass == 0) {
#pragma unroll
      for (int i = 0; i < 32; i++) u[i] = u[32 + i];
    }
    TL(4 + 2 * pass);
  }
  fence_regs(u);
  float accA[32], accB[32];
  rg.slot = Q_G2 % NSTAGE; rg.phase = (Q_G2 / NSTAGE) & 1;
  auto stage = [&](float (&acc)[32], int st) {
    mbar_wait(BAR_FULL(sb, rg.slot), rg.phase);
    const uint64_t db = mk_desc(sb + SM_RING + rg.slot * STAGE_BYTES, 8192, 1024, 1);
    wg_fence();
#pragma unroll
    for (int kk = 0; kk < 8; kk++) {
      const uint32_t* a = u + 32 * st + 4 * kk;
      wgmma_rs_n64<1, 1>(acc, a[0], a[1], a[2], a[3], db + kk * 128, (st | kk) != 0);
    }
    wg_commit();
  };
  auto retire = [&](bool rel) {
    wg_wait<1>();
    if (rel) release_slot(sb, prev, tid, 1);
    prev = rg.slot;
    rg.next();
  };
  auto put = [&](float (&acc)[32], int c) {
    fence_regs(acc);
    int o = jj + 1 + c;
    if (o >= 7) o -= 7;
    uint4* dst = p.s->part + ((((mt * 7 + o) * 6 + c) * 2 + wg) * 4) * 128 + tid;
#pragma unroll
    for (int v = 0; v < 4; v++) {
      const float* a = acc + 8 * v;
      dst[v * 128] = make_uint4(pack2(a[0], a[1]), pack2(a[2], a[3]), pack2(a[4], a[5]), pack2(a[6], a[7]));
    }
  };
#pragma unroll
  for (int c2 = 0; c2 < 4; c2++) {
    stage(accA, 0);
    retire(c2 == 1 || c2 == 2);
    stage(accA, 1);
    if (c2 > 0) { put(accB, 2 * c2 - 1); bar_arrive(3 * wg + c2, 160); }
    TL(7 + c2);
    if (c2 == 3) break;
    retire(true);
    stage(accB, 0);
    retire(true);
    stage(accB, 1);
    put(accA, 2 * c2);
    retire(true);
  }
  rg.next();
#pragma unroll 1
  for (int kb = 0; kb < 7; kb++) {
    if ((kb & 1) == 0) mbar_wait(BAR_FULL(sb, rg.slot), rg.phase);
    mbar_wait(BAR_Y(sb, kb), 0);
    const uint64_t da = mk_desc(sb + SM_X + kb * 16384 + wg * 8192, 8192, 1024, 1);
    const uint64_t db = mk_desc(sb + SM_RING + rg.slot * STAGE_BYTES + (kb & 1) * 8192, 16, 1024, 1);
    wg_fence();
#pragma unroll
    for (int kk = 0; kk < 4; kk++) wgmma_ss_n64<1, 0>(accB, da + kk * 128, db + kk * 2, (kb | kk) != 0);
    wg_commit();
    if (kb & 1) rg.next();
  }
  TL(11);
  const int row = 128 * mt + 64 * wg + r0;
  const float ga0 = __ldcg(&p.s->gate[row]), ga1 = __ldcg(&p.s->gate[row + 8]);
  const uint4* src = p.s->part + (((mt * 7 + jj) * 6 * 2 + wg) * 4) * 128 + tid;
  const uint32_t* cnt = &p.s->cnt_p[((mt * 7 + jj) * 2 + wg) * 8];
  float sum[32];
  auto add8 = [&](const uint4& pv, int v, bool first) {
    const float t[8] = {bf_lo(pv.x), bf_hi(pv.x), bf_lo(pv.y), bf_hi(pv.y), bf_lo(pv.z), bf_hi(pv.z), bf_lo(pv.w), bf_hi(pv.w)};
#pragma unroll
    for (int i = 0; i < 8; i++) sum[8 * v + i] = first ? t[i] : sum[8 * v + i] + t[i];
  };
  {
    if (lane < 2) wait_counter(cnt + lane, epoch * 2);
    __syncwarp();
    TL(24);
    uint4 pv[16];
#pragma unroll
    for (int i = 0; i < 16; i++) pv[i] = ld_cg(src + ((i >> 2) * 8 + (i & 3)) * 128);
    if (lane == 0) wait_counter(cnt + 2, epoch * 2);
    __syncwarp();
    TL(25);
    uint4 pw[8];
#pragma unroll
    for (int i = 0; i < 8; i++) pw[i] = ld_cg(src + ((4 + (i >> 2)) * 8 + (i & 3)) * 128);
#pragma unroll
    for (int i = 0; i < 16; i++) add8(pv[i], i & 3, i < 4);
#pragma unroll
    for (int i = 0; i < 8; i++) add8(pw[i], i & 3, false);
  }
  TL(12);
  wg_wait<0>();
  fence_regs(accA);
  fence_regs(accB);
  TL(13);
  const float gb0 = bf_round(1.f - ga0), gb1 = bf_round(1.f - ga1);
  const float gs0 = ga0 * (2.f / (float)(S_ * D_)), gs1 = ga1 * (2.f / (float)(S_ * D_));
  uint4* const o = reinterpret_cast<uint4*>(p.out + (size_t)row * D_ + 64 * jj + 8 * q);
#pragma unroll
  for (int h = 0; h < 2; h++) {
    const float gs = h ? gs1 : gs0, gb = h ? gb1 : gb0;
#pragma unroll
    for (int k = 0; k < 2; k++) {
      uint32_t w[4];
#pragma unroll
      for (int j = 0; j < 4; j++) {
        const int i = 16 * k + 4 * j + 2 * h;
        w[j] = pack2(fmaf(gs, accB[i], gb * (accA[i] + sum[i])), fmaf(gs, accB[i + 1], gb * (accA[i + 1] + sum[i + 1])));
      }
      const bool o1 = q & 1, o2 = q & 2;
      uint32_t a = __shfl_xor_sync(0xffffffffu, o1 ? w[0] : w[1], 1), b = __shfl_xor_sync(0xffffffffu, o1 ? w[2] : w[3], 1);
      if (o1) { w[0] = a; w[2] = b; } else { w[1] = a; w[3] = b; }
      a = __shfl_xor_sync(0xffffffffu, o2 ? w[0] : w[2], 2); b = __shfl_xor_sync(0xffffffffu, o2 ? w[1] : w[3], 2);
      if (o2) { w[0] = a; w[1] = b; } else { w[2] = a; w[3] = b; }
      o[h * D_ + 4 * k] = make_uint4(w[0], w[1], w[2], w[3]);
    }
  }
  if (lane == 0) *my_epoch = epoch;
  TL(14);
}

__device__ __forceinline__ void ring_issue(uint32_t sb, const Params& p, int qi, uint32_t slot, bool wait, uint32_t phase, int jj, uint32_t rank) {
  const CUtensorMap* m;
  int c0, c1, c2 = 0;
  bool half = false, is3d = false;
  if (qi < Q_G2) {
    const int nc = __popc(CMASK & ((1u << qi) - 1));
    if ((CMASK >> qi) & 1) {
      m = &p.ct; c0 = 64 * jj; c1 = 128 * nc + 64 * rank; half = nc == 3;
    } else {
      const int pass = qi >= Q_G1B;
      m = rank ? &p.wu : &p.wg; c0 = 0; c1 = 32 * (qi - nc - 14 * pass); c2 = 4 * jj + 2 * pass; is3d = true;
    }
  } else if (qi < Q_P3) {
    int o = jj + 1 + ((qi - Q_G2) >> 1);
    if (o >= 7) o -= 7;
    m = &p.wd; c0 = 64 * o; c1 = 256 * jj + 128 * (qi & 1) + 64 * rank;
  } else {
    m = &p.ct; c0 = 128 * (qi - Q_P3) + 64 * rank; c1 = 64 * jj; half = qi == Q_END - 1;
  }
  const uint32_t bar = BAR_FULL(sb, slot);
  const uint32_t dst = sb + SM_RING + slot * STAGE_BYTES + rank * 8192;
  if (wait) mbar_wait_cluster(BAR_EMPTY(sb, slot), phase);
  mbar_expect_tx(bar, half ? 8192 : 16384);
  if (is3d) tma3d_mc(dst, m, c0, c1, c2, bar);
  else if (!(half && rank)) tma2d_mc(dst, m, c0, c1, bar);
}

__device__ __forceinline__ void ffn_producer(uint32_t sb, int bid, const Params& p, int warp, int lane, int mt, int jj, uint32_t rank) {
  if (warp < 2) {
    if (lane == 0) {
      uint32_t slot = warp, phase = 0;
#pragma unroll 1
      for (int qi = NSTAGE + warp; qi < Q_END; qi += 2) {
        ring_issue(sb, p, qi, slot, true, phase, jj, rank);
        TL(10 + qi);
        slot += 2;
        if (slot >= NSTAGE) { slot -= NSTAGE; phase ^= 1; }
      }
    }
  } else {
    const int wg = warp - 2;
    if (wg == 0) {
      if (lane == 0) { prefetch_tmap(&p.wd); prefetch_tmap(&p.yt); }
      uint32_t* const my_epoch = &p.s->epoch[blockIdx.x * 12 + 10];
      const uint32_t epoch = ld_relaxed(my_epoch) + 1;
      mbar_wait(BAR_XFREE(sb), 0);
      TL(3);
      bool todo = lane < 7;
      uint32_t n = 0;
      while (__any_sync(0xffffffffu, todo)) {
        if (todo) {
          uint32_t v;
          asm volatile("ld.acquire.gpu.global.u32 %0, [%1];" : "=r"(v) : "l"(&p.s->cnt_y[lane * 32]) : "memory");
          if ((int32_t)(v - epoch * (lane ? 16 : 17)) >= 0 || ++n > SPIN_LIMIT) {
            fence_async();
            mbar_expect_tx(BAR_Y(sb, lane), 16384);
            tma3d(sb + SM_X + lane * 16384, &p.yt, 0, 64 * lane, 2 * mt, BAR_Y(sb, lane));
            todo = false;
          }
        }
      }
      TL(4);
      if (lane == 0) *my_epoch = epoch;
    } else {
      mbar_wait(BAR_X(sb, PFAT), 0);
      if (lane < 6) {
        int row = 176 + 3 * bid + (lane >> 1);
        if (row >= D_) row -= D_;
        l2_prefetch(((lane & 1) ? p.pwu : p.pwg) + row * F_, F_ * 2);
      }
      TL(2);
      bar_sync(7, 160);
      if (lane == 0) { fence_gpu(); red_add(&p.s->cnt_x1[jj * 32], 1); l2_prefetch(p.pwd + bid * 16 * D_, 32 * D_); }
      TL(3);
    }
#pragma unroll 1
    for (int c = 0; c < 3; c++) {
      bar_sync(1 + 3 * wg + c, 160);
      if (lane < 2) {
        int o = jj + 1 + 2 * c + lane;
        if (o >= 7) o -= 7;
        fence_gpu();
        red_add(&p.s->cnt_p[((mt * 7 + o) * 2 + wg) * 8 + c], 1);
      }
      TL(5 + c);
    }
  }
}

__device__ __forceinline__ void spectral_cta(uint32_t sb, uint8_t* smem, const Params& p, int sc, int wg) {
  const int t384 = threadIdx.x, lane = t384 & 31, warp12 = t384 >> 5, tid = t384 & 127;
  const int warp = tid >> 5, q = lane & 3, r0 = 16 * warp + (lane >> 2);
  const int sl0 = 6 * sc + min(sc, 8), nsl = sc < 8 ? 7 : 6;
  if (t384 == 320) {
#pragma unroll 1
    for (int i = 0; i < nsl; i++) {
      mbar_expect_tx(BAR_X(sb, i), 2 * SLAB_BYTES);
      bulk_g2s(sb + SP_Z + 2 * i * SLAB_BYTES, p.w_r + (sl0 + i) * 16 * DF_, SLAB_BYTES, BAR_X(sb, i));
      bulk_g2s(sb + SP_Z + (2 * i + 1) * SLAB_BYTES, p.w_i + (sl0 + i) * 16 * DF_, SLAB_BYTES, BAR_X(sb, i));
    }
    if (sc < 19) {
      const uint32_t bytes = (sc < 18 ? 108 : 104) * D_ * 2;
      mbar_expect_tx(BAR_Y(sb, 6), bytes + 24576);
      bulk_g2s(sb + SP_G, p.px + (size_t)sc * 108 * D_, bytes, BAR_Y(sb, 6));
      bulk_g2s(sb + SP_TW, p.spec, 24576, BAR_Y(sb, 6));
      prefetch_tmap(&p.x1);
    }
  }
  uint32_t* const my_epoch = &p.s->epoch[blockIdx.x * 12 + warp12];
  const uint32_t epoch = ld_relaxed(my_epoch) + 1;
  __syncwarp();
  asm volatile("barrier.cluster.wait.acquire.aligned;" ::: "memory");
#pragma unroll 2
  for (int un = wg; un < 8 * nsl; un += 3) {
    const int i = un >> 3, sl = sl0 + i, pr = 16 * (un & 7) + 4 * (lane >> 3) + warp, r = lane & 7;
    mbar_wait(BAR_X(sb, i), 0);
    if (pr < 113) {
      const uint16_t* w = reinterpret_cast<const uint16_t*>(smem + SP_Z + 2 * i * SLAB_BYTES) + r * DF_ + 2 * pr;
      const uint32_t m = pr < 112 ? 0xffffffffu : 0xffffu;
      p.s->wt[pr * 1024 + sl * 8 + (r ^ ((sl >> 2) & 6))] =
          make_uint4((w[0] | ((uint32_t)w[1] << 16)) & m, (w[16 * DF_] | ((uint32_t)w[16 * DF_ + 1] << 16)) & m,
                     (w[8 * DF_] | ((uint32_t)w[8 * DF_ + 1] << 16)) & m, (w[24 * DF_] | ((uint32_t)w[24 * DF_ + 1] << 16)) & m);
    }
  }
  __syncthreads();
  if (t384 == 352) { fence_gpu(); red_add(&p.s->cnt_w[0], 1); }
  TL(1);
  if (sc < 19) {
    const uint4* gw4 = reinterpret_cast<const uint4*>(p.gate_w);
    const uint4 ga = __ldg(gw4 + lane), gb = lane < 24 ? __ldg(gw4 + 32 + lane) : make_uint4(0, 0, 0, 0);
    mbar_wait(BAR_Y(sb, 6), 0);
    float mine = 0.f;
#pragma unroll 3
    for (int u = 0; u < 9; u++) {
      const uint4* xr = reinterpret_cast<const uint4*>(smem + SP_G + (warp12 * 9 + u) * (D_ * 2));
      const uint4 xa = xr[lane], xb = lane < 24 ? xr[32 + lane] : make_uint4(0, 0, 0, 0);
      float s = 0.f;
      auto dot2 = [&](uint32_t a, uint32_t b) {
        const uint32_t pr = pack2(bf_lo(a) * bf_lo(b), bf_hi(a) * bf_hi(b));
        s += bf_lo(pr) + bf_hi(pr);
      };
      dot2(xa.x, ga.x); dot2(xa.y, ga.y); dot2(xa.z, ga.z); dot2(xa.w, ga.w);
      dot2(xb.x, gb.x); dot2(xb.y, gb.y); dot2(xb.z, gb.z); dot2(xb.w, gb.w);
#pragma unroll
      for (int o = 16; o > 0; o >>= 1) s += __shfl_xor_sync(0xffffffffu, s, o);
      if (lane == u) mine = s;
    }
    const int row = sc * 108 + warp12 * 9 + lane;
    if (lane < 9 && row < S_) p.s->gate[row] = bf_round(1.f / (1.f + __expf(-bf_round(mine))));
  }
  TL(2);
  if (sc == 19) return;
  uint32_t fc[16], fs[16];
#pragma unroll
  for (int i = 0; i < 4; i++) {
    const uint4 a = __ldg(reinterpret_cast<const uint4*>(p.spec->f64) + i * 128 + tid);
    const uint4 b = __ldg(reinterpret_cast<const uint4*>(p.spec->f64) + (4 + i) * 128 + tid);
    fc[4 * i] = a.x; fc[4 * i + 1] = a.y; fc[4 * i + 2] = a.z; fc[4 * i + 3] = a.w;
    fs[4 * i] = b.x; fs[4 * i + 1] = b.y; fs[4 * i + 2] = b.z; fs[4 * i + 3] = b.w;
  }
  __syncthreads();
  const int nrnd = (sc == 18 && wg == 2) ? 1 : 2;
  if (tid == 32) {
    wait_counter(&p.s->cnt_w[0], epoch * NSPEC);
    fence_async();
    for (int rnd = 0; rnd < nrnd; rnd++) {
      const int item = wg + 3 * rnd;
      mbar_expect_tx(BAR_Y(sb, item), 16384);
      bulk_g2s(sb + SP_W + item * 16384, p.s->wt + (6 * sc + item) * 1024, 16384, BAR_Y(sb, item));
    }
  } else if (tid == 0) {
#pragma unroll 1
    for (int rnd = 0; rnd < nrnd; rnd++) {
      const int item = wg + 3 * rnd, pr = 6 * sc + item;
      const int ra = pr < 112 ? 4 * pr : 1;
      wait_counter(&p.s->cnt_x1[(ra >> 6) * 32], epoch * 16);
      fence_async();
      const uint32_t bar = BAR_FULL(sb, item), z = sb + SP_Z + item * 16384;
      mbar_expect_tx(bar, 16384);
      tma2d(z, &p.x1, 0, ra * 64, bar);
      tma2d(z + 4096, &p.x1, 0, (4 * pr + 2) * 64, bar);
      tma2d(z + 8192, &p.x1, 0, (pr ? 4 * pr + 1 : D_) * 64, bar);
      tma2d(z + 12288, &p.x1, 0, (4 * pr + 3) * 64, bar);
    }
  }
  __syncwarp();
  fence_regs(fc); fence_regs(fs);
  TL(3);
  const uint64_t dT_n = mk_desc(sb + SP_T, 8192, 1024, 1);
#pragma unroll 1
  for (int rnd = 0; rnd < nrnd; rnd++) {
    const int item = wg + 3 * rnd, pr = 6 * sc + item;
    const uint32_t z = sb + SP_Z + item * 16384;
    mbar_wait(BAR_FULL(sb, item), 0);
    TL(4 + 8 * rnd);
    if (rnd == 0 && wg > 0) bar_sync(3 + wg, 256);
    float aR[32], aI[32];
    {
      const uint64_t dr = mk_desc(z, 4096, 512, 2), di = mk_desc(z + 8192, 4096, 512, 2);
      wg_fence();
#pragma unroll
      for (int kk = 0; kk < 4; kk++) {
        wgmma_rs_n64<1, 1>(aR, fc[4 * kk], fc[4 * kk + 1], fc[4 * kk + 2], fc[4 * kk + 3], dr + kk * 64, kk != 0);
        wgmma_rs_n64<1, 1>(aI, fc[4 * kk], fc[4 * kk + 1], fc[4 * kk + 2], fc[4 * kk + 3], di + kk * 64, kk != 0);
      }
#pragma unroll
      for (int kk = 0; kk < 4; kk++) {
        wgmma_rs_n64<1, 1>(aR, fs[4 * kk], fs[4 * kk + 1], fs[4 * kk + 2], fs[4 * kk + 3], di + kk * 64, 1);
        wgmma_rs_n64<-1, 1>(aI, fs[4 * kk], fs[4 * kk + 1], fs[4 * kk + 2], fs[4 * kk + 3], dr + kk * 64, 1);
      }
      wg_commit();
      if (rnd == 0 && wg < 2) bar_arrive(4 + wg, 256);
      if (rnd == 1 && tid == 0) { fence_gpu(); red_add(&p.s->cnt_y[((pr - 3) >> 4) * 32], 1); }
      wg_wait<0>();
      fence_regs(aR); fence_regs(aI);
    }
    TL(5 + 8 * rnd);
    uint32_t fa[16], fb[16];
#pragma unroll
    for (int v = 0; v < 8; v++) {
      const float4 tw = *reinterpret_cast<const float4*>(smem + SP_TW + v * 2048 + tid * 16);
      fa[v] = pack2(aR[2 * v] * tw.x + aI[2 * v] * tw.y, aR[2 * v + 1] * tw.z + aI[2 * v + 1] * tw.w);
      fa[8 + v] = pack2(aI[2 * v] * tw.x - aR[2 * v] * tw.y, aI[2 * v + 1] * tw.z - aR[2 * v + 1] * tw.w);
      fb[v] = pack2(aR[16 + 2 * v] * tw.x + aI[16 + 2 * v] * tw.y, aR[16 + 2 * v + 1] * tw.z + aI[16 + 2 * v + 1] * tw.w);
      fb[8 + v] = pack2(aI[16 + 2 * v] * tw.x - aR[16 + 2 * v] * tw.y, aI[16 + 2 * v + 1] * tw.z - aR[16 + 2 * v + 1] * tw.w);
    }
    fence_regs(fa); fence_regs(fb);
    wg_fence();
#pragma unroll
    for (int kk = 0; kk < 4; kk++) {
      wgmma_rs_n64<1, 1>(aR, fa[4 * kk], fa[4 * kk + 1], fa[4 * kk + 2], fa[4 * kk + 3], dT_n + kk * 128, kk != 0);
      wgmma_rs_n64<1, 1>(aI, fb[4 * kk], fb[4 * kk + 1], fb[4 * kk + 2], fb[4 * kk + 3], dT_n + kk * 128, kk != 0);
    }
    wg_commit();
    mbar_wait(BAR_Y(sb, item), 0);
    wg_wait<0>();
    fence_regs(aR); fence_regs(aI);
    TL(6 + 8 * rnd);
    {
      const uint8_t* wp = smem + SP_W + item * 16384 + q * 1024 + warp * 128 + (((lane >> 2) ^ (2 * q)) << 4);
#pragma unroll
      for (int jb = 0; jb < 4; jb++) {
        const uint4 w0 = *reinterpret_cast<const uint4*>(wp + jb * 4096), w1 = *reinterpret_cast<const uint4*>(wp + jb * 4096 + 512);
        auto cm = [&](const float* a, float r0_, float i0, float r1, float i1, uint32_t& re, uint32_t& im) {
          re = pack2(a[0] * r0_ - a[16] * i0, a[1] * r1 - a[17] * i1);
          im = pack2(a[0] * i0 + a[16] * r0_, a[1] * i1 + a[17] * r1);
        };
        cm(aR + 4 * jb, bf_lo(w0.x), bf_lo(w0.y), bf_lo(w1.x), bf_lo(w1.y), fa[2 * jb], fa[8 + 2 * jb]);
        cm(aR + 4 * jb + 2, bf_lo(w0.z), bf_lo(w0.w), bf_lo(w1.z), bf_lo(w1.w), fa[2 * jb + 1], fa[9 + 2 * jb]);
        cm(aI + 4 * jb, bf_hi(w0.x), bf_hi(w0.y), bf_hi(w1.x), bf_hi(w1.y), fb[2 * jb], fb[8 + 2 * jb]);
        cm(aI + 4 * jb + 2, bf_hi(w0.z), bf_hi(w0.w), bf_hi(w1.z), bf_hi(w1.w), fb[2 * jb + 1], fb[9 + 2 * jb]);
      }
    }
    fence_regs(fa); fence_regs(fb);
    wg_fence();
#pragma unroll
    for (int kk = 0; kk < 4; kk++) {
      wgmma_rs_n64<1, 0>(aR, fa[4 * kk], fa[4 * kk + 1], fa[4 * kk + 2], fa[4 * kk + 3], dT_n + kk * 2, kk != 0);
      wgmma_rs_n64<1, 0>(aI, fb[4 * kk], fb[4 * kk + 1], fb[4 * kk + 2], fb[4 * kk + 3], dT_n + kk * 2, kk != 0);
    }
    wg_commit();
    wg_wait<0>();
    fence_regs(aR); fence_regs(aI);
    TL(7 + 8 * rnd);
#pragma unroll
    for (int v = 0; v < 8; v++) {
      const float4 tw = *reinterpret_cast<const float4*>(smem + SP_TW + v * 2048 + tid * 16);
      fa[v] = pack2(aR[2 * v] * tw.x - aR[16 + 2 * v] * tw.y, aR[2 * v + 1] * tw.z - aR[16 + 2 * v + 1] * tw.w);
      fb[v] = pack2(aR[16 + 2 * v] * tw.x + aR[2 * v] * tw.y, aR[16 + 2 * v + 1] * tw.z + aR[2 * v + 1] * tw.w);
      fa[8 + v] = pack2(aI[2 * v] * tw.x - aI[16 + 2 * v] * tw.y, aI[2 * v + 1] * tw.z - aI[16 + 2 * v + 1] * tw.w);
      fb[8 + v] = pack2(aI[16 + 2 * v] * tw.x + aI[2 * v] * tw.y, aI[16 + 2 * v + 1] * tw.z + aI[2 * v + 1] * tw.w);
    }
    bar_sync(1 + wg, 128);
    {
      const int row = 16 * warp + (lane & 7) + 8 * ((lane >> 3) & 1);
#pragma unroll
      for (int u = 0; u < 4; u++) {
        const uint32_t a = z + row * 128 + (((2 * u + (lane >> 4)) ^ (row & 7)) << 4);
        stmatrix_x4(a, fa[4 * u], fa[4 * u + 1], fa[4 * u + 2], fa[4 * u + 3]);
        stmatrix_x4(a + 8192, fb[4 * u], fb[4 * u + 1], fb[4 * u + 2], fb[4 * u + 3]);
      }
    }
    fence_async_smem();
    bar_sync(1 + wg, 128);
    TL(8 + 8 * rnd);
    {
      const uint64_t dr = mk_desc(z, 8192, 1024, 1), di = mk_desc(z + 8192, 8192, 1024, 1);
      wg_fence();
#pragma unroll
      for (int kk = 0; kk < 4; kk++) {
        wgmma_rs_n64<1, 1>(aR, fc[4 * kk], fc[4 * kk + 1], fc[4 * kk + 2], fc[4 * kk + 3], dr + kk * 128, kk != 0);
        wgmma_rs_n64<1, 1>(aI, fc[4 * kk], fc[4 * kk + 1], fc[4 * kk + 2], fc[4 * kk + 3], di + kk * 128, kk != 0);
      }
#pragma unroll
      for (int kk = 0; kk < 4; kk++) {
        wgmma_rs_n64<-1, 1>(aR, fs[4 * kk], fs[4 * kk + 1], fs[4 * kk + 2], fs[4 * kk + 3], di + kk * 128, 1);
        wgmma_rs_n64<1, 1>(aI, fs[4 * kk], fs[4 * kk + 1], fs[4 * kk + 2], fs[4 * kk + 3], dr + kk * 128, 1);
      }
      wg_commit();
      wg_wait<0>();
      fence_regs(aR); fence_regs(aI);
    }
    TL(9 + 8 * rnd);
    const bool edge = pr == 0 || pr == 112;
    if (edge) {
#pragma unroll
      for (int i = 0; i < 16; i++) aR[i] *= 0.5f;
    }
#pragma unroll
    for (int h = 0; h < 2; h++) {
      __nv_bfloat16* dst = p.s->yt + (size_t)(4 * pr) * S_ + 32 * (r0 + 8 * h) + 8 * q;
      auto st = [&](bool ok, int jrow, const float* a) {
        if (ok)
          *reinterpret_cast<uint4*>(dst + jrow * S_) =
              make_uint4(pack2(a[2 * h], a[2 * h + 1]), pack2(a[4 + 2 * h], a[5 + 2 * h]), pack2(a[8 + 2 * h], a[9 + 2 * h]), pack2(a[12 + 2 * h], a[13 + 2 * h]));
      };
      st(true, pr < 112 ? 0 : 1 - D_, aR); st(!edge, 1, aI); st(pr < 112, 2, aR + 16); st(pr < 112, 3, aI + 16);
    }
    bar_sync(1 + wg, 128);
    if (rnd == nrnd - 1 && tid == 0) { fence_gpu(); red_add(&p.s->cnt_y[(pr < 112 ? pr >> 4 : 0) * 32], 1); }
    TL(10 + 8 * rnd);
  }
  if (lane == 0) *my_epoch = epoch;
}

__global__ void __cluster_dims__(2, 1, 1) __launch_bounds__(384, 1)
fused_kernel(const __grid_constant__ Params p) {
  extern __shared__ __align__(1024) uint8_t smem[];
  const uint32_t sb = smem_u32(smem);
  TL(0);
  const uint32_t rank = blockIdx.x & 1;
  const int hc = blockIdx.x >> 1;
  int grp, jj;
  if (hc < 4) { grp = 8; jj = hc; }
  else if (hc < 36) { grp = (hc - 4) & 7; jj = (hc - 4) >> 3; }
  else if (hc < 57) { jj = (hc - 36) / 7; grp = 1 + (hc - 36) - 7 * jj; jj += 4; }
  else if (hc < 60) { grp = 0; jj = hc - 53; }
  else { grp = 8; jj = hc - 56; }
  const int mt = 2 * grp + rank, bid = 2 * (7 * grp + jj) + rank;
  if (threadIdx.x == 256) {
#pragma unroll
    for (int i = 0; i < NSTAGE; i++) { mbar_init(BAR_FULL(sb, i), 1); mbar_init(BAR_EMPTY(sb, i), 4); }
    asm volatile("fence.mbarrier_init.release.cluster;" ::: "memory");
  } else if (threadIdx.x == 320) {
#pragma unroll
    for (int i = 0; i < NSTAGE; i++) { mbar_init(BAR_X(sb, i), 1); mbar_init(BAR_Y(sb, i), 1); }
    mbar_init(BAR_XFREE(sb), 2);
    asm volatile("fence.mbarrier_init.release.cluster;" ::: "memory");
  } else if (threadIdx.x == 288) {
    prefetch_tmap(rank ? &p.wu : &p.wg); prefetch_tmap(&p.ct);
  }
  __syncwarp();
  asm volatile("barrier.cluster.arrive.relaxed.aligned;" ::: "memory");
  const int wg = __shfl_sync(0xffffffffu, threadIdx.x >> 7, 0);
  if (bid >= NFFN) {
    spectral_cta(sb, smem, p, bid - NFFN, wg);
  } else if (wg < 2) {
    asm volatile("setmaxnreg.inc.sync.aligned.u32 232;");
    asm volatile("barrier.cluster.wait.acquire.aligned;" ::: "memory");
    TL(1);
    ffn_consumer(sb, smem, p, bid, wg, threadIdx.x & 127, mt, jj);
  } else {
    asm volatile("setmaxnreg.dec.sync.aligned.u32 40;");
    if (threadIdx.x == 320) {
      mbar_expect_tx(BAR_X(sb, 0), 16384);
      tma2d(sb + SM_X, &p.x, 0, 128 * mt, BAR_X(sb, 0));
    }
    __syncwarp();
    asm volatile("barrier.cluster.wait.acquire.aligned;" ::: "memory");
    TL(1);
    if (threadIdx.x == 320) {
      constexpr int order[13] = {XORDER};
#pragma unroll
      for (int i = 0; i < 13; i++) {
        if (order[i] < 8) {
          ring_issue(sb, p, order[i], order[i], false, 0, jj, rank);
        } else {
          const int kb = order[i] - 10;
          mbar_expect_tx(BAR_X(sb, kb), 16384);
          tma2d(sb + SM_X + kb * 16384, &p.x, 64 * kb, 128 * mt, BAR_X(sb, kb));
        }
      }
      TL(2);
    } else if (threadIdx.x == 352) {
      l2_prefetch(reinterpret_cast<const char*>(p.ctab) + bid * 3584, 3584);
      l2_prefetch(p.pwg + (64 + bid) * F_, F_ * 2);
      l2_prefetch(p.pwu + (64 + bid) * F_, F_ * 2);
    }
    __syncwarp();
    ffn_producer(sb, bid, p, (threadIdx.x >> 5) & 3, threadIdx.x & 31, mt, jj, rank);
  }
}

typedef CUresult (*EncodeFn)(CUtensorMap*, CUtensorMapDataType, cuuint32_t, void*, const cuuint64_t*, const cuuint64_t*,
                             const cuuint32_t*, const cuuint32_t*, CUtensorMapInterleave, CUtensorMapSwizzle,
                             CUtensorMapL2promotion, CUtensorMapFloatOOBfill);

void make_map(EncodeFn fn, CUtensorMap* m, const void* base, int rank, const cuuint64_t* dims, const cuuint64_t* strides,
              const cuuint32_t* box, CUtensorMapSwizzle sw) {
  const cuuint32_t es[3] = {1, 1, 1};
  fn(m, CU_TENSOR_MAP_DATA_TYPE_BFLOAT16, rank, const_cast<void*>(base), dims, strides, box, es,
     CU_TENSOR_MAP_INTERLEAVE_NONE, sw, CU_TENSOR_MAP_L2_PROMOTION_L2_256B, CU_TENSOR_MAP_FLOAT_OOB_FILL_NONE);
}

}

extern "C" void kernel_launch(void* const* d_in, const int* in_sizes, int n_in, void* d_out, int out_size) {
  const __nv_bfloat16* x = (const __nv_bfloat16*)d_in[0];
  const __nv_bfloat16* w_r = (const __nv_bfloat16*)d_in[1];
  const __nv_bfloat16* w_i = (const __nv_bfloat16*)d_in[2];
  const __nv_bfloat16* wg = (const __nv_bfloat16*)d_in[4];
  const __nv_bfloat16* wu = (const __nv_bfloat16*)d_in[5];
  const __nv_bfloat16* wd = (const __nv_bfloat16*)d_in[6];
  const __nv_bfloat16* gate_w = (const __nv_bfloat16*)d_in[7];

  void* fnp = nullptr;
  cudaDriverEntryPointQueryResult qr;
  cudaGetDriverEntryPoint("cuTensorMapEncodeTiled", &fnp, cudaEnableDefault, &qr);
  EncodeFn fn = (EncodeFn)fnp;
  void *ctab, *spec, *scr;
  cudaGetSymbolAddress(&ctab, g_ctab);
  cudaGetSymbolAddress(&spec, g_spec);
  cudaGetSymbolAddress(&scr, g_scratch);
  const void* x1t = (const char*)scr + offsetof(Scratch, x1t);
  const void* yt = (const char*)scr + offsetof(Scratch, yt);
  Params p;
  p.s = (Scratch*)scr; p.out = (__nv_bfloat16*)d_out;
  p.px = x; p.w_r = w_r; p.w_i = w_i; p.gate_w = gate_w; p.pwg = wg; p.pwu = wu; p.pwd = wd;
  p.ctab = (const tab::Table*)ctab; p.spec = (const tab::Spec*)spec;
  {
    const cuuint64_t d[2] = {D_, S_}, s[1] = {D_ * 2};
    const cuuint32_t b[2] = {64, 128};
    make_map(fn, &p.x, x, 2, d, s, b, CU_TENSOR_MAP_SWIZZLE_128B);
  }
  {
    const cuuint64_t d[3] = {64, D_, F_ / 64}, s[2] = {F_ * 2, 128};
    const cuuint32_t b[3] = {64, 32, 2};
    make_map(fn, &p.wg, wg, 3, d, s, b, CU_TENSOR_MAP_SWIZZLE_128B);
    make_map(fn, &p.wu, wu, 3, d, s, b, CU_TENSOR_MAP_SWIZZLE_128B);
  }
  {
    const cuuint64_t d[2] = {D_, F_}, s[1] = {D_ * 2};
    const cuuint32_t b[2] = {64, 64};
    make_map(fn, &p.wd, wd, 2, d, s, b, CU_TENSOR_MAP_SWIZZLE_128B);
  }
  {
    const cuuint64_t d[2] = {D_, D_}, s[1] = {D_ * 2};
    const cuuint32_t b[2] = {64, 64};
    make_map(fn, &p.ct, ctab, 2, d, s, b, CU_TENSOR_MAP_SWIZZLE_128B);
  }
  {
    const cuuint64_t d[2] = {32, D_ * 64}, s[1] = {64};
    const cuuint32_t b[2] = {32, 64};
    make_map(fn, &p.x1, x1t, 2, d, s, b, CU_TENSOR_MAP_SWIZZLE_64B);
  }
  {
    const cuuint64_t d[3] = {64, D_, S_ / 64}, s[2] = {S_ * 2, 128};
    const cuuint32_t b[3] = {64, 64, 2};
    make_map(fn, &p.yt, yt, 3, d, s, b, CU_TENSOR_MAP_SWIZZLE_128B);
  }
  cudaFuncSetAttribute(fused_kernel, cudaFuncAttributeMaxDynamicSharedMemorySize, SM_TOTAL);
  fused_kernel<<<NCTA, 384, SM_TOTAL, cudaStreamPerThread>>>(p, x, w_r, w_i, gate_w, wd, (__nv_bfloat16*)d_out);
}
```

```cpp
#include <cuda_runtime.h>
#include <cuda_bf16.h>
#include <cuda.h>
#include <stdint.h>
#include <stddef.h>

namespace {

constexpr int S_ = 2048, D_ = 448, F_ = 1792, DF_ = 225;
constexpr int NFFN = 112, NSPEC = 20, NCTA = NFFN + NSPEC;
constexpr int NSTAGE = 7, STAGE_BYTES = 16384;
constexpr int SM_X = 0, SM_RING = 114688, SM_BAR = 229376, SM_TOTAL = SM_BAR + 512;
constexpr int SP_Z = 0, SP_W = 98304, SP_TW = 198656, SP_T = 215040, SLAB_BYTES = 16 * DF_ * 2;
constexpr uint32_t SPIN_LIMIT = 1u << 20;

namespace tab {
constexpr double PI = 3.14159265358979323846264338327950288;
constexpr double csin(double x) {
  double t = x, s = x;
  for (int i = 1; i < 20; i++) { t = -t * x * x / ((2 * i) * (2 * i + 1)); s += t; }
  return s;
}
constexpr double ccos(double x) {
  double t = 1, s = 1;
  for (int i = 1; i < 20; i++) { t = -t * x * x / ((2 * i - 1) * (2 * i)); s += t; }
  return s;
}
constexpr uint32_t to_bf16(double v) {
  uint32_t sign = v < 0 ? 0x8000u : 0u;
  double a = v < 0 ? -v : v;
  if (a < 1e-12) return 0;
  int e = 0;
  while (a >= 2.0) { a /= 2; e++; }
  while (a < 1.0) { a *= 2; e--; }
  double m = a * 128.0;
  int mi = (int)m;
  double fr = m - mi;
  if (fr > 0.5 || (fr == 0.5 && (mi & 1))) mi++;
  if (mi == 256) { mi = 128; e++; }
  return sign | (uint32_t)((e + 127) << 7) | (uint32_t)(mi - 128);
}
struct Base { uint32_t v[448]; };
constexpr Base make_base() {
  Base b{};
  for (int m = 0; m < 448; m++) {
    int mm = m > 224 ? m - 448 : m;
    double ang = 2 * PI * mm / 448.0;
    b.v[m] = to_bf16(ccos(ang)) | (to_bf16(-csin(ang)) << 16);
  }
  return b;
}
constexpr Base base = make_base();
struct Row { uint32_t v[224]; };
constexpr Row make_row(int d) {
  Row r{};
  r.v[0] = 0x3f80u | ((d & 1) ? 0xbf800000u : 0x3f800000u);
  int m = 0;
  for (int c = 1; c < 224; c++) { m += d; if (m >= 448) m -= 448; r.v[c] = base.v[m]; }
  return r;
}
struct Table { Row r[448]; };
constexpr Table make_table() {
  Table t{};
  for (int d = 0; d < 448; d++) t.r[d] = make_row(d);
  return t;
}
struct Cs { double c[2048], s[2048]; };
constexpr Cs make_cs() {
  Cs t{};
  for (int m = 0; m <= 256; m++) {
    const double a = 2 * PI * m / 2048.0, c = ccos(a), s = csin(a);
    t.c[m] = c; t.s[m] = s;
    t.c[512 - m] = s; t.s[512 - m] = c;
  }
  for (int m = 513; m < 2048; m++) { t.c[m] = -t.s[m - 512]; t.s[m] = t.c[m - 512]; }
  return t;
}
constexpr Cs cs = make_cs();
struct Spec {
  uint32_t fo[2048], fot[2048];
  uint16_t t32[4096];
  uint32_t fe[2048];
  uint32_t tw[2048];
};
constexpr uint32_t blk(int h, int c, int a) { return to_bf16(h == c ? cs.c[a & 2047] : (h ? -cs.s[a & 2047] : cs.s[a & 2047])); }
constexpr Spec make_spec() {
  Spec t{};
  for (int row = 0; row < 64; row++)
    for (int col = 0; col < 64; col++) {
      const int c = row & 31, k2 = col & 31, n2 = 8 * ((c >> 1) & 3) + 2 * (c >> 3) + (c & 1), m = 64 * ((n2 * k2) & 31);
      const double v = (row >> 5) == (col >> 5) ? cs.c[m] : (row < 32 ? -cs.s[m] : cs.s[m]);
      t.t32[row * 64 + (((col >> 3) ^ (row & 7)) << 3) + (col & 7)] = (uint16_t)to_bf16(v);
    }
  for (int th = 0; th < 128; th++)
    for (int i = 0; i < 16; i++) {
      const int r = 8 * (th >> 5) + ((th & 31) >> 2), h = i & 1, c = i >> 3, m = 8 * ((i >> 1) & 3) + 2 * (th & 3);
      const int o = ((i >> 2) * 128 + th) * 4 + (i & 3);
      t.fe[o] = blk(h, c, 64 * m * r) | (blk(h, c, 64 * (m + 1) * r) << 16);
      t.fo[o] = blk(h, c, 32 * (2 * m + 1) * r) | (blk(h, c, 32 * (2 * m + 3) * r) << 16);
      t.fot[o] = blk(h, c, 32 * (2 * r + 1) * m) | (blk(h, c, 32 * (2 * r + 1) * (m + 1)) << 16);
      const int k1 = r + 32 * h, n2 = 8 * (th & 3) + 2 * ((i >> 1) & 3);
      t.tw[o] = blk(0, c, n2 * k1) | (blk(0, c, (n2 + 1) * k1) << 16);
    }
  return t;
}
}
}

__device__ __align__(1024) const tab::Table g_ctab = tab::make_table();
__device__ __align__(1024) const tab::Spec g_spec = tab::make_spec();

struct Scratch {
  uint32_t cnt_w[32];
  uint32_t cnt_x1[7 * 32];
  uint32_t cnt_y[7 * 32];
  uint32_t cnt_p[16 * 7 * 2 * 8];
  uint32_t epoch[NCTA * 12 + 240];
  float gate[S_];
  __nv_bfloat16 x1t[(D_ + 1) * S_];
  __nv_bfloat16 yt[D_ * S_];
  uint4 wt[114 * 1024];
  uint4 part[16 * 7 * 6 * 2 * 4 * 128];
};
static_assert(offsetof(Scratch, x1t) % 1024 == 0, "alignment");
__device__ __align__(1024) Scratch g_scratch;
#define TL(i)

namespace {

struct Params {
  Scratch* s;
  __nv_bfloat16* out;
  const __nv_bfloat16 *px, *w_r, *w_i, *gate_w, *pwg, *pwu, *pwd;
  const tab::Table* ctab;
  const tab::Spec* spec;
  CUtensorMap x, wg, wu, wd, ct, x1, yt;
};

__device__ __forceinline__ uint32_t smem_u32(const void* p) { return (uint32_t)__cvta_generic_to_shared(p); }
__device__ __forceinline__ void mbar_init(uint32_t bar, uint32_t cnt) {
  asm volatile("mbarrier.init.shared::cta.b64 [%0], %1;" ::"r"(bar), "r"(cnt) : "memory");
}
__device__ __forceinline__ void mbar_expect_tx(uint32_t bar, uint32_t bytes) {
  asm volatile("mbarrier.arrive.expect_tx.shared::cta.b64 _, [%0], %1;" ::"r"(bar), "r"(bytes) : "memory");
}
__device__ __forceinline__ void mbar_arrive(uint32_t bar) {
  asm volatile("mbarrier.arrive.shared::cta.b64 _, [%0];" ::"r"(bar) : "memory");
}
__device__ __forceinline__ void mbar_arrive_cluster(uint32_t bar, uint32_t cta) {
  asm volatile("{\n.reg .b32 ra;\nmapa.shared::cluster.u32 ra, %0, %1;\n"
               "mbarrier.arrive.shared::cluster.b64 _, [ra];\n}" ::"r"(bar), "r"(cta) : "memory");
}
__device__ __forceinline__ void mbar_wait(uint32_t bar, uint32_t parity) {
  uint32_t ok, n = 0;
  do {
    asm volatile("{\n.reg .pred p;\nmbarrier.try_wait.parity.shared::cta.b64 p, [%1], %2;\nselp.u32 %0, 1, 0, p;\n}"
                 : "=r"(ok) : "r"(bar), "r"(parity) : "memory");
  } while (!ok && ++n < SPIN_LIMIT);
}
__device__ __forceinline__ void mbar_wait_cluster(uint32_t bar, uint32_t parity) {
  uint32_t ok, n = 0;
  do {
    asm volatile("{\n.reg .pred p;\nmbarrier.try_wait.parity.acquire.cluster.shared::cta.b64 p, [%1], %2;\nselp.u32 %0, 1, 0, p;\n}"
                 : "=r"(ok) : "r"(bar), "r"(parity) : "memory");
  } while (!ok && ++n < SPIN_LIMIT);
}
__device__ __forceinline__ void tma2d(uint32_t dst, const CUtensorMap* m, int c0, int c1, uint32_t bar) {
  asm volatile("cp.async.bulk.tensor.2d.shared::cluster.global.mbarrier::complete_tx::bytes [%0], [%1, {%3, %4}], [%2];"
               ::"r"(dst), "l"(m), "r"(bar), "r"(c0), "r"(c1) : "memory");
}
__device__ __forceinline__ void tma3d(uint32_t dst, const CUtensorMap* m, int c0, int c1, int c2, uint32_t bar) {
  asm volatile("cp.async.bulk.tensor.3d.shared::cluster.global.mbarrier::complete_tx::bytes [%0], [%1, {%3, %4, %5}], [%2];"
               ::"r"(dst), "l"(m), "r"(bar), "r"(c0), "r"(c1), "r"(c2) : "memory");
}
__device__ __forceinline__ void tma4d(uint32_t dst, const CUtensorMap* m, int c2, uint32_t bar) {
  asm volatile("cp.async.bulk.tensor.4d.shared::cluster.global.mbarrier::complete_tx::bytes [%0], [%1, {%4, %4, %3, %4}], [%2];"
               ::"r"(dst), "l"(m), "r"(bar), "r"(c2), "r"(0) : "memory");
}
__device__ __forceinline__ void tma2d_mc(uint32_t dst, const CUtensorMap* m, int c0, int c1, uint32_t bar) {
  asm volatile("cp.async.bulk.tensor.2d.shared::cluster.global.mbarrier::complete_tx::bytes.multicast::cluster [%0], [%1, {%3, %4}], [%2], %5;"
               ::"r"(dst), "l"(m), "r"(bar), "r"(c0), "r"(c1), "h"((uint16_t)3) : "memory");
}
__device__ __forceinline__ void tma3d_mc(uint32_t dst, const CUtensorMap* m, int c0, int c1, int c2, uint32_t bar) {
  asm volatile("cp.async.bulk.tensor.3d.shared::cluster.global.mbarrier::complete_tx::bytes.multicast::cluster [%0], [%1, {%3, %4, %5}], [%2], %6;"
               ::"r"(dst), "l"(m), "r"(bar), "r"(c0), "r"(c1), "r"(c2), "h"((uint16_t)3) : "memory");
}
__device__ __forceinline__ void bulk_g2s(uint32_t dst, const void* src, uint32_t bytes, uint32_t bar) {
  asm volatile("cp.async.bulk.shared::cluster.global.mbarrier::complete_tx::bytes [%0], [%1], %2, [%3];"
               ::"r"(dst), "l"(src), "r"(bytes), "r"(bar) : "memory");
}
__device__ __forceinline__ void prefetch_tmap(const CUtensorMap* m) {
  asm volatile("prefetch.tensormap [%0];" ::"l"(m) : "memory");
}
__device__ __forceinline__ void l2_prefetch(const void* p, uint32_t bytes) {
  asm volatile("cp.async.bulk.prefetch.L2.global [%0], %1;" ::"l"(p), "r"(bytes) : "memory");
}
__device__ __forceinline__ void wg_fence() { asm volatile("wgmma.fence.sync.aligned;" ::: "memory"); }
__device__ __forceinline__ void wg_commit() { asm volatile("wgmma.commit_group.sync.aligned;" ::: "memory"); }
template <int N> __device__ __forceinline__ void wg_wait() { asm volatile("wgmma.wait_group.sync.aligned %0;" ::"n"(N) : "memory"); }
template <int N> __device__ __forceinline__ void fence_regs(float (&d)[N]) {
#pragma unroll
  for (int i = 0; i < N; i++) asm volatile("" : "+f"(d[i])::"memory");
}
template <int N> __device__ __forceinline__ void fence_regs(uint32_t (&d)[N]) {
#pragma unroll
  for (int i = 0; i < N; i++) asm volatile("" : "+r"(d[i])::"memory");
}
__device__ __forceinline__ void bar_sync(int id, int n) { asm volatile("bar.sync %0, %1;" ::"r"(id), "r"(n) : "memory"); }
__device__ __forceinline__ void bar_arrive(int id, int n) { asm volatile("bar.arrive %0, %1;" ::"r"(id), "r"(n) : "memory"); }
__device__ __forceinline__ void fence_gpu() { asm volatile("fence.acq_rel.gpu;" ::: "memory"); }
__device__ __forceinline__ void fence_async() { asm volatile("fence.proxy.async;" ::: "memory"); }
__device__ __forceinline__ void fence_async_smem() { asm volatile("fence.proxy.async.shared::cta;" ::: "memory"); }
__device__ __forceinline__ void red_add(uint32_t* p, uint32_t v) {
  asm volatile("red.relaxed.gpu.global.add.u32 [%0], %1;" ::"l"(p), "r"(v) : "memory");
}
__device__ __forceinline__ uint32_t ld_relaxed(const uint32_t* p) {
  uint32_t v;
  asm volatile("ld.relaxed.gpu.global.u32 %0, [%1];" : "=r"(v) : "l"(p) : "memory");
  return v;
}
__device__ __forceinline__ void wait_counter(const uint32_t* p, uint32_t target) {
  uint32_t v, n = 0;
  while (true) {
    asm volatile("ld.acquire.gpu.global.u32 %0, [%1];" : "=r"(v) : "l"(p) : "memory");
    if ((int32_t)(v - target) >= 0 || ++n > SPIN_LIMIT) break;
  }
}
__device__ __forceinline__ uint4 ld_cg(const uint4* p) {
  uint4 v;
  asm volatile("ld.global.cg.v4.u32 {%0, %1, %2, %3}, [%4];" : "=r"(v.x), "=r"(v.y), "=r"(v.z), "=r"(v.w) : "l"(p) : "memory");
  return v;
}
__device__ __forceinline__ uint32_t pack2(float lo, float hi) {
  uint32_t r;
  asm("cvt.rn.bf16x2.f32 %0, %1, %2;" : "=r"(r) : "f"(hi), "f"(lo));
  return r;
}
__device__ __forceinline__ uint32_t mul2(uint32_t a, uint32_t b) {
  uint32_t r;
  asm("mul.rn.bf16x2 %0, %1, %2;" : "=r"(r) : "r"(a), "r"(b));
  return r;
}
__device__ __forceinline__ uint32_t fma2(uint32_t a, uint32_t b, uint32_t c) {
  uint32_t r;
  asm("fma.rn.bf16x2 %0, %1, %2, %3;" : "=r"(r) : "r"(a), "r"(b), "r"(c));
  return r;
}
__device__ __forceinline__ uint32_t add2(uint32_t a, uint32_t b) {
  uint32_t r;
  asm("add.rn.bf16x2 %0, %1, %2;" : "=r"(r) : "r"(a), "r"(b));
  return r;
}
__device__ __forceinline__ uint32_t sub2(uint32_t a, uint32_t b) {
  uint32_t r;
  asm("sub.rn.bf16x2 %0, %1, %2;" : "=r"(r) : "r"(a), "r"(b));
  return r;
}
__device__ __forceinline__ uint32_t fms2(uint32_t a, uint32_t b, uint32_t c) {
  uint32_t r;
  asm("{\n.reg .b32 n;\nneg.bf16x2 n, %3;\nfma.rn.bf16x2 %0, %1, %2, n;\n}" : "=r"(r) : "r"(a), "r"(b), "r"(c));
  return r;
}
__device__ __forceinline__ float bf_lo(uint32_t v) { return __uint_as_float(v << 16); }
__device__ __forceinline__ float bf_hi(uint32_t v) { return __uint_as_float(v & 0xffff0000u); }
__device__ __forceinline__ float bf_round(float v) { return bf_lo(pack2(v, 0.f)); }
__device__ __forceinline__ float tanh_fast(float v) {
  float r;
  asm("tanh.approx.f32 %0, %1;" : "=f"(r) : "f"(v));
  return r;
}
__device__ __forceinline__ uint64_t mk_desc(uint32_t addr, uint32_t lbo, uint32_t sbo, uint32_t mode) {
  return (uint64_t)((addr & 0x3FFFF) >> 4) | ((uint64_t)(lbo >> 4) << 16) | ((uint64_t)(sbo >> 4) << 32) | ((uint64_t)mode << 62);
}
__device__ __forceinline__ void stmatrix_x4(uint32_t addr, uint32_t r0, uint32_t r1, uint32_t r2, uint32_t r3) {
  asm volatile("stmatrix.sync.aligned.m8n8.x4.shared.b16 [%0], {%1, %2, %3, %4};" ::"r"(addr), "r"(r0), "r"(r1), "r"(r2), "r"(r3) : "memory");
}

template <int TA, int TB>
__device__ __forceinline__ void wgmma_ss_n256(float (&d)[128], uint64_t da, uint64_t db, int sd) {
  asm volatile("{\n.reg .pred p;\nsetp.ne.b32 p, %130, 0;\n"
      "wgmma.mma_async.sync.aligned.m64n256k16.f32.bf16.bf16 {"
      "%0, %1, %2, %3, %4, %5, %6, %7, %8, %9, %10, %11, %12, %13, %14, %15, %16, %17, %18, %19, %20, %21, %22, %23, "
      "%24, %25, %26, %27, %28, %29, %30, %31, %32, %33, %34, %35, %36, %37, %38, %39, %40, %41, %42, %43, %44, %45, "
      "%46, %47, %48, %49, %50, %51, %52, %53, %54, %55, %56, %57, %58, %59, %60, %61, %62, %63, %64, %65, %66, %67, "
      "%68, %69, %70, %71, %72, %73, %74, %75, %76, %77, %78, %79, %80, %81, %82, %83, %84, %85, %86, %87, %88, %89, "
      "%90, %91, %92, %93, %94, %95, %96, %97, %98, %99, %100, %101, %102, %103, %104, %105, %106, %107, %108, %109, "
      "%110, %111, %112, %113, %114, %115, %116, %117, %118, %119, %120, %121, %122, %123, %124, %125, %126, %127"
      "}, %128, %129, p, 1, 1, %131, %132;\n}\n"
      : "+f"(d[0]), "+f"(d[1]), "+f"(d[2]), "+f"(d[3]), "+f"(d[4]), "+f"(d[5]), "+f"(d[6]), "+f"(d[7]), "+f"(d[8]),
        "+f"(d[9]), "+f"(d[10]), "+f"(d[11]), "+f"(d[12]), "+f"(d[13]), "+f"(d[14]), "+f"(d[15]), "+f"(d[16]),
        "+f"(d[17]), "+f"(d[18]), "+f"(d[19]), "+f"(d[20]), "+f"(d[21]), "+f"(d[22]), "+f"(d[23]), "+f"(d[24]),
        "+f"(d[25]), "+f"(d[26]), "+f"(d[27]), "+f"(d[28]), "+f"(d[29]), "+f"(d[30]), "+f"(d[31]), "+f"(d[32]),
        "+f"(d[33]), "+f"(d[34]), "+f"(d[35]), "+f"(d[36]), "+f"(d[37]), "+f"(d[38]), "+f"(d[39]), "+f"(d[40]),
        "+f"(d[41]), "+f"(d[42]), "+f"(d[43]), "+f"(d[44]), "+f"(d[45]), "+f"(d[46]), "+f"(d[47]), "+f"(d[48]),
        "+f"(d[49]), "+f"(d[50]), "+f"(d[51]), "+f"(d[52]), "+f"(d[53]), "+f"(d[54]), "+f"(d[55]), "+f"(d[56]),
        "+f"(d[57]), "+f"(d[58]), "+f"(d[59]), "+f"(d[60]), "+f"(d[61]), "+f"(d[62]), "+f"(d[63]), "+f"(d[64]),
        "+f"(d[65]), "+f"(d[66]), "+f"(d[67]), "+f"(d[68]), "+f"(d[69]), "+f"(d[70]), "+f"(d[71]), "+f"(d[72]),
        "+f"(d[73]), "+f"(d[74]), "+f"(d[75]), "+f"(d[76]), "+f"(d[77]), "+f"(d[78]), "+f"(d[79]), "+f"(d[80]),
        "+f"(d[81]), "+f"(d[82]), "+f"(d[83]), "+f"(d[84]), "+f"(d[85]), "+f"(d[86]), "+f"(d[87]), "+f"(d[88]),
        "+f"(d[89]), "+f"(d[90]), "+f"(d[91]), "+f"(d[92]), "+f"(d[93]), "+f"(d[94]), "+f"(d[95]), "+f"(d[96]),
        "+f"(d[97]), "+f"(d[98]), "+f"(d[99]), "+f"(d[100]), "+f"(d[101]), "+f"(d[102]), "+f"(d[103]), "+f"(d[104]),
        "+f"(d[105]), "+f"(d[106]), "+f"(d[107]), "+f"(d[108]), "+f"(d[109]), "+f"(d[110]), "+f"(d[111]),
        "+f"(d[112]), "+f"(d[113]), "+f"(d[114]), "+f"(d[115]), "+f"(d[116]), "+f"(d[117]), "+f"(d[118]),
        "+f"(d[119]), "+f"(d[120]), "+f"(d[121]), "+f"(d[122]), "+f"(d[123]), "+f"(d[124]), "+f"(d[125]),
        "+f"(d[126]), "+f"(d[127])
      : "l"(da), "l"(db), "r"(sd), "n"(TA), "n"(TB));
}
template <int TA, int TB>
__device__ __forceinline__ void wgmma_ss_n128(float (&d)[64], uint64_t da, uint64_t db, int sd) {
  asm volatile("{\n.reg .pred p;\nsetp.ne.b32 p, %66, 0;\n"
      "wgmma.mma_async.sync.aligned.m64n128k16.f32.bf16.bf16 {"
      "%0, %1, %2, %3, %4, %5, %6, %7, %8, %9, %10, %11, %12, %13, %14, %15, %16, %17, %18, %19, %20, %21, %22, %23, "
      "%24, %25, %26, %27, %28, %29, %30, %31, %32, %33, %34, %35, %36, %37, %38, %39, %40, %41, %42, %43, %44, %45, "
      "%46, %47, %48, %49, %50, %51, %52, %53, %54, %55, %56, %57, %58, %59, %60, %61, %62, %63"
      "}, %64, %65, p, 1, 1, %67, %68;\n}\n"
      : "+f"(d[0]), "+f"(d[1]), "+f"(d[2]), "+f"(d[3]), "+f"(d[4]), "+f"(d[5]), "+f"(d[6]), "+f"(d[7]), "+f"(d[8]),
        "+f"(d[9]), "+f"(d[10]), "+f"(d[11]), "+f"(d[12]), "+f"(d[13]), "+f"(d[14]), "+f"(d[15]), "+f"(d[16]),
        "+f"(d[17]), "+f"(d[18]), "+f"(d[19]), "+f"(d[20]), "+f"(d[21]), "+f"(d[22]), "+f"(d[23]), "+f"(d[24]),
        "+f"(d[25]), "+f"(d[26]), "+f"(d[27]), "+f"(d[28]), "+f"(d[29]), "+f"(d[30]), "+f"(d[31]), "+f"(d[32]),
        "+f"(d[33]), "+f"(d[34]), "+f"(d[35]), "+f"(d[36]), "+f"(d[37]), "+f"(d[38]), "+f"(d[39]), "+f"(d[40]),
        "+f"(d[41]), "+f"(d[42]), "+f"(d[43]), "+f"(d[44]), "+f"(d[45]), "+f"(d[46]), "+f"(d[47]), "+f"(d[48]),
        "+f"(d[49]), "+f"(d[50]), "+f"(d[51]), "+f"(d[52]), "+f"(d[53]), "+f"(d[54]), "+f"(d[55]), "+f"(d[56]),
        "+f"(d[57]), "+f"(d[58]), "+f"(d[59]), "+f"(d[60]), "+f"(d[61]), "+f"(d[62]), "+f"(d[63])
      : "l"(da), "l"(db), "r"(sd), "n"(TA), "n"(TB));
}
template <int TA, int TB>
__device__ __forceinline__ void wgmma_ss_n64(float (&d)[32], uint64_t da, uint64_t db, int sd) {
  asm volatile("{\n.reg .pred p;\nsetp.ne.b32 p, %34, 0;\n"
      "wgmma.mma_async.sync.aligned.m64n64k16.f32.bf16.bf16 {"
      "%0, %1, %2, %3, %4, %5, %6, %7, %8, %9, %10, %11, %12, %13, %14, %15, %16, %17, %18, %19, %20, %21, %22, %23, "
      "%24, %25, %26, %27, %28, %29, %30, %31"
      "}, %32, %33, p, 1, 1, %35, %36;\n}\n"
      : "+f"(d[0]), "+f"(d[1]), "+f"(d[2]), "+f"(d[3]), "+f"(d[4]), "+f"(d[5]), "+f"(d[6]), "+f"(d[7]), "+f"(d[8]),
        "+f"(d[9]), "+f"(d[10]), "+f"(d[11]), "+f"(d[12]), "+f"(d[13]), "+f"(d[14]), "+f"(d[15]), "+f"(d[16]),
        "+f"(d[17]), "+f"(d[18]), "+f"(d[19]), "+f"(d[20]), "+f"(d[21]), "+f"(d[22]), "+f"(d[23]), "+f"(d[24]),
        "+f"(d[25]), "+f"(d[26]), "+f"(d[27]), "+f"(d[28]), "+f"(d[29]), "+f"(d[30]), "+f"(d[31])
      : "l"(da), "l"(db), "r"(sd), "n"(TA), "n"(TB));
}
template <int SA, int TB>
__device__ __forceinline__ void wgmma_rs_n64(float (&d)[32], uint32_t a0, uint32_t a1, uint32_t a2, uint32_t a3, uint64_t db, int sd) {
  asm volatile("{\n.reg .pred p;\nsetp.ne.b32 p, %37, 0;\n"
      "wgmma.mma_async.sync.aligned.m64n64k16.f32.bf16.bf16 {"
      "%0, %1, %2, %3, %4, %5, %6, %7, %8, %9, %10, %11, %12, %13, %14, %15, %16, %17, %18, %19, %20, %21, %22, %23, "
      "%24, %25, %26, %27, %28, %29, %30, %31"
      "}, {%32, %33, %34, %35}, %36, p, %38, 1, %39;\n}\n"
      : "+f"(d[0]), "+f"(d[1]), "+f"(d[2]), "+f"(d[3]), "+f"(d[4]), "+f"(d[5]), "+f"(d[6]), "+f"(d[7]), "+f"(d[8]),
        "+f"(d[9]), "+f"(d[10]), "+f"(d[11]), "+f"(d[12]), "+f"(d[13]), "+f"(d[14]), "+f"(d[15]), "+f"(d[16]),
        "+f"(d[17]), "+f"(d[18]), "+f"(d[19]), "+f"(d[20]), "+f"(d[21]), "+f"(d[22]), "+f"(d[23]), "+f"(d[24]),
        "+f"(d[25]), "+f"(d[26]), "+f"(d[27]), "+f"(d[28]), "+f"(d[29]), "+f"(d[30]), "+f"(d[31])
      : "r"(a0), "r"(a1), "r"(a2), "r"(a3), "l"(db), "r"(sd), "n"(SA), "n"(TB));
}

__device__ __forceinline__ uint32_t BAR_FULL(uint32_t sb, int i) { return sb + SM_BAR + 8 * i; }
__device__ __forceinline__ uint32_t BAR_EMPTY(uint32_t sb, int i) { return sb + SM_BAR + 64 + 8 * i; }
__device__ __forceinline__ uint32_t BAR_X(uint32_t sb, int i) { return sb + SM_BAR + 128 + 8 * i; }
__device__ __forceinline__ uint32_t BAR_Y(uint32_t sb, int i) { return sb + SM_BAR + 192 + 8 * i; }
__device__ __forceinline__ uint32_t BAR_XFREE(uint32_t sb) { return sb + SM_BAR + 256; }

#define CMASK 0x194u
#define XORDER 0, 1, 11, 2, 3, 12, 13, 4, 5, 14, 6, 15, 16
#define XSPREAD 2
#define PFAT 3
#define SKEW 3
constexpr int Q_G1B = 18, Q_G2 = 32, Q_P3 = 46, Q_END = 50;

struct Ring {
  uint32_t slot, phase;
  __device__ __forceinline__ void next() { if (++slot == NSTAGE) { slot = 0; phase ^= 1; } }
};

__device__ __forceinline__ void release_slot(uint32_t sb, uint32_t slot, int tid, int times) {
  if (tid < 2 * times) mbar_arrive_cluster(BAR_EMPTY(sb, slot), tid & 1);
}

__device__ __forceinline__ void ffn_consumer(uint32_t sb, const uint8_t* smem, const Params& p, int bid, int wg, int tid, int mt, int jj) {
  const int lane = tid & 31, warp = tid >> 5, q = lane & 3, r0 = 16 * warp + (lane >> 2);
  uint32_t* const my_epoch = &p.s->epoch[blockIdx.x * 12 + (threadIdx.x >> 5)];
  const uint32_t epoch = ld_relaxed(my_epoch) + 1;
  Ring rg{0, 0};
  uint32_t u[64];
  float acc[128];
  uint32_t prev = 0, cmask = CMASK;
  int st = 0;
  auto g1_stage = [&](uint32_t slot, int s) {
    const uint64_t da = mk_desc(sb + SM_X + (s >> 1) * 16384 + wg * 8192 + (s & 1) * 64, 16, 1024, 1);
    const uint64_t db = mk_desc(sb + SM_RING + slot * STAGE_BYTES, 4096, 1024, 1);
    wg_fence();
    wgmma_ss_n256<0, 1>(acc, da, db, s != 0);
    wgmma_ss_n256<0, 1>(acc, da + 2, db + 128, 1);
    wg_commit();
  };
  if (wg == 1) {
    float ap[64];
    constexpr int QX = 32 - __builtin_clz(CMASK);
    constexpr int NPRE = QX + XSPREAD;
    uint4* const x1dst = reinterpret_cast<uint4*>(p.s->x1t + (size_t)(64 * jj + r0 + 8) * S_ + 128 * mt + 8 * q);
    const int x1lo = 64 * jj + r0 == 1 ? (D_ - 9) * (S_ / 8) : -S_;
#pragma unroll
    for (int qi = 0; qi < NPRE; qi++) {
      const int slot = qi % NSTAGE, nc = __builtin_popcount(CMASK & ((1u << qi) - 1));
      if (qi == 0) TL(60);
      mbar_wait(BAR_FULL(sb, slot), (qi / NSTAGE) & 1);
      if (qi == 0) TL(61);
      if ((CMASK >> qi) & 1) {
#pragma unroll
        for (int kb = 2 * nc; kb < 2 * nc + 2 && kb < 7; kb++) {
          const uint64_t da = mk_desc(sb + SM_RING + slot * STAGE_BYTES + (kb & 1) * 8192, 8192, 1024, 1);
          const uint64_t db = mk_desc(sb + SM_X + kb * 16384, 16, 1024, 1);
          mbar_wait(BAR_X(sb, kb), 0);
          TL(16 + kb);
          wg_fence();
#pragma unroll
          for (int kk = 0; kk < 4; kk++) wgmma_ss_n128<1, 0>(ap, da + kk * 128, db + kk * 2, (kb | kk) != 0);
          wg_commit();
        }
      } else {
        if (((qi - nc) & 1) == 0 && qi - nc >= 4 * nc) mbar_wait(BAR_X(sb, (qi - nc) >> 1), 0);
        TL(32 + qi - nc);
        g1_stage(slot, qi - nc);
      }
      if (qi > 0) {
        wg_wait<1>();
        release_slot(sb, (qi - 1) % NSTAGE, tid, ((CMASK >> (qi - 1)) & 1) ? 2 : 1);
      }
      if (qi >= QX) {
        if (qi == QX) { fence_regs(ap); TL(2); }
#pragma unroll
        for (int t = (qi - QX) * (4 / XSPREAD); t < (qi - QX + 1) * (4 / XSPREAD); t++)
#pragma unroll
        for (int h = 0; h < 2; h++)
          x1dst[(h ? 0 : x1lo) + 4 * t] = make_uint4(pack2(ap[16 * t + 2 * h], ap[16 * t + 2 * h + 1]), pack2(ap[16 * t + 4 + 2 * h], ap[16 * t + 5 + 2 * h]),
                                             pack2(ap[16 * t + 8 + 2 * h], ap[16 * t + 9 + 2 * h]), pack2(ap[16 * t + 12 + 2 * h], ap[16 * t + 13 + 2 * h]));
      }
    }
    bar_arrive(7, 160);
    st = NPRE - 4; cmask = 0; prev = (NPRE - 1) % NSTAGE;
    rg.slot = NPRE % NSTAGE; rg.phase = (NPRE / NSTAGE) & 1;
  }
#pragma unroll 1
  for (int pass = 0; pass < 2; pass++) {
#pragma unroll 1
    for (; st < 14; st++) {
      while (cmask & 1) { cmask >>= 1; rg.next(); }
      cmask >>= 1;
      if (pass == 0 && (st & 1) == 0) mbar_wait(BAR_X(sb, st >> 1), 0);
      if (st == 14 - SKEW && wg == 1) bar_sync(9 + pass, 256);
      mbar_wait(BAR_FULL(sb, rg.slot), rg.phase);
      TL(32 + 14 * pass + st);
      g1_stage(rg.slot, st);
      wg_wait<1>();
      if (st > 0) release_slot(sb, prev, tid, 1);
      prev = rg.slot;
      rg.next();
    }
    st = 0;
    if (wg == 0) bar_arrive(9 + pass, 256);
    wg_wait<0>();
    fence_regs(acc);
    release_slot(sb, prev, tid, 1);
    if (pass == 1 && tid == 0) mbar_arrive(BAR_XFREE(sb));
    TL(3 + 2 * pass);
#pragma unroll
    for (int i = 0; i < 32; i++) {
      const float g0 = 0.5f * acc[2 * i], g1 = 0.5f * acc[2 * i + 1];
      const float s0 = fmaf(g0, tanh_fast(g0), g0), s1 = fmaf(g1, tanh_fast(g1), g1);
      u[32 + i] = pack2(s0 * acc[64 + 2 * i], s1 * acc[64 + 2 * i + 1]);
    }
    if (pass == 0) {
#pragma unroll
      for (int i = 0; i < 32; i++) u[i] = u[32 + i];
    }
    TL(4 + 2 * pass);
  }
  fence_regs(u);
  float accA[32], accB[32];
  rg.slot = Q_G2 % NSTAGE; rg.phase = (Q_G2 / NSTAGE) & 1;
  auto stage = [&](float (&acc)[32], int st) {
    mbar_wait(BAR_FULL(sb, rg.slot), rg.phase);
    const uint64_t db = mk_desc(sb + SM_RING + rg.slot * STAGE_BYTES, 8192, 1024, 1);
    wg_fence();
#pragma unroll
    for (int kk = 0; kk < 8; kk++) {
      const uint32_t* a = u + 32 * st + 4 * kk;
      wgmma_rs_n64<1, 1>(acc, a[0], a[1], a[2], a[3], db + kk * 128, (st | kk) != 0);
    }
    wg_commit();
  };
  auto retire = [&](bool rel) {
    wg_wait<1>();
    if (rel) release_slot(sb, prev, tid, 1);
    prev = rg.slot;
    rg.next();
  };
  auto put = [&](float (&acc)[32], int c) {
    fence_regs(acc);
    int o = jj + 1 + c;
    if (o >= 7) o -= 7;
    uint4* dst = p.s->part + ((((mt * 7 + o) * 6 + c) * 2 + wg) * 4) * 128 + tid;
#pragma unroll
    for (int v = 0; v < 4; v++) {
      const float* a = acc + 8 * v;
      dst[v * 128] = make_uint4(pack2(a[0], a[1]), pack2(a[2], a[3]), pack2(a[4], a[5]), pack2(a[6], a[7]));
    }
  };
  float sum[32];
  uint4 pv[8];
  auto gload = [&](int c) {
    if (lane == 0) wait_counter(&p.s->cnt_p[((mt * 7 + jj) * 2 + wg) * 8 + c], epoch * 2);
    __syncwarp();
    TL(24 + c);
    const uint4* src = p.s->part + (((mt * 7 + jj) * 6 * 2 + wg) * 4) * 128 + tid;
#pragma unroll
    for (int i = 0; i < 8; i++) pv[i] = ld_cg(src + ((2 * c + (i >> 2)) * 8 + (i & 3)) * 128);
  };
  auto gsum = [&](bool first) {
#pragma unroll
    for (int i = 0; i < 8; i++) {
      const float t[8] = {bf_lo(pv[i].x), bf_hi(pv[i].x), bf_lo(pv[i].y), bf_hi(pv[i].y), bf_lo(pv[i].z), bf_hi(pv[i].z), bf_lo(pv[i].w), bf_hi(pv[i].w)};
#pragma unroll
      for (int k = 0; k < 8; k++) sum[8 * (i & 3) + k] = (first && i < 4) ? t[k] : sum[8 * (i & 3) + k] + t[k];
    }
  };
#pragma unroll
  for (int c2 = 0; c2 < 4; c2++) {
    stage(accA, 0);
    retire(c2 == 1 || c2 == 2);
    stage(accA, 1);
    if (c2 > 0) { put(accB, 2 * c2 - 1); bar_arrive(3 * wg + c2, 160); }
    TL(7 + c2);
    if (c2 == 3) { gsum(true); gload(1); break; }
    retire(true);
    stage(accB, 0);
    retire(true);
    stage(accB, 1);
    put(accA, 2 * c2);
    if (c2 == 2) gload(0);
    retire(true);
  }
  rg.next();
#pragma unroll 1
  for (int kb = 0; kb < 7; kb++) {
    if ((kb & 1) == 0) mbar_wait(BAR_FULL(sb, rg.slot), rg.phase);
    mbar_wait(BAR_Y(sb, kb), 0);
    const uint64_t da = mk_desc(sb + SM_X + kb * 16384 + wg * 8192, 8192, 1024, 1);
    const uint64_t db = mk_desc(sb + SM_RING + rg.slot * STAGE_BYTES + (kb & 1) * 8192, 16, 1024, 1);
    wg_fence();
#pragma unroll
    for (int kk = 0; kk < 4; kk++) wgmma_ss_n64<1, 0>(accB, da + kk * 128, db + kk * 2, (kb | kk) != 0);
    wg_commit();
    if (kb & 1) rg.next();
  }
  TL(11);
  const int row = 128 * mt + 64 * wg + r0;
  gsum(false);
  gload(2);
  const float ga0 = __ldcg(&p.s->gate[row]), ga1 = __ldcg(&p.s->gate[row + 8]);
  gsum(false);
  TL(12);
  wg_wait<0>();
  fence_regs(accA);
  fence_regs(accB);
  TL(13);
  const float gb0 = bf_round(1.f - ga0), gb1 = bf_round(1.f - ga1);
  const float gs0 = ga0 * (2.f / (float)(S_ * D_)), gs1 = ga1 * (2.f / (float)(S_ * D_));
  uint4* const o = reinterpret_cast<uint4*>(p.out + (size_t)row * D_ + 64 * jj + 8 * q);
#pragma unroll
  for (int h = 0; h < 2; h++) {
    const float gs = h ? gs1 : gs0, gb = h ? gb1 : gb0;
#pragma unroll
    for (int k = 0; k < 2; k++) {
      uint32_t w[4];
#pragma unroll
      for (int j = 0; j < 4; j++) {
        const int i = 16 * k + 4 * j + 2 * h;
        w[j] = pack2(fmaf(gs, accB[i], gb * (accA[i] + sum[i])), fmaf(gs, accB[i + 1], gb * (accA[i + 1] + sum[i + 1])));
      }
      const bool o1 = q & 1, o2 = q & 2;
      uint32_t a = __shfl_xor_sync(0xffffffffu, o1 ? w[0] : w[1], 1), b = __shfl_xor_sync(0xffffffffu, o1 ? w[2] : w[3], 1);
      if (o1) { w[0] = a; w[2] = b; } else { w[1] = a; w[3] = b; }
      a = __shfl_xor_sync(0xffffffffu, o2 ? w[0] : w[2], 2); b = __shfl_xor_sync(0xffffffffu, o2 ? w[1] : w[3], 2);
      if (o2) { w[0] = a; w[1] = b; } else { w[2] = a; w[3] = b; }
      o[h * D_ + 4 * k] = make_uint4(w[0], w[1], w[2], w[3]);
    }
  }
  if (lane == 0) *my_epoch = epoch;
  TL(14);
}

__device__ __forceinline__ void ring_issue(uint32_t sb, const Params& p, int qi, uint32_t slot, bool wait, uint32_t phase, int jj, uint32_t rank) {
  const CUtensorMap* m;
  int c0, c1, c2 = 0;
  bool half = false, is3d = false;
  if (qi < Q_G2) {
    const int nc = __popc(CMASK & ((1u << qi) - 1));
    if ((CMASK >> qi) & 1) {
      m = &p.ct; c0 = 64 * jj; c1 = 128 * nc + 64 * rank; half = nc == 3;
    } else {
      const int pass = qi >= Q_G1B;
      m = rank ? &p.wu : &p.wg; c0 = 0; c1 = 32 * (qi - nc - 14 * pass); c2 = 4 * jj + 2 * pass; is3d = true;
    }
  } else if (qi < Q_P3) {
    int o = jj + 1 + ((qi - Q_G2) >> 1);
    if (o >= 7) o -= 7;
    m = &p.wd; c0 = 64 * o; c1 = 256 * jj + 128 * (qi & 1) + 64 * rank;
  } else {
    m = &p.ct; c0 = 128 * (qi - Q_P3) + 64 * rank; c1 = 64 * jj; half = qi == Q_END - 1;
  }
  const uint32_t bar = BAR_FULL(sb, slot);
  const uint32_t dst = sb + SM_RING + slot * STAGE_BYTES + rank * 8192;
  if (wait) mbar_wait_cluster(BAR_EMPTY(sb, slot), phase);
  mbar_expect_tx(bar, half ? 8192 : 16384);
  if (is3d) tma3d_mc(dst, m, c0, c1, c2, bar);
  else if (!(half && rank)) tma2d_mc(dst, m, c0, c1, bar);
}

__device__ __forceinline__ void ffn_producer(uint32_t sb, const uint8_t* smem, int bid, const Params& p, int warp, int lane, int mt, int jj, uint32_t rank) {
  if (warp < 2) {
    if (lane == 0) {
      uint32_t slot = warp, phase = 0;
#pragma unroll 1
      for (int qi = NSTAGE + warp; qi < Q_END; qi += 2) {
        ring_issue(sb, p, qi, slot, true, phase, jj, rank);
        TL(10 + qi);
        slot += 2;
        if (slot >= NSTAGE) { slot -= NSTAGE; phase ^= 1; }
      }
    }
  } else {
    const int wg = warp - 2;
    if (wg == 0) {
      if (lane == 0) { prefetch_tmap(&p.wd); prefetch_tmap(&p.yt); }
      uint32_t* const my_epoch = &p.s->epoch[blockIdx.x * 12 + 10];
      const uint32_t epoch = ld_relaxed(my_epoch) + 1;
      {
        const uint4* gw4 = reinterpret_cast<const uint4*>(p.gate_w);
        const uint4 ga = __ldg(gw4 + lane), gb = lane < 24 ? __ldg(gw4 + 32 + lane) : make_uint4(0, 0, 0, 0);
        if (lane < 7) mbar_wait(BAR_X(sb, lane), 0);
        __syncwarp();
        float mine = 0.f;
#pragma unroll 1
        for (int u = 0; u < 19; u++) {
          const int r = min(19 * jj + u, 127);
          const uint8_t* xr = smem + SM_X + (lane >> 3) * 16384 + r * 128 + (((lane ^ r) & 7) << 4);
          const uint4 xa = *reinterpret_cast<const uint4*>(xr);
          const uint4 xb = lane < 24 ? *reinterpret_cast<const uint4*>(xr + 65536) : make_uint4(0, 0, 0, 0);
          float s = 0.f;
          auto dot2 = [&](uint32_t a, uint32_t b) {
            const uint32_t pr = mul2(a, b);
            s += bf_lo(pr) + bf_hi(pr);
          };
          dot2(xa.x, ga.x); dot2(xa.y, ga.y); dot2(xa.z, ga.z); dot2(xa.w, ga.w);
          dot2(xb.x, gb.x); dot2(xb.y, gb.y); dot2(xb.z, gb.z); dot2(xb.w, gb.w);
#pragma unroll
          for (int o = 16; o > 0; o >>= 1) s += __shfl_xor_sync(0xffffffffu, s, o);
          if (lane == u) mine = s;
        }
        if (lane < 19 && 19 * jj + lane < 128) p.s->gate[128 * mt + 19 * jj + lane] = bf_round(1.f / (1.f + __expf(-bf_round(mine))));
        bar_arrive(8, 64);
      }
      TL(9);
      mbar_wait(BAR_XFREE(sb), 0);
      TL(3);
      bool todo = lane < 7;
      uint32_t n = 0;
      while (__any_sync(0xffffffffu, todo)) {
        if (todo) {
          uint32_t v;
          asm volatile("ld.acquire.gpu.global.u32 %0, [%1];" : "=r"(v) : "l"(&p.s->cnt_y[lane * 32]) : "memory");
          if ((int32_t)(v - epoch * (lane ? 16 : 17)) >= 0 || ++n > SPIN_LIMIT) {
            fence_async();
            mbar_expect_tx(BAR_Y(sb, lane), 16384);
            tma3d(sb + SM_X + lane * 16384, &p.yt, 0, 64 * lane, 2 * mt, BAR_Y(sb, lane));
            todo = false;
          }
        }
      }
      TL(4);
      if (lane == 0) *my_epoch = epoch;
    } else {
      mbar_wait(BAR_X(sb, PFAT), 0);
      if (lane < 6) {
        int row = 176 + 3 * bid + (lane >> 1);
        if (row >= D_) row -= D_;
        l2_prefetch(((lane & 1) ? p.pwu : p.pwg) + row * F_, F_ * 2);
      }
      TL(2);
      bar_sync(7, 160);
      if (lane == 0) { fence_gpu(); red_add(&p.s->cnt_x1[jj * 32], 1); l2_prefetch(p.pwd + bid * 16 * D_, 32 * D_); }
      TL(3);
      bar_sync(8, 64);
    }
#pragma unroll 1
    for (int c = 0; c < 3; c++) {
      bar_sync(1 + 3 * wg + c, 160);
      if (lane < 2) {
        int o = jj + 1 + 2 * c + lane;
        if (o >= 7) o -= 7;
        fence_gpu();
        red_add(&p.s->cnt_p[((mt * 7 + o) * 2 + wg) * 8 + c], 1);
      }
      TL(5 + c);
    }
  }
}

__device__ __forceinline__ void spectral_cta(uint32_t sb, uint8_t* smem, const Params& p, int sc, int wg) {
  const int t384 = threadIdx.x, lane = t384 & 31, warp12 = t384 >> 5, tid = t384 & 127;
  const int warp = tid >> 5, q = lane & 3;
  const int sl0 = 6 * sc + min(sc, 8), nsl = sc < 8 ? 7 : 6;
  if (t384 == 320) {
#pragma unroll 1
    for (int i = 0; i < nsl; i++) {
      mbar_expect_tx(BAR_X(sb, i), 2 * SLAB_BYTES);
      const int row = 128 * ((sl0 + i) >> 3) + 8 * ((sl0 + i) & 7);
      const uint32_t dst = sb + SP_Z + 2 * i * SLAB_BYTES;
      bulk_g2s(dst, p.w_r + row * DF_, SLAB_BYTES / 2, BAR_X(sb, i));
      bulk_g2s(dst + SLAB_BYTES / 2, p.w_r + (row + 64) * DF_, SLAB_BYTES / 2, BAR_X(sb, i));
      bulk_g2s(dst + SLAB_BYTES, p.w_i + row * DF_, SLAB_BYTES / 2, BAR_X(sb, i));
      bulk_g2s(dst + 3 * SLAB_BYTES / 2, p.w_i + (row + 64) * DF_, SLAB_BYTES / 2, BAR_X(sb, i));
    }
    if (sc < 19) {
      mbar_expect_tx(BAR_Y(sb, 6), 24576);
      bulk_g2s(sb + SP_TW, p.spec, 24576, BAR_Y(sb, 6));
      prefetch_tmap(&p.x1);
    }
  }
  uint32_t* const my_epoch = &p.s->epoch[blockIdx.x * 12 + warp12];
  const uint32_t epoch = ld_relaxed(my_epoch) + 1;
  uint32_t fe[16], tw[16];
#pragma unroll
  for (int i = 0; i < 4; i++) {
    const uint4 a = __ldg(reinterpret_cast<const uint4*>(p.spec->fe) + i * 128 + tid);
    const uint4 b = __ldg(reinterpret_cast<const uint4*>(p.spec->tw) + i * 128 + tid);
    fe[4 * i] = a.x; fe[4 * i + 1] = a.y; fe[4 * i + 2] = a.z; fe[4 * i + 3] = a.w;
    tw[4 * i] = b.x; tw[4 * i + 1] = b.y; tw[4 * i + 2] = b.z; tw[4 * i + 3] = b.w;
  }
  __syncwarp();
  asm volatile("barrier.cluster.wait.acquire.aligned;" ::: "memory");
#pragma unroll 2
  for (int un = wg; un < 8 * nsl; un += 3) {
    const int i = un >> 3, sl = sl0 + i, pr = 16 * (un & 7) + 4 * (lane >> 3) + warp, r = lane & 7;
    mbar_wait(BAR_X(sb, i), 0);
    if (pr < 113) {
      const uint16_t* w = reinterpret_cast<const uint16_t*>(smem + SP_Z + 2 * i * SLAB_BYTES) + r * DF_ + 2 * pr;
      const uint32_t m = pr < 112 ? 0xffffffffu : 0u;
      p.s->wt[pr * 1024 + sl * 8 + (r ^ ((sl >> 2) & 6))] =
          make_uint4(w[0] | ((uint32_t)w[8 * DF_] << 16), w[16 * DF_] | ((uint32_t)w[24 * DF_] << 16),
                     (w[1] | ((uint32_t)w[8 * DF_ + 1] << 16)) & m, (w[16 * DF_ + 1] | ((uint32_t)w[24 * DF_ + 1] << 16)) & m);
    }
  }
  __syncthreads();
  if (t384 == 352) { fence_gpu(); red_add(&p.s->cnt_w[0], 1); }
  TL(1);
  if (sc == 19) return;
  const int nrnd = (sc == 18 && wg == 2) ? 1 : 2;
  if (tid == 32) {
    wait_counter(&p.s->cnt_w[0], epoch * NSPEC);
    fence_async();
    for (int rnd = 0; rnd < nrnd; rnd++) {
      const int item = wg + 3 * rnd;
      mbar_expect_tx(BAR_Y(sb, item), 16384);
      bulk_g2s(sb + SP_W + item * 16384, p.s->wt + (6 * sc + item) * 1024, 16384, BAR_Y(sb, item));
    }
  } else if (tid == 0) {
#pragma unroll 1
    for (int rnd = 0; rnd < nrnd; rnd++) {
      const int item = wg + 3 * rnd, pr = 6 * sc + item;
      wait_counter(&p.s->cnt_x1[(pr < 112 ? pr >> 4 : 0) * 32], epoch * 16);
      fence_async();
      const uint32_t bar = BAR_FULL(sb, item), z = sb + SP_Z + item * 16384;
      mbar_expect_tx(bar, 16384);
      tma4d(z, &p.x1, 4 * pr, bar);
    }
  }
  __syncwarp();
  fence_regs(fe); fence_regs(tw);
  mbar_wait(BAR_Y(sb, 6), 0);
  TL(3);
  const uint64_t dT_n = mk_desc(sb + SP_T, 8192, 1024, 1);
#pragma unroll 1
  for (int rnd = 0; rnd < nrnd; rnd++) {
    const int item = wg + 3 * rnd, pr = 6 * sc + item;
    const uint32_t z = sb + SP_Z + item * 16384;
    uint32_t fa[16], fb[16];
    auto load_frag = [&](int off) {
#pragma unroll
      for (int i = 0; i < 4; i++) {
        const uint4 a = *reinterpret_cast<const uint4*>(smem + SP_TW + off + i * 2048 + tid * 16);
        fa[4 * i] = a.x; fa[4 * i + 1] = a.y; fa[4 * i + 2] = a.z; fa[4 * i + 3] = a.w;
      }
      fence_regs(fa);
    };
    load_frag(0);
    mbar_wait(BAR_FULL(sb, item), 0);
    TL(4 + 8 * rnd);
    if (rnd == 0 && wg > 0) bar_sync(3 + wg, 256);
    float aR[32], aI[32];
    {
      const uint64_t de = mk_desc(z, 4096, 512, 2);
      wg_fence();
#pragma unroll
      for (int kk = 0; kk < 4; kk++) {
        wgmma_rs_n64<1, 1>(aR, fe[4 * kk], fe[4 * kk + 1], fe[4 * kk + 2], fe[4 * kk + 3], de + kk * 64, kk != 0);
        wgmma_rs_n64<1, 1>(aI, fa[4 * kk], fa[4 * kk + 1], fa[4 * kk + 2], fa[4 * kk + 3], de + 512 + kk * 64, kk != 0);
      }
      wg_commit();
      if (rnd == 0 && wg < 2) bar_arrive(4 + wg, 256);
      if (rnd == 1 && tid == 0) { fence_gpu(); red_add(&p.s->cnt_y[((pr - 3) >> 4) * 32], 1); }
      wg_wait<0>();
      fence_regs(aR); fence_regs(aI);
    }
    TL(5 + 8 * rnd);
#pragma unroll
    for (int v = 0; v < 8; v++) {
      uint32_t* f = (v < 4 ? fa : fb) + 2 * (v & 3);
      const uint32_t* t = tw + 2 * (v & 3);
      const float *e = aR + 4 * v, *o = aI + 4 * v;
      const uint32_t er = pack2(e[0], e[1]), ei = pack2(e[2], e[3]), qr = pack2(o[0], o[1]), qi = pack2(o[2], o[3]);
      const uint32_t u0r = add2(er, qr), u0i = add2(ei, qi), u1r = sub2(er, qr), u1i = sub2(ei, qi);
      f[0] = fma2(u0r, t[0], mul2(u0i, t[8]));
      f[8] = fms2(u0i, t[0], mul2(u0r, t[8]));
      f[1] = fma2(u1r, t[1], mul2(u1i, t[9]));
      f[9] = fms2(u1i, t[1], mul2(u1r, t[9]));
    }
    fence_regs(fa); fence_regs(fb);
    wg_fence();
#pragma unroll
    for (int kk = 0; kk < 4; kk++) {
      wgmma_rs_n64<1, 1>(aR, fa[4 * kk], fa[4 * kk + 1], fa[4 * kk + 2], fa[4 * kk + 3], dT_n + kk * 128, kk != 0);
      wgmma_rs_n64<1, 1>(aI, fb[4 * kk], fb[4 * kk + 1], fb[4 * kk + 2], fb[4 * kk + 3], dT_n + kk * 128, kk != 0);
    }
    wg_commit();
    mbar_wait(BAR_Y(sb, item), 0);
    wg_wait<0>();
    fence_regs(aR); fence_regs(aI);
    TL(6 + 8 * rnd);
    {
      const uint8_t* wp = smem + SP_W + item * 16384 + q * 1024 + warp * 128 + (((lane >> 2) ^ (2 * q)) << 4);
#pragma unroll
      for (int jb = 0; jb < 4; jb++) {
#pragma unroll
        for (int h = 0; h < 2; h++) {
          const uint4 w = *reinterpret_cast<const uint4*>(wp + jb * 4096 + h * 512);
          const int i = 4 * jb + 2 * h;
          const uint32_t ar = pack2(aR[i], aR[i + 1]), ai = pack2(aR[16 + i], aR[17 + i]);
          const uint32_t br = pack2(aI[i], aI[i + 1]), bi = pack2(aI[16 + i], aI[17 + i]);
          fa[2 * jb + h] = fms2(ar, w.x, mul2(ai, w.y));
          fa[8 + 2 * jb + h] = fma2(ar, w.y, mul2(ai, w.x));
          fb[2 * jb + h] = fms2(br, w.z, mul2(bi, w.w));
          fb[8 + 2 * jb + h] = fma2(br, w.w, mul2(bi, w.z));
        }
      }
    }
    fence_regs(fa); fence_regs(fb);
    wg_fence();
#pragma unroll
    for (int kk = 0; kk < 4; kk++) {
      wgmma_rs_n64<1, 0>(aR, fa[4 * kk], fa[4 * kk + 1], fa[4 * kk + 2], fa[4 * kk + 3], dT_n + kk * 2, kk != 0);
      wgmma_rs_n64<1, 0>(aI, fb[4 * kk], fb[4 * kk + 1], fb[4 * kk + 2], fb[4 * kk + 3], dT_n + kk * 2, kk != 0);
    }
    wg_commit();
    wg_wait<0>();
    fence_regs(aR); fence_regs(aI);
    TL(7 + 8 * rnd);
#pragma unroll
    for (int v = 0; v < 8; v++) {
      const float* a = (v < 4 ? aR : aI) + 4 * (v & 3);
      const uint32_t* t = tw + 2 * (v & 3);
      const uint32_t u0r = pack2(a[0], a[1]), u1r = pack2(a[2], a[3]), u0i = pack2(a[16], a[17]), u1i = pack2(a[18], a[19]);
      const uint32_t t0r = fms2(u0r, t[0], mul2(u0i, t[8])), t0i = fma2(u0i, t[0], mul2(u0r, t[8]));
      const uint32_t t1r = fms2(u1r, t[1], mul2(u1i, t[9])), t1i = fma2(u1i, t[1], mul2(u1r, t[9]));
      fa[v] = add2(t0i, t1i); fa[8 + v] = add2(t0r, t1r);
      fb[v] = sub2(t0i, t1i); fb[8 + v] = sub2(t0r, t1r);
    }
    bar_sync(1 + wg, 128);
#pragma unroll
    for (int u = 0; u < 4; u++) {
      const uint32_t a = z + (32 * (u >> 1) + 8 * warp + (lane & 7)) * 128 + (((4 * (u & 1) + (lane >> 3)) ^ (lane & 7)) << 4);
      stmatrix_x4(a, fa[4 * u], fa[4 * u + 1], fa[4 * u + 2], fa[4 * u + 3]);
      stmatrix_x4(a + 8192, fb[4 * u], fb[4 * u + 1], fb[4 * u + 2], fb[4 * u + 3]);
    }
    load_frag(8192);
    fence_async_smem();
    bar_sync(1 + wg, 128);
    TL(8 + 8 * rnd);
    {
      const uint64_t de = mk_desc(z, 8192, 1024, 1);
      wg_fence();
#pragma unroll
      for (int kk = 0; kk < 4; kk++) {
        wgmma_rs_n64<1, 1>(aR, fe[4 * kk], fe[4 * kk + 1], fe[4 * kk + 2], fe[4 * kk + 3], de + kk * 128, kk != 0);
        wgmma_rs_n64<1, 1>(aI, fa[4 * kk], fa[4 * kk + 1], fa[4 * kk + 2], fa[4 * kk + 3], de + 512 + kk * 128, kk != 0);
      }
      wg_commit();
      wg_wait<0>();
      fence_regs(aR); fence_regs(aI);
    }
    TL(9 + 8 * rnd);
    const bool edge = pr == 0 || pr == 112;
    if (edge) {
#pragma unroll
      for (int i = 0; i < 16; i++) { aR[i] *= 0.5f; aI[i] *= 0.5f; }
    }
#pragma unroll
    for (int h = 0; h < 2; h++) {
      __nv_bfloat16* dst = p.s->yt + (size_t)(4 * pr) * S_ + 64 * (8 * warp + (lane >> 2)) + 32 * h + 8 * q;
      auto st = [&](bool ok, int jrow, const float* a) {
        if (ok)
          *reinterpret_cast<uint4*>(dst + jrow * S_) = make_uint4(pack2(a[0], a[1]), pack2(a[4], a[5]), pack2(a[8], a[9]), pack2(a[12], a[13]));
      };
      const float* a = h ? aI : aR;
      st(true, pr < 112 ? 0 : 1 - D_, a + 2); st(!edge, 1, a); st(pr < 112, 2, a + 18); st(pr < 112, 3, a + 16);
    }
    bar_sync(1 + wg, 128);
    if (rnd == nrnd - 1 && tid == 0) { fence_gpu(); red_add(&p.s->cnt_y[(pr < 112 ? pr >> 4 : 0) * 32], 1); }
    TL(10 + 8 * rnd);
  }
  if (lane == 0) *my_epoch = epoch;
}

__global__ void __cluster_dims__(2, 1, 1) __launch_bounds__(384, 1)
fused_kernel(const __grid_constant__ Params p) {
  extern __shared__ __align__(1024) uint8_t smem[];
  const uint32_t sb = smem_u32(smem);
  TL(0);
  const uint32_t rank = blockIdx.x & 1;
  const int hc = blockIdx.x >> 1;
  int grp, jj;
  if (hc < 4) { grp = 8; jj = hc; }
  else if (hc < 36) { grp = (hc - 4) & 7; jj = (hc - 4) >> 3; }
  else if (hc < 57) { jj = (hc - 36) / 7; grp = 1 + (hc - 36) - 7 * jj; jj += 4; }
  else if (hc < 60) { grp = 0; jj = hc - 53; }
  else { grp = 8; jj = hc - 56; }
  const int mt = 2 * grp + rank, bid = 2 * (7 * grp + jj) + rank;
  if (threadIdx.x == 256) {
#pragma unroll
    for (int i = 0; i < NSTAGE; i++) { mbar_init(BAR_FULL(sb, i), 1); mbar_init(BAR_EMPTY(sb, i), 4); }
    asm volatile("fence.mbarrier_init.release.cluster;" ::: "memory");
  } else if (threadIdx.x == 320) {
#pragma unroll
    for (int i = 0; i < NSTAGE; i++) { mbar_init(BAR_X(sb, i), 1); mbar_init(BAR_Y(sb, i), 1); }
    mbar_init(BAR_XFREE(sb), 2);
    asm volatile("fence.mbarrier_init.release.cluster;" ::: "memory");
  } else if (threadIdx.x == 288) {
    prefetch_tmap(rank ? &p.wu : &p.wg); prefetch_tmap(&p.ct);
  }
  __syncwarp();
  asm volatile("barrier.cluster.arrive.relaxed.aligned;" ::: "memory");
  const int wg = __shfl_sync(0xffffffffu, threadIdx.x >> 7, 0);
  if (bid >= NFFN) {
    spectral_cta(sb, smem, p, bid - NFFN, wg);
  } else if (wg < 2) {
    asm volatile("setmaxnreg.inc.sync.aligned.u32 232;");
    asm volatile("barrier.cluster.wait.acquire.aligned;" ::: "memory");
    TL(1);
    ffn_consumer(sb, smem, p, bid, wg, threadIdx.x & 127, mt, jj);
  } else {
    asm volatile("setmaxnreg.dec.sync.aligned.u32 40;");
    if (threadIdx.x == 320) {
      mbar_expect_tx(BAR_X(sb, 0), 16384);
      tma2d(sb + SM_X, &p.x, 0, 128 * mt, BAR_X(sb, 0));
    }
    __syncwarp();
    asm volatile("barrier.cluster.wait.acquire.aligned;" ::: "memory");
    TL(1);
    if (threadIdx.x == 320) {
      constexpr int order[13] = {XORDER};
#pragma unroll
      for (int i = 0; i < 13; i++) {
        if (order[i] < 8) {
          ring_issue(sb, p, order[i], order[i], false, 0, jj, rank);
        } else {
          const int kb = order[i] - 10;
          mbar_expect_tx(BAR_X(sb, kb), 16384);
          tma2d(sb + SM_X + kb * 16384, &p.x, 64 * kb, 128 * mt, BAR_X(sb, kb));
        }
      }
      TL(2);
    } else if (threadIdx.x == 352) {
    }
    __syncwarp();
    ffn_producer(sb, smem, bid, p, (threadIdx.x >> 5) & 3, threadIdx.x & 31, mt, jj, rank);
  }
}

typedef CUresult (*EncodeFn)(CUtensorMap*, CUtensorMapDataType, cuuint32_t, void*, const cuuint64_t*, const cuuint64_t*,
                             const cuuint32_t*, const cuuint32_t*, CUtensorMapInterleave, CUtensorMapSwizzle,
                             CUtensorMapL2promotion, CUtensorMapFloatOOBfill);

void make_map(EncodeFn fn, CUtensorMap* m, const void* base, int rank, const cuuint64_t* dims, const cuuint64_t* strides,
              const cuuint32_t* box, CUtensorMapSwizzle sw) {
  const cuuint32_t es[4] = {1, 1, 1, 1};
  fn(m, CU_TENSOR_MAP_DATA_TYPE_BFLOAT16, rank, const_cast<void*>(base), dims, strides, box, es,
     CU_TENSOR_MAP_INTERLEAVE_NONE, sw, CU_TENSOR_MAP_L2_PROMOTION_L2_256B, CU_TENSOR_MAP_FLOAT_OOB_FILL_NONE);
}

}

extern "C" void kernel_launch(void* const* d_in, const int* in_sizes, int n_in, void* d_out, int out_size) {
  const __nv_bfloat16* x = (const __nv_bfloat16*)d_in[0];
  const __nv_bfloat16* w_r = (const __nv_bfloat16*)d_in[1];
  const __nv_bfloat16* w_i = (const __nv_bfloat16*)d_in[2];
  const __nv_bfloat16* wg = (const __nv_bfloat16*)d_in[4];
  const __nv_bfloat16* wu = (const __nv_bfloat16*)d_in[5];
  const __nv_bfloat16* wd = (const __nv_bfloat16*)d_in[6];
  const __nv_bfloat16* gate_w = (const __nv_bfloat16*)d_in[7];

  void* fnp = nullptr;
  cudaDriverEntryPointQueryResult qr;
  cudaGetDriverEntryPoint("cuTensorMapEncodeTiled", &fnp, cudaEnableDefault, &qr);
  EncodeFn fn = (EncodeFn)fnp;
  void *ctab, *spec, *scr;
  cudaGetSymbolAddress(&ctab, g_ctab);
  cudaGetSymbolAddress(&spec, g_spec);
  cudaGetSymbolAddress(&scr, g_scratch);
  const void* x1t = (const char*)scr + offsetof(Scratch, x1t);
  const void* yt = (const char*)scr + offsetof(Scratch, yt);
  Params p;
  p.s = (Scratch*)scr; p.out = (__nv_bfloat16*)d_out;
  p.px = x; p.w_r = w_r; p.w_i = w_i; p.gate_w = gate_w; p.pwg = wg; p.pwu = wu; p.pwd = wd;
  p.ctab = (const tab::Table*)ctab; p.spec = (const tab::Spec*)spec;
  {
    const cuuint64_t d[2] = {D_, S_}, s[1] = {D_ * 2};
    const cuuint32_t b[2] = {64, 128};
    make_map(fn, &p.x, x, 2, d, s, b, CU_TENSOR_MAP_SWIZZLE_128B);
  }
  {
    const cuuint64_t d[3] = {64, D_, F_ / 64}, s[2] = {F_ * 2, 128};
    const cuuint32_t b[3] = {64, 32, 2};
    make_map(fn, &p.wg, wg, 3, d, s, b, CU_TENSOR_MAP_SWIZZLE_128B);
    make_map(fn, &p.wu, wu, 3, d, s, b, CU_TENSOR_MAP_SWIZZLE_128B);
  }
  {
    const cuuint64_t d[2] = {D_, F_}, s[1] = {D_ * 2};
    const cuuint32_t b[2] = {64, 64};
    make_map(fn, &p.wd, wd, 2, d, s, b, CU_TENSOR_MAP_SWIZZLE_128B);
  }
  {
    const cuuint64_t d[2] = {D_, D_}, s[1] = {D_ * 2};
    const cuuint32_t b[2] = {64, 64};
    make_map(fn, &p.ct, ctab, 2, d, s, b, CU_TENSOR_MAP_SWIZZLE_128B);
  }
  {
    const cuuint64_t d[4] = {32, 32, D_ + 1, 2}, s[3] = {128, S_ * 2, 64};
    const cuuint32_t b[4] = {32, 32, 4, 2};
    make_map(fn, &p.x1, x1t, 4, d, s, b, CU_TENSOR_MAP_SWIZZLE_64B);
  }
  {
    const cuuint64_t d[3] = {64, D_, S_ / 64}, s[2] = {S_ * 2, 128};
    const cuuint32_t b[3] = {64, 64, 2};
    make_map(fn, &p.yt, yt, 3, d, s, b, CU_TENSOR_MAP_SWIZZLE_128B);
  }
  cudaFuncSetAttribute(fused_kernel, cudaFuncAttributeMaxDynamicSharedMemorySize, SM_TOTAL);
  fused_kernel<<<NCTA, 384, SM_TOTAL, cudaStreamPerThread>>>(p, x, w_r, w_i, gate_w, wd, (__nv_bfloat16*)d_out);
}
```

```cpp
#include <cuda_runtime.h>
#include <cuda_bf16.h>
#include <cuda.h>
#include <stdint.h>
#include <stddef.h>

namespace {

constexpr int S_ = 2048, D_ = 448, F_ = 1792, DF_ = 225;
constexpr int NFFN = 112, NSPEC = 20, NCTA = NFFN + NSPEC;
constexpr int NSTAGE = 7, STAGE_BYTES = 16384;
constexpr int SM_X = 0, SM_RING = 114688, SM_BAR = 229376, SM_TOTAL = SM_BAR + 512;
constexpr int SP_Z = 0, SP_W = 98304, SP_TW = 198656, SP_T = 215040, SLAB_BYTES = 16 * DF_ * 2;
constexpr uint32_t SPIN_LIMIT = 1u << 20;

namespace tab {
constexpr double PI = 3.14159265358979323846264338327950288;
constexpr double csin(double x) {
  double t = x, s = x;
  for (int i = 1; i < 20; i++) { t = -t * x * x / ((2 * i) * (2 * i + 1)); s += t; }
  return s;
}
constexpr double ccos(double x) {
  double t = 1, s = 1;
  for (int i = 1; i < 20; i++) { t = -t * x * x / ((2 * i - 1) * (2 * i)); s += t; }
  return s;
}
constexpr uint32_t to_bf16(double v) {
  uint32_t sign = v < 0 ? 0x8000u : 0u;
  double a = v < 0 ? -v : v;
  if (a < 1e-12) return 0;
  int e = 0;
  while (a >= 2.0) { a /= 2; e++; }
  while (a < 1.0) { a *= 2; e--; }
  double m = a * 128.0;
  int mi = (int)m;
  double fr = m - mi;
  if (fr > 0.5 || (fr == 0.5 && (mi & 1))) mi++;
  if (mi == 256) { mi = 128; e++; }
  return sign | (uint32_t)((e + 127) << 7) | (uint32_t)(mi - 128);
}
struct Base { uint32_t v[448]; };
constexpr Base make_base() {
  Base b{};
  for (int m = 0; m < 448; m++) {
    int mm = m > 224 ? m - 448 : m;
    double ang = 2 * PI * mm / 448.0;
    b.v[m] = to_bf16(ccos(ang)) | (to_bf16(-csin(ang)) << 16);
  }
  return b;
}
constexpr Base base = make_base();
struct Row { uint32_t v[224]; };
constexpr Row make_row(int d) {
  Row r{};
  r.v[0] = 0x3f80u | ((d & 1) ? 0xbf800000u : 0x3f800000u);
  int m = 0;
  for (int c = 1; c < 224; c++) { m += d; if (m >= 448) m -= 448; r.v[c] = base.v[m]; }
  return r;
}
struct Table { Row r[448]; };
constexpr Table make_table() {
  Table t{};
  for (int d = 0; d < 448; d++) t.r[d] = make_row(d);
  return t;
}
struct Cs { double c[2048], s[2048]; };
constexpr Cs make_cs() {
  Cs t{};
  for (int m = 0; m <= 256; m++) {
    const double a = 2 * PI * m / 2048.0, c = ccos(a), s = csin(a);
    t.c[m] = c; t.s[m] = s;
    t.c[512 - m] = s; t.s[512 - m] = c;
  }
  for (int m = 513; m < 2048; m++) { t.c[m] = -t.s[m - 512]; t.s[m] = t.c[m - 512]; }
  return t;
}
constexpr Cs cs = make_cs();
struct Spec {
  uint32_t fo[2048], fot[2048];
  uint16_t t32[4096];
  uint32_t fe[2048];
  uint32_t tw[2048];
};
constexpr uint32_t blk(int h, int c, int a) { return to_bf16(h == c ? cs.c[a & 2047] : (h ? -cs.s[a & 2047] : cs.s[a & 2047])); }
constexpr Spec make_spec() {
  Spec t{};
  for (int row = 0; row < 64; row++)
    for (int col = 0; col < 64; col++) {
      const int c = row & 31, k2 = col & 31, n2 = 8 * ((c >> 1) & 3) + 2 * (c >> 3) + (c & 1), m = 64 * ((n2 * k2) & 31);
      const double v = (row >> 5) == (col >> 5) ? cs.c[m] : (row < 32 ? -cs.s[m] : cs.s[m]);
      t.t32[row * 64 + (((col >> 3) ^ (row & 7)) << 3) + (col & 7)] = (uint16_t)to_bf16(v);
    }
  for (int th = 0; th < 128; th++)
    for (int i = 0; i < 16; i++) {
      const int r = 8 * (th >> 5) + ((th & 31) >> 2), h = i & 1, c = i >> 3, m = 8 * ((i >> 1) & 3) + 2 * (th & 3);
      const int o = ((i >> 2) * 128 + th) * 4 + (i & 3);
      t.fe[o] = blk(h, c, 64 * m * r) | (blk(h, c, 64 * (m + 1) * r) << 16);
      t.fo[o] = blk(h, c, 32 * (2 * m + 1) * r) | (blk(h, c, 32 * (2 * m + 3) * r) << 16);
      t.fot[o] = blk(h, c, 32 * (2 * r + 1) * m) | (blk(h, c, 32 * (2 * r + 1) * (m + 1)) << 16);
      const int k1 = r + 32 * h, n2 = 8 * (th & 3) + 2 * ((i >> 1) & 3);
      t.tw[o] = blk(0, c, n2 * k1) | (blk(0, c, (n2 + 1) * k1) << 16);
    }
  return t;
}
}
}

__device__ __align__(1024) const tab::Table g_ctab = tab::make_table();
__device__ __align__(1024) const tab::Spec g_spec = tab::make_spec();

struct Scratch {
  uint32_t cnt_w[32];
  uint32_t cnt_x1[7 * 32];
  uint32_t cnt_y[7 * 32];
  uint32_t cnt_p[16 * 7 * 2 * 8];
  uint32_t epoch[NCTA * 12 + 240];
  float gate[S_];
  __nv_bfloat16 x1t[(D_ + 1) * S_];
  __nv_bfloat16 yt[D_ * S_];
  uint4 wt[114 * 1024];
  uint4 part[16 * 7 * 6 * 2 * 4 * 128];
};
static_assert(offsetof(Scratch, x1t) % 1024 == 0, "alignment");
__device__ __align__(1024) Scratch g_scratch;
#define TL(i)

namespace {

struct Params {
  Scratch* s;
  __nv_bfloat16* out;
  const __nv_bfloat16 *px, *w_r, *w_i, *gate_w, *pwg, *pwu, *pwd;
  const tab::Table* ctab;
  const tab::Spec* spec;
  CUtensorMap x, wg, wu, wd, ct, x1, yt;
};

__device__ __forceinline__ uint32_t smem_u32(const void* p) { return (uint32_t)__cvta_generic_to_shared(p); }
__device__ __forceinline__ void mbar_init(uint32_t bar, uint32_t cnt) {
  asm volatile("mbarrier.init.shared::cta.b64 [%0], %1;" ::"r"(bar), "r"(cnt) : "memory");
}
__device__ __forceinline__ void mbar_expect_tx(uint32_t bar, uint32_t bytes) {
  asm volatile("mbarrier.arrive.expect_tx.shared::cta.b64 _, [%0], %1;" ::"r"(bar), "r"(bytes) : "memory");
}
__device__ __forceinline__ void mbar_arrive(uint32_t bar) {
  asm volatile("mbarrier.arrive.shared::cta.b64 _, [%0];" ::"r"(bar) : "memory");
}
__device__ __forceinline__ void mbar_arrive_cluster(uint32_t bar, uint32_t cta) {
  asm volatile("{\n.reg .b32 ra;\nmapa.shared::cluster.u32 ra, %0, %1;\n"
               "mbarrier.arrive.shared::cluster.b64 _, [ra];\n}" ::"r"(bar), "r"(cta) : "memory");
}
__device__ __forceinline__ void mbar_wait(uint32_t bar, uint32_t parity) {
  uint32_t ok, n = 0;
  do {
    asm volatile("{\n.reg .pred p;\nmbarrier.try_wait.parity.shared::cta.b64 p, [%1], %2;\nselp.u32 %0, 1, 0, p;\n}"
                 : "=r"(ok) : "r"(bar), "r"(parity) : "memory");
  } while (!ok && ++n < SPIN_LIMIT);
}
__device__ __forceinline__ void mbar_wait_cluster(uint32_t bar, uint32_t parity) {
  uint32_t ok, n = 0;
  do {
    asm volatile("{\n.reg .pred p;\nmbarrier.try_wait.parity.acquire.cluster.shared::cta.b64 p, [%1], %2;\nselp.u32 %0, 1, 0, p;\n}"
                 : "=r"(ok) : "r"(bar), "r"(parity) : "memory");
  } while (!ok && ++n < SPIN_LIMIT);
}
__device__ __forceinline__ void tma2d(uint32_t dst, const CUtensorMap* m, int c0, int c1, uint32_t bar) {
  asm volatile("cp.async.bulk.tensor.2d.shared::cluster.global.mbarrier::complete_tx::bytes [%0], [%1, {%3, %4}], [%2];"
               ::"r"(dst), "l"(m), "r"(bar), "r"(c0), "r"(c1) : "memory");
}
__device__ __forceinline__ void tma3d(uint32_t dst, const CUtensorMap* m, int c0, int c1, int c2, uint32_t bar) {
  asm volatile("cp.async.bulk.tensor.3d.shared::cluster.global.mbarrier::complete_tx::bytes [%0], [%1, {%3, %4, %5}], [%2];"
               ::"r"(dst), "l"(m), "r"(bar), "r"(c0), "r"(c1), "r"(c2) : "memory");
}
__device__ __forceinline__ void tma4d(uint32_t dst, const CUtensorMap* m, int c2, uint32_t bar) {
  asm volatile("cp.async.bulk.tensor.4d.shared::cluster.global.mbarrier::complete_tx::bytes [%0], [%1, {%4, %4, %3, %4}], [%2];"
               ::"r"(dst), "l"(m), "r"(bar), "r"(c2), "r"(0) : "memory");
}
__device__ __forceinline__ void tma2d_mc(uint32_t dst, const CUtensorMap* m, int c0, int c1, uint32_t bar) {
  asm volatile("cp.async.bulk.tensor.2d.shared::cluster.global.mbarrier::complete_tx::bytes.multicast::cluster [%0], [%1, {%3, %4}], [%2], %5;"
               ::"r"(dst), "l"(m), "r"(bar), "r"(c0), "r"(c1), "h"((uint16_t)3) : "memory");
}
__device__ __forceinline__ void tma3d_mc(uint32_t dst, const CUtensorMap* m, int c0, int c1, int c2, uint32_t bar) {
  asm volatile("cp.async.bulk.tensor.3d.shared::cluster.global.mbarrier::complete_tx::bytes.multicast::cluster [%0], [%1, {%3, %4, %5}], [%2], %6;"
               ::"r"(dst), "l"(m), "r"(bar), "r"(c0), "r"(c1), "r"(c2), "h"((uint16_t)3) : "memory");
}
__device__ __forceinline__ void bulk_g2s(uint32_t dst, const void* src, uint32_t bytes, uint32_t bar) {
  asm volatile("cp.async.bulk.shared::cluster.global.mbarrier::complete_tx::bytes [%0], [%1], %2, [%3];"
               ::"r"(dst), "l"(src), "r"(bytes), "r"(bar) : "memory");
}
__device__ __forceinline__ void bulk_s2g(void* dst, uint32_t src, uint32_t bytes) {
  asm volatile("cp.async.bulk.global.shared::cta.bulk_group [%0], [%1], %2;" ::"l"(dst), "r"(src), "r"(bytes) : "memory");
}
__device__ __forceinline__ void prefetch_tmap(const CUtensorMap* m) {
  asm volatile("prefetch.tensormap [%0];" ::"l"(m) : "memory");
}
__device__ __forceinline__ void l2_prefetch(const void* p, uint32_t bytes) {
  asm volatile("cp.async.bulk.prefetch.L2.global [%0], %1;" ::"l"(p), "r"(bytes) : "memory");
}
__device__ __forceinline__ void wg_fence() { asm volatile("wgmma.fence.sync.aligned;" ::: "memory"); }
__device__ __forceinline__ void wg_commit() { asm volatile("wgmma.commit_group.sync.aligned;" ::: "memory"); }
template <int N> __device__ __forceinline__ void wg_wait() { asm volatile("wgmma.wait_group.sync.aligned %0;" ::"n"(N) : "memory"); }
template <int N> __device__ __forceinline__ void fence_regs(float (&d)[N]) {
#pragma unroll
  for (int i = 0; i < N; i++) asm volatile("" : "+f"(d[i])::"memory");
}
template <int N> __device__ __forceinline__ void fence_regs(uint32_t (&d)[N]) {
#pragma unroll
  for (int i = 0; i < N; i++) asm volatile("" : "+r"(d[i])::"memory");
}
__device__ __forceinline__ void bar_sync(int id, int n) { asm volatile("bar.sync %0, %1;" ::"r"(id), "r"(n) : "memory"); }
__device__ __forceinline__ void bar_arrive(int id, int n) { asm volatile("bar.arrive %0, %1;" ::"r"(id), "r"(n) : "memory"); }
__device__ __forceinline__ void fence_gpu() { asm volatile("fence.acq_rel.gpu;" ::: "memory"); }
__device__ __forceinline__ void fence_async() { asm volatile("fence.proxy.async;" ::: "memory"); }
__device__ __forceinline__ void fence_async_smem() { asm volatile("fence.proxy.async.shared::cta;" ::: "memory"); }
__device__ __forceinline__ void red_add(uint32_t* p, uint32_t v) {
  asm volatile("red.relaxed.gpu.global.add.u32 [%0], %1;" ::"l"(p), "r"(v) : "memory");
}
__device__ __forceinline__ uint32_t ld_relaxed(const uint32_t* p) {
  uint32_t v;
  asm volatile("ld.relaxed.gpu.global.u32 %0, [%1];" : "=r"(v) : "l"(p) : "memory");
  return v;
}
__device__ __forceinline__ void wait_counter(const uint32_t* p, uint32_t target) {
  uint32_t v, n = 0;
  while (true) {
    asm volatile("ld.acquire.gpu.global.u32 %0, [%1];" : "=r"(v) : "l"(p) : "memory");
    if ((int32_t)(v - target) >= 0 || ++n > SPIN_LIMIT) break;
  }
}
__device__ __forceinline__ uint4 ld_cg(const uint4* p) {
  uint4 v;
  asm volatile("ld.global.cg.v4.u32 {%0, %1, %2, %3}, [%4];" : "=r"(v.x), "=r"(v.y), "=r"(v.z), "=r"(v.w) : "l"(p) : "memory");
  return v;
}
__device__ __forceinline__ uint32_t pack2(float lo, float hi) {
  uint32_t r;
  asm("cvt.rn.bf16x2.f32 %0, %1, %2;" : "=r"(r) : "f"(hi), "f"(lo));
  return r;
}
__device__ __forceinline__ uint32_t mul2(uint32_t a, uint32_t b) {
  uint32_t r;
  asm("mul.rn.bf16x2 %0, %1, %2;" : "=r"(r) : "r"(a), "r"(b));
  return r;
}
__device__ __forceinline__ uint32_t fma2(uint32_t a, uint32_t b, uint32_t c) {
  uint32_t r;
  asm("fma.rn.bf16x2 %0, %1, %2, %3;" : "=r"(r) : "r"(a), "r"(b), "r"(c));
  return r;
}
__device__ __forceinline__ uint32_t add2(uint32_t a, uint32_t b) {
  uint32_t r;
  asm("add.rn.bf16x2 %0, %1, %2;" : "=r"(r) : "r"(a), "r"(b));
  return r;
}
__device__ __forceinline__ uint32_t sub2(uint32_t a, uint32_t b) {
  uint32_t r;
  asm("sub.rn.bf16x2 %0, %1, %2;" : "=r"(r) : "r"(a), "r"(b));
  return r;
}
__device__ __forceinline__ uint32_t fms2(uint32_t a, uint32_t b, uint32_t c) {
  uint32_t r;
  asm("{\n.reg .b32 n;\nneg.bf16x2 n, %3;\nfma.rn.bf16x2 %0, %1, %2, n;\n}" : "=r"(r) : "r"(a), "r"(b), "r"(c));
  return r;
}
__device__ __forceinline__ float bf_lo(uint32_t v) { return __uint_as_float(v << 16); }
__device__ __forceinline__ float bf_hi(uint32_t v) { return __uint_as_float(v & 0xffff0000u); }
__device__ __forceinline__ float bf_round(float v) { return bf_lo(pack2(v, 0.f)); }
__device__ __forceinline__ float tanh_fast(float v) {
  float r;
  asm("tanh.approx.f32 %0, %1;" : "=f"(r) : "f"(v));
  return r;
}
__device__ __forceinline__ uint64_t mk_desc(uint32_t addr, uint32_t lbo, uint32_t sbo, uint32_t mode) {
  return (uint64_t)((addr & 0x3FFFF) >> 4) | ((uint64_t)(lbo >> 4) << 16) | ((uint64_t)(sbo >> 4) << 32) | ((uint64_t)mode << 62);
}
__device__ __forceinline__ void stmatrix_x4(uint32_t addr, uint32_t r0, uint32_t r1, uint32_t r2, uint32_t r3) {
  asm volatile("stmatrix.sync.aligned.m8n8.x4.shared.b16 [%0], {%1, %2, %3, %4};" ::"r"(addr), "r"(r0), "r"(r1), "r"(r2), "r"(r3) : "memory");
}

template <int TA, int TB>
__device__ __forceinline__ void wgmma_ss_n256(float (&d)[128], uint64_t da, uint64_t db, int sd) {
  asm volatile("{\n.reg .pred p;\nsetp.ne.b32 p, %130, 0;\n"
      "wgmma.mma_async.sync.aligned.m64n256k16.f32.bf16.bf16 {"
      "%0, %1, %2, %3, %4, %5, %6, %7, %8, %9, %10, %11, %12, %13, %14, %15, %16, %17, %18, %19, %20, %21, %22, %23, "
      "%24, %25, %26, %27, %28, %29, %30, %31, %32, %33, %34, %35, %36, %37, %38, %39, %40, %41, %42, %43, %44, %45, "
      "%46, %47, %48, %49, %50, %51, %52, %53, %54, %55, %56, %57, %58, %59, %60, %61, %62, %63, %64, %65, %66, %67, "
      "%68, %69, %70, %71, %72, %73, %74, %75, %76, %77, %78, %79, %80, %81, %82, %83, %84, %85, %86, %87, %88, %89, "
      "%90, %91, %92, %93, %94, %95, %96, %97, %98, %99, %100, %101, %102, %103, %104, %105, %106, %107, %108, %109, "
      "%110, %111, %112, %113, %114, %115, %116, %117, %118, %119, %120, %121, %122, %123, %124, %125, %126, %127"
      "}, %128, %129, p, 1, 1, %131, %132;\n}\n"
      : "+f"(d[0]), "+f"(d[1]), "+f"(d[2]), "+f"(d[3]), "+f"(d[4]), "+f"(d[5]), "+f"(d[6]), "+f"(d[7]), "+f"(d[8]),
        "+f"(d[9]), "+f"(d[10]), "+f"(d[11]), "+f"(d[12]), "+f"(d[13]), "+f"(d[14]), "+f"(d[15]), "+f"(d[16]),
        "+f"(d[17]), "+f"(d[18]), "+f"(d[19]), "+f"(d[20]), "+f"(d[21]), "+f"(d[22]), "+f"(d[23]), "+f"(d[24]),
        "+f"(d[25]), "+f"(d[26]), "+f"(d[27]), "+f"(d[28]), "+f"(d[29]), "+f"(d[30]), "+f"(d[31]), "+f"(d[32]),
        "+f"(d[33]), "+f"(d[34]), "+f"(d[35]), "+f"(d[36]), "+f"(d[37]), "+f"(d[38]), "+f"(d[39]), "+f"(d[40]),
        "+f"(d[41]), "+f"(d[42]), "+f"(d[43]), "+f"(d[44]), "+f"(d[45]), "+f"(d[46]), "+f"(d[47]), "+f"(d[48]),
        "+f"(d[49]), "+f"(d[50]), "+f"(d[51]), "+f"(d[52]), "+f"(d[53]), "+f"(d[54]), "+f"(d[55]), "+f"(d[56]),
        "+f"(d[57]), "+f"(d[58]), "+f"(d[59]), "+f"(d[60]), "+f"(d[61]), "+f"(d[62]), "+f"(d[63]), "+f"(d[64]),
        "+f"(d[65]), "+f"(d[66]), "+f"(d[67]), "+f"(d[68]), "+f"(d[69]), "+f"(d[70]), "+f"(d[71]), "+f"(d[72]),
        "+f"(d[73]), "+f"(d[74]), "+f"(d[75]), "+f"(d[76]), "+f"(d[77]), "+f"(d[78]), "+f"(d[79]), "+f"(d[80]),
        "+f"(d[81]), "+f"(d[82]), "+f"(d[83]), "+f"(d[84]), "+f"(d[85]), "+f"(d[86]), "+f"(d[87]), "+f"(d[88]),
        "+f"(d[89]), "+f"(d[90]), "+f"(d[91]), "+f"(d[92]), "+f"(d[93]), "+f"(d[94]), "+f"(d[95]), "+f"(d[96]),
        "+f"(d[97]), "+f"(d[98]), "+f"(d[99]), "+f"(d[100]), "+f"(d[101]), "+f"(d[102]), "+f"(d[103]), "+f"(d[104]),
        "+f"(d[105]), "+f"(d[106]), "+f"(d[107]), "+f"(d[108]), "+f"(d[109]), "+f"(d[110]), "+f"(d[111]),
        "+f"(d[112]), "+f"(d[113]), "+f"(d[114]), "+f"(d[115]), "+f"(d[116]), "+f"(d[117]), "+f"(d[118]),
        "+f"(d[119]), "+f"(d[120]), "+f"(d[121]), "+f"(d[122]), "+f"(d[123]), "+f"(d[124]), "+f"(d[125]),
        "+f"(d[126]), "+f"(d[127])
      : "l"(da), "l"(db), "r"(sd), "n"(TA), "n"(TB));
}
template <int TA, int TB>
__device__ __forceinline__ void wgmma_ss_n128(float (&d)[64], uint64_t da, uint64_t db, int sd) {
  asm volatile("{\n.reg .pred p;\nsetp.ne.b32 p, %66, 0;\n"
      "wgmma.mma_async.sync.aligned.m64n128k16.f32.bf16.bf16 {"
      "%0, %1, %2, %3, %4, %5, %6, %7, %8, %9, %10, %11, %12, %13, %14, %15, %16, %17, %18, %19, %20, %21, %22, %23, "
      "%24, %25, %26, %27, %28, %29, %30, %31, %32, %33, %34, %35, %36, %37, %38, %39, %40, %41, %42, %43, %44, %45, "
      "%46, %47, %48, %49, %50, %51, %52, %53, %54, %55, %56, %57, %58, %59, %60, %61, %62, %63"
      "}, %64, %65, p, 1, 1, %67, %68;\n}\n"
      : "+f"(d[0]), "+f"(d[1]), "+f"(d[2]), "+f"(d[3]), "+f"(d[4]), "+f"(d[5]), "+f"(d[6]), "+f"(d[7]), "+f"(d[8]),
        "+f"(d[9]), "+f"(d[10]), "+f"(d[11]), "+f"(d[12]), "+f"(d[13]), "+f"(d[14]), "+f"(d[15]), "+f"(d[16]),
        "+f"(d[17]), "+f"(d[18]), "+f"(d[19]), "+f"(d[20]), "+f"(d[21]), "+f"(d[22]), "+f"(d[23]), "+f"(d[24]),
        "+f"(d[25]), "+f"(d[26]), "+f"(d[27]), "+f"(d[28]), "+f"(d[29]), "+f"(d[30]), "+f"(d[31]), "+f"(d[32]),
        "+f"(d[33]), "+f"(d[34]), "+f"(d[35]), "+f"(d[36]), "+f"(d[37]), "+f"(d[38]), "+f"(d[39]), "+f"(d[40]),
        "+f"(d[41]), "+f"(d[42]), "+f"(d[43]), "+f"(d[44]), "+f"(d[45]), "+f"(d[46]), "+f"(d[47]), "+f"(d[48]),
        "+f"(d[49]), "+f"(d[50]), "+f"(d[51]), "+f"(d[52]), "+f"(d[53]), "+f"(d[54]), "+f"(d[55]), "+f"(d[56]),
        "+f"(d[57]), "+f"(d[58]), "+f"(d[59]), "+f"(d[60]), "+f"(d[61]), "+f"(d[62]), "+f"(d[63])
      : "l"(da), "l"(db), "r"(sd), "n"(TA), "n"(TB));
}
template <int TA, int TB>
__device__ __forceinline__ void wgmma_ss_n64(float (&d)[32], uint64_t da, uint64_t db, int sd) {
  asm volatile("{\n.reg .pred p;\nsetp.ne.b32 p, %34, 0;\n"
      "wgmma.mma_async.sync.aligned.m64n64k16.f32.bf16.bf16 {"
      "%0, %1, %2, %3, %4, %5, %6, %7, %8, %9, %10, %11, %12, %13, %14, %15, %16, %17, %18, %19, %20, %21, %22, %23, "
      "%24, %25, %26, %27, %28, %29, %30, %31"
      "}, %32, %33, p, 1, 1, %35, %36;\n}\n"
      : "+f"(d[0]), "+f"(d[1]), "+f"(d[2]), "+f"(d[3]), "+f"(d[4]), "+f"(d[5]), "+f"(d[6]), "+f"(d[7]), "+f"(d[8]),
        "+f"(d[9]), "+f"(d[10]), "+f"(d[11]), "+f"(d[12]), "+f"(d[13]), "+f"(d[14]), "+f"(d[15]), "+f"(d[16]),
        "+f"(d[17]), "+f"(d[18]), "+f"(d[19]), "+f"(d[20]), "+f"(d[21]), "+f"(d[22]), "+f"(d[23]), "+f"(d[24]),
        "+f"(d[25]), "+f"(d[26]), "+f"(d[27]), "+f"(d[28]), "+f"(d[29]), "+f"(d[30]), "+f"(d[31])
      : "l"(da), "l"(db), "r"(sd), "n"(TA), "n"(TB));
}
template <int SA, int TB>
__device__ __forceinline__ void wgmma_rs_n64(float (&d)[32], uint32_t a0, uint32_t a1, uint32_t a2, uint32_t a3, uint64_t db, int sd) {
  asm volatile("{\n.reg .pred p;\nsetp.ne.b32 p, %37, 0;\n"
      "wgmma.mma_async.sync.aligned.m64n64k16.f32.bf16.bf16 {"
      "%0, %1, %2, %3, %4, %5, %6, %7, %8, %9, %10, %11, %12, %13, %14, %15, %16, %17, %18, %19, %20, %21, %22, %23, "
      "%24, %25, %26, %27, %28, %29, %30, %31"
      "}, {%32, %33, %34, %35}, %36, p, %38, 1, %39;\n}\n"
      : "+f"(d[0]), "+f"(d[1]), "+f"(d[2]), "+f"(d[3]), "+f"(d[4]), "+f"(d[5]), "+f"(d[6]), "+f"(d[7]), "+f"(d[8]),
        "+f"(d[9]), "+f"(d[10]), "+f"(d[11]), "+f"(d[12]), "+f"(d[13]), "+f"(d[14]), "+f"(d[15]), "+f"(d[16]),
        "+f"(d[17]), "+f"(d[18]), "+f"(d[19]), "+f"(d[20]), "+f"(d[21]), "+f"(d[22]), "+f"(d[23]), "+f"(d[24]),
        "+f"(d[25]), "+f"(d[26]), "+f"(d[27]), "+f"(d[28]), "+f"(d[29]), "+f"(d[30]), "+f"(d[31])
      : "r"(a0), "r"(a1), "r"(a2), "r"(a3), "l"(db), "r"(sd), "n"(SA), "n"(TB));
}

__device__ __forceinline__ uint32_t BAR_FULL(uint32_t sb, int i) { return sb + SM_BAR + 8 * i; }
__device__ __forceinline__ uint32_t BAR_EMPTY(uint32_t sb, int i) { return sb + SM_BAR + 64 + 8 * i; }
__device__ __forceinline__ uint32_t BAR_X(uint32_t sb, int i) { return sb + SM_BAR + 128 + 8 * i; }
__device__ __forceinline__ uint32_t BAR_Y(uint32_t sb, int i) { return sb + SM_BAR + 192 + 8 * i; }
__device__ __forceinline__ uint32_t BAR_XFREE(uint32_t sb) { return sb + SM_BAR + 256; }

#define CMASK 0x194u
#define XORDER 0, 1, 11, 2, 3, 12, 13, 4, 5, 14, 6, 15, 16
#define XSPREAD 2
#define PFAT 3
#define SKEW 3
constexpr int Q_G1B = 18, Q_G2 = 32, Q_P3 = 46, Q_END = 50;

struct Ring {
  uint32_t slot, phase;
  __device__ __forceinline__ void next() { if (++slot == NSTAGE) { slot = 0; phase ^= 1; } }
};

__device__ __forceinline__ void release_slot(uint32_t sb, uint32_t slot, int tid, int times) {
  if (tid < 2 * times) mbar_arrive_cluster(BAR_EMPTY(sb, slot), tid & 1);
}

__device__ __forceinline__ void ffn_consumer(uint32_t sb, const uint8_t* smem, const Params& p, int bid, int wg, int tid, int mt, int jj) {
  const int lane = tid & 31, warp = tid >> 5, q = lane & 3, r0 = 16 * warp + (lane >> 2);
  uint32_t* const my_epoch = &p.s->epoch[blockIdx.x * 12 + (threadIdx.x >> 5)];
  const uint32_t epoch = ld_relaxed(my_epoch) + 1;
  Ring rg{0, 0};
  uint32_t u[64];
  float acc[128];
  uint32_t prev = 0, cmask = CMASK;
  int st = 0;
  auto g1_stage = [&](uint32_t slot, int s) {
    const uint64_t da = mk_desc(sb + SM_X + (s >> 1) * 16384 + wg * 8192 + (s & 1) * 64, 16, 1024, 1);
    const uint64_t db = mk_desc(sb + SM_RING + slot * STAGE_BYTES, 4096, 1024, 1);
    wg_fence();
    wgmma_ss_n256<0, 1>(acc, da, db, s != 0);
    wgmma_ss_n256<0, 1>(acc, da + 2, db + 128, 1);
    wg_commit();
  };
  if (wg == 1) {
    float ap[64];
    constexpr int QX = 32 - __builtin_clz(CMASK);
    constexpr int NPRE = QX + XSPREAD;
    uint4* const x1dst = reinterpret_cast<uint4*>(p.s->x1t + (size_t)(64 * jj + r0 + 8) * S_ + 128 * mt + 8 * q);
    const int x1lo = 64 * jj + r0 == 1 ? (D_ - 9) * (S_ / 8) : -S_;
#pragma unroll
    for (int qi = 0; qi < NPRE; qi++) {
      const int slot = qi % NSTAGE, nc = __builtin_popcount(CMASK & ((1u << qi) - 1));
      if (qi == 0) TL(60);
      mbar_wait(BAR_FULL(sb, slot), (qi / NSTAGE) & 1);
      if (qi == 0) TL(61);
      if ((CMASK >> qi) & 1) {
#pragma unroll
        for (int kb = 2 * nc; kb < 2 * nc + 2 && kb < 7; kb++) {
          const uint64_t da = mk_desc(sb + SM_RING + slot * STAGE_BYTES + (kb & 1) * 8192, 8192, 1024, 1);
          const uint64_t db = mk_desc(sb + SM_X + kb * 16384, 16, 1024, 1);
          mbar_wait(BAR_X(sb, kb), 0);
          TL(16 + kb);
          wg_fence();
#pragma unroll
          for (int kk = 0; kk < 4; kk++) wgmma_ss_n128<1, 0>(ap, da + kk * 128, db + kk * 2, (kb | kk) != 0);
          wg_commit();
        }
      } else {
        if (((qi - nc) & 1) == 0 && qi - nc >= 4 * nc) mbar_wait(BAR_X(sb, (qi - nc) >> 1), 0);
        TL(32 + qi - nc);
        g1_stage(slot, qi - nc);
      }
      if (qi > 0) {
        wg_wait<1>();
        release_slot(sb, (qi - 1) % NSTAGE, tid, ((CMASK >> (qi - 1)) & 1) ? 2 : 1);
      }
      if (qi >= QX) {
        if (qi == QX) { fence_regs(ap); TL(2); }
#pragma unroll
        for (int t = (qi - QX) * (4 / XSPREAD); t < (qi - QX + 1) * (4 / XSPREAD); t++)
#pragma unroll
        for (int h = 0; h < 2; h++)
          x1dst[(h ? 0 : x1lo) + 4 * t] = make_uint4(pack2(ap[16 * t + 2 * h], ap[16 * t + 2 * h + 1]), pack2(ap[16 * t + 4 + 2 * h], ap[16 * t + 5 + 2 * h]),
                                             pack2(ap[16 * t + 8 + 2 * h], ap[16 * t + 9 + 2 * h]), pack2(ap[16 * t + 12 + 2 * h], ap[16 * t + 13 + 2 * h]));
      }
    }
    bar_arrive(7, 160);
    st = NPRE - 4; cmask = 0; prev = (NPRE - 1) % NSTAGE;
    rg.slot = NPRE % NSTAGE; rg.phase = (NPRE / NSTAGE) & 1;
  }
#pragma unroll 1
  for (int pass = 0; pass < 2; pass++) {
#pragma unroll 1
    for (; st < 14; st++) {
      while (cmask & 1) { cmask >>= 1; rg.next(); }
      cmask >>= 1;
      if (pass == 0 && (st & 1) == 0) mbar_wait(BAR_X(sb, st >> 1), 0);
      if (st == 14 - SKEW && wg == 1) bar_sync(9 + pass, 256);
      mbar_wait(BAR_FULL(sb, rg.slot), rg.phase);
      TL(32 + 14 * pass + st);
      g1_stage(rg.slot, st);
      wg_wait<1>();
      if (st > 0) release_slot(sb, prev, tid, 1);
      prev = rg.slot;
      rg.next();
    }
    st = 0;
    if (wg == 0) bar_arrive(9 + pass, 256);
    wg_wait<0>();
    fence_regs(acc);
    release_slot(sb, prev, tid, 1);
    if (pass == 1 && tid == 0) mbar_arrive(BAR_XFREE(sb));
    TL(3 + 2 * pass);
#pragma unroll
    for (int i = 0; i < 32; i++) {
      const float g0 = 0.5f * acc[2 * i], g1 = 0.5f * acc[2 * i + 1];
      const float s0 = fmaf(g0, tanh_fast(g0), g0), s1 = fmaf(g1, tanh_fast(g1), g1);
      u[32 + i] = pack2(s0 * acc[64 + 2 * i], s1 * acc[64 + 2 * i + 1]);
    }
    if (pass == 0) {
#pragma unroll
      for (int i = 0; i < 32; i++) u[i] = u[32 + i];
    }
    TL(4 + 2 * pass);
  }
  fence_regs(u);
  float accA[32], accB[32];
  rg.slot = Q_G2 % NSTAGE; rg.phase = (Q_G2 / NSTAGE) & 1;
  auto stage = [&](float (&acc)[32], int st) {
    mbar_wait(BAR_FULL(sb, rg.slot), rg.phase);
    const uint64_t db = mk_desc(sb + SM_RING + rg.slot * STAGE_BYTES, 8192, 1024, 1);
    wg_fence();
#pragma unroll
    for (int kk = 0; kk < 8; kk++) {
      const uint32_t* a = u + 32 * st + 4 * kk;
      wgmma_rs_n64<1, 1>(acc, a[0], a[1], a[2], a[3], db + kk * 128, (st | kk) != 0);
    }
    wg_commit();
  };
  auto retire = [&](bool rel) {
    wg_wait<1>();
    if (rel) release_slot(sb, prev, tid, 1);
    prev = rg.slot;
    rg.next();
  };
  auto put = [&](float (&acc)[32], int c) {
    fence_regs(acc);
    int o = jj + 1 + c;
    if (o >= 7) o -= 7;
    uint4* dst = p.s->part + ((((mt * 7 + o) * 6 + c) * 2 + wg) * 4) * 128 + tid;
#pragma unroll
    for (int v = 0; v < 4; v++) {
      const float* a = acc + 8 * v;
      dst[v * 128] = make_uint4(pack2(a[0], a[1]), pack2(a[2], a[3]), pack2(a[4], a[5]), pack2(a[6], a[7]));
    }
  };
  float sum[32];
  uint4 pv[8];
  auto gload = [&](int c) {
    if (lane == 0) wait_counter(&p.s->cnt_p[((mt * 7 + jj) * 2 + wg) * 8 + c], epoch * 2);
    __syncwarp();
    TL(24 + c);
    const uint4* src = p.s->part + (((mt * 7 + jj) * 6 * 2 + wg) * 4) * 128 + tid;
#pragma unroll
    for (int i = 0; i < 8; i++) pv[i] = ld_cg(src + ((2 * c + (i >> 2)) * 8 + (i & 3)) * 128);
  };
  auto gsum = [&](bool first) {
#pragma unroll
    for (int i = 0; i < 8; i++) {
      const float t[8] = {bf_lo(pv[i].x), bf_hi(pv[i].x), bf_lo(pv[i].y), bf_hi(pv[i].y), bf_lo(pv[i].z), bf_hi(pv[i].z), bf_lo(pv[i].w), bf_hi(pv[i].w)};
#pragma unroll
      for (int k = 0; k < 8; k++) sum[8 * (i & 3) + k] = (first && i < 4) ? t[k] : sum[8 * (i & 3) + k] + t[k];
    }
  };
#pragma unroll
  for (int c2 = 0; c2 < 4; c2++) {
    stage(accA, 0);
    retire(c2 == 1 || c2 == 2);
    stage(accA, 1);
    if (c2 > 0) { put(accB, 2 * c2 - 1); bar_arrive(3 * wg + c2, 160); }
    TL(7 + c2);
    if (c2 == 3) { gsum(true); gload(1); break; }
    retire(true);
    stage(accB, 0);
    retire(true);
    stage(accB, 1);
    put(accA, 2 * c2);
    if (c2 == 2) gload(0);
    retire(true);
  }
  rg.next();
#pragma unroll 1
  for (int kb = 0; kb < 7; kb++) {
    if ((kb & 1) == 0) mbar_wait(BAR_FULL(sb, rg.slot), rg.phase);
    mbar_wait(BAR_Y(sb, kb), 0);
    const uint64_t da = mk_desc(sb + SM_X + kb * 16384 + wg * 8192, 8192, 1024, 1);
    const uint64_t db = mk_desc(sb + SM_RING + rg.slot * STAGE_BYTES + (kb & 1) * 8192, 16, 1024, 1);
    wg_fence();
#pragma unroll
    for (int kk = 0; kk < 4; kk++) wgmma_ss_n64<1, 0>(accB, da + kk * 128, db + kk * 2, (kb | kk) != 0);
    wg_commit();
    if (kb & 1) rg.next();
  }
  TL(11);
  const int row = 128 * mt + 64 * wg + r0;
  gsum(false);
  gload(2);
  const float ga0 = __ldcg(&p.s->gate[row]), ga1 = __ldcg(&p.s->gate[row + 8]);
  gsum(false);
  TL(12);
  wg_wait<0>();
  fence_regs(accA);
  fence_regs(accB);
  TL(13);
  const float gb0 = bf_round(1.f - ga0), gb1 = bf_round(1.f - ga1);
  const float gs0 = ga0 * (2.f / (float)(S_ * D_)), gs1 = ga1 * (2.f / (float)(S_ * D_));
  uint4* const o = reinterpret_cast<uint4*>(p.out + (size_t)row * D_ + 64 * jj + 8 * q);
#pragma unroll
  for (int h = 0; h < 2; h++) {
    const float gs = h ? gs1 : gs0, gb = h ? gb1 : gb0;
#pragma unroll
    for (int k = 0; k < 2; k++) {
      uint32_t w[4];
#pragma unroll
      for (int j = 0; j < 4; j++) {
        const int i = 16 * k + 4 * j + 2 * h;
        w[j] = pack2(fmaf(gs, accB[i], gb * (accA[i] + sum[i])), fmaf(gs, accB[i + 1], gb * (accA[i + 1] + sum[i + 1])));
      }
      const bool o1 = q & 1, o2 = q & 2;
      uint32_t a = __shfl_xor_sync(0xffffffffu, o1 ? w[0] : w[1], 1), b = __shfl_xor_sync(0xffffffffu, o1 ? w[2] : w[3], 1);
      if (o1) { w[0] = a; w[2] = b; } else { w[1] = a; w[3] = b; }
      a = __shfl_xor_sync(0xffffffffu, o2 ? w[0] : w[2], 2); b = __shfl_xor_sync(0xffffffffu, o2 ? w[1] : w[3], 2);
      if (o2) { w[0] = a; w[1] = b; } else { w[2] = a; w[3] = b; }
      o[h * D_ + 4 * k] = make_uint4(w[0], w[1], w[2], w[3]);
    }
  }
  if (lane == 0) *my_epoch = epoch;
  TL(14);
}

__device__ __forceinline__ void ring_issue(uint32_t sb, const Params& p, int qi, uint32_t slot, bool wait, uint32_t phase, int jj, uint32_t rank) {
  const CUtensorMap* m;
  int c0, c1, c2 = 0;
  bool half = false, is3d = false;
  if (qi < Q_G2) {
    const int nc = __popc(CMASK & ((1u << qi) - 1));
    if ((CMASK >> qi) & 1) {
      m = &p.ct; c0 = 64 * jj; c1 = 128 * nc + 64 * rank; half = nc == 3;
    } else {
      const int pass = qi >= Q_G1B;
      m = rank ? &p.wu : &p.wg; c0 = 0; c1 = 32 * (qi - nc - 14 * pass); c2 = 4 * jj + 2 * pass; is3d = true;
    }
  } else if (qi < Q_P3) {
    int o = jj + 1 + ((qi - Q_G2) >> 1);
    if (o >= 7) o -= 7;
    m = &p.wd; c0 = 64 * o; c1 = 256 * jj + 128 * (qi & 1) + 64 * rank;
  } else {
    m = &p.ct; c0 = 128 * (qi - Q_P3) + 64 * rank; c1 = 64 * jj; half = qi == Q_END - 1;
  }
  const uint32_t bar = BAR_FULL(sb, slot);
  const uint32_t dst = sb + SM_RING + slot * STAGE_BYTES + rank * 8192;
  if (wait) mbar_wait_cluster(BAR_EMPTY(sb, slot), phase);
  mbar_expect_tx(bar, half ? 8192 : 16384);
  if (is3d) tma3d_mc(dst, m, c0, c1, c2, bar);
  else if (!(half && rank)) tma2d_mc(dst, m, c0, c1, bar);
}

__device__ __forceinline__ void ffn_producer(uint32_t sb, const uint8_t* smem, int bid, const Params& p, int warp, int lane, int mt, int jj, uint32_t rank) {
  if (warp < 2) {
    if (lane == 0) {
      uint32_t slot = warp, phase = 0;
#pragma unroll 1
      for (int qi = NSTAGE + warp; qi < Q_END; qi += 2) {
        ring_issue(sb, p, qi, slot, true, phase, jj, rank);
        TL(10 + qi);
        slot += 2;
        if (slot >= NSTAGE) { slot -= NSTAGE; phase ^= 1; }
      }
    }
  } else {
    const int wg = warp - 2;
    if (wg == 0) {
      if (lane == 0) { prefetch_tmap(&p.wd); prefetch_tmap(&p.yt); }
      uint32_t* const my_epoch = &p.s->epoch[blockIdx.x * 12 + 10];
      const uint32_t epoch = ld_relaxed(my_epoch) + 1;
      {
        const uint4* gw4 = reinterpret_cast<const uint4*>(p.gate_w);
        const uint4 ga = __ldg(gw4 + lane), gb = lane < 24 ? __ldg(gw4 + 32 + lane) : make_uint4(0, 0, 0, 0);
        if (lane < 7) mbar_wait(BAR_X(sb, lane), 0);
        __syncwarp();
        float mine = 0.f;
#pragma unroll 1
        for (int u = 0; u < 19; u++) {
          const int r = min(19 * jj + u, 127);
          const uint8_t* xr = smem + SM_X + (lane >> 3) * 16384 + r * 128 + (((lane ^ r) & 7) << 4);
          const uint4 xa = *reinterpret_cast<const uint4*>(xr);
          const uint4 xb = lane < 24 ? *reinterpret_cast<const uint4*>(xr + 65536) : make_uint4(0, 0, 0, 0);
          float s = 0.f;
          auto dot2 = [&](uint32_t a, uint32_t b) {
            const uint32_t pr = mul2(a, b);
            s += bf_lo(pr) + bf_hi(pr);
          };
          dot2(xa.x, ga.x); dot2(xa.y, ga.y); dot2(xa.z, ga.z); dot2(xa.w, ga.w);
          dot2(xb.x, gb.x); dot2(xb.y, gb.y); dot2(xb.z, gb.z); dot2(xb.w, gb.w);
#pragma unroll
          for (int o = 16; o > 0; o >>= 1) s += __shfl_xor_sync(0xffffffffu, s, o);
          if (lane == u) mine = s;
        }
        if (lane < 19 && 19 * jj + lane < 128) p.s->gate[128 * mt + 19 * jj + lane] = bf_round(1.f / (1.f + __expf(-bf_round(mine))));
        bar_arrive(8, 64);
      }
      TL(9);
      mbar_wait(BAR_XFREE(sb), 0);
      TL(3);
      bool todo = lane < 7;
      uint32_t n = 0;
      while (__any_sync(0xffffffffu, todo)) {
        if (todo) {
          uint32_t v;
          asm volatile("ld.acquire.gpu.global.u32 %0, [%1];" : "=r"(v) : "l"(&p.s->cnt_y[lane * 32]) : "memory");
          if ((int32_t)(v - epoch * (lane ? 16 : 17)) >= 0 || ++n > SPIN_LIMIT) {
            fence_async();
            mbar_expect_tx(BAR_Y(sb, lane), 16384);
            tma3d(sb + SM_X + lane * 16384, &p.yt, 0, 64 * lane, 2 * mt, BAR_Y(sb, lane));
            todo = false;
          }
        }
      }
      TL(4);
      if (lane == 0) *my_epoch = epoch;
    } else {
      mbar_wait(BAR_X(sb, PFAT), 0);
      if (lane < 6) {
        int row = 176 + 3 * bid + (lane >> 1);
        if (row >= D_) row -= D_;
        l2_prefetch(((lane & 1) ? p.pwu : p.pwg) + row * F_, F_ * 2);
      }
      TL(2);
      bar_sync(7, 160);
      if (lane == 0) { fence_gpu(); red_add(&p.s->cnt_x1[jj * 32], 1); l2_prefetch(p.pwd + bid * 16 * D_, 32 * D_); }
      TL(3);
      bar_sync(8, 64);
    }
#pragma unroll 1
    for (int c = 0; c < 3; c++) {
      bar_sync(1 + 3 * wg + c, 160);
      if (lane < 2) {
        int o = jj + 1 + 2 * c + lane;
        if (o >= 7) o -= 7;
        fence_gpu();
        red_add(&p.s->cnt_p[((mt * 7 + o) * 2 + wg) * 8 + c], 1);
      }
      TL(5 + c);
    }
  }
}

__device__ __forceinline__ void spectral_cta(uint32_t sb, uint8_t* smem, const Params& p, int sc, int wg) {
  const int t384 = threadIdx.x, lane = t384 & 31, warp12 = t384 >> 5, tid = t384 & 127;
  const int warp = tid >> 5, q = lane & 3;
  const int sl0 = 6 * sc + min(sc, 8), nsl = sc < 8 ? 7 : 6;
  if (t384 == 320) {
#pragma unroll 1
    for (int i = 0; i < nsl; i++) {
      mbar_expect_tx(BAR_X(sb, i), 2 * SLAB_BYTES);
      const int row = 128 * ((sl0 + i) >> 3) + 8 * ((sl0 + i) & 7);
      const uint32_t dst = sb + SP_Z + 2 * i * SLAB_BYTES;
      bulk_g2s(dst, p.w_r + row * DF_, SLAB_BYTES / 2, BAR_X(sb, i));
      bulk_g2s(dst + SLAB_BYTES / 2, p.w_r + (row + 64) * DF_, SLAB_BYTES / 2, BAR_X(sb, i));
      bulk_g2s(dst + SLAB_BYTES, p.w_i + row * DF_, SLAB_BYTES / 2, BAR_X(sb, i));
      bulk_g2s(dst + 3 * SLAB_BYTES / 2, p.w_i + (row + 64) * DF_, SLAB_BYTES / 2, BAR_X(sb, i));
    }
    if (sc < 19) {
      mbar_expect_tx(BAR_Y(sb, 6), 24576);
      bulk_g2s(sb + SP_TW, p.spec, 24576, BAR_Y(sb, 6));
      prefetch_tmap(&p.x1);
    }
  }
  uint32_t* const my_epoch = &p.s->epoch[blockIdx.x * 12 + warp12];
  const uint32_t epoch = ld_relaxed(my_epoch) + 1;
  uint32_t fe[16], tw[16];
#pragma unroll
  for (int i = 0; i < 4; i++) {
    const uint4 a = __ldg(reinterpret_cast<const uint4*>(p.spec->fe) + i * 128 + tid);
    const uint4 b = __ldg(reinterpret_cast<const uint4*>(p.spec->tw) + i * 128 + tid);
    fe[4 * i] = a.x; fe[4 * i + 1] = a.y; fe[4 * i + 2] = a.z; fe[4 * i + 3] = a.w;
    tw[4 * i] = b.x; tw[4 * i + 1] = b.y; tw[4 * i + 2] = b.z; tw[4 * i + 3] = b.w;
  }
  __syncwarp();
  asm volatile("barrier.cluster.wait.acquire.aligned;" ::: "memory");
#pragma unroll 2
  for (int un = wg; un < 8 * nsl; un += 3) {
    const int i = un >> 3, sl = sl0 + i, pr = 16 * (un & 7) + 4 * (lane >> 3) + warp, r = lane & 7;
    mbar_wait(BAR_X(sb, i), 0);
    if (pr < 113) {
      const uint16_t* w = reinterpret_cast<const uint16_t*>(smem + SP_Z + 2 * i * SLAB_BYTES) + r * DF_ + 2 * pr;
      const uint32_t m = pr < 112 ? 0xffffffffu : 0u;
      p.s->wt[pr * 1024 + sl * 8 + (r ^ ((sl >> 2) & 6))] =
          make_uint4(w[0] | ((uint32_t)w[8 * DF_] << 16), w[16 * DF_] | ((uint32_t)w[24 * DF_] << 16),
                     (w[1] | ((uint32_t)w[8 * DF_ + 1] << 16)) & m, (w[16 * DF_ + 1] | ((uint32_t)w[24 * DF_ + 1] << 16)) & m);
    }
  }
  __syncthreads();
  if (t384 == 352) { fence_gpu(); red_add(&p.s->cnt_w[0], 1); }
  TL(1);
  if (sc == 19) return;
  const int nrnd = (sc == 18 && wg == 2) ? 1 : 2;
  if (tid == 32) {
    wait_counter(&p.s->cnt_w[0], epoch * NSPEC);
    fence_async();
    for (int rnd = 0; rnd < nrnd; rnd++) {
      const int item = wg + 3 * rnd;
      mbar_expect_tx(BAR_Y(sb, item), 16384);
      bulk_g2s(sb + SP_W + item * 16384, p.s->wt + (6 * sc + item) * 1024, 16384, BAR_Y(sb, item));
    }
  } else if (tid == 0) {
#pragma unroll 1
    for (int rnd = 0; rnd < nrnd; rnd++) {
      const int item = wg + 3 * rnd, pr = 6 * sc + item;
      wait_counter(&p.s->cnt_x1[(pr < 112 ? pr >> 4 : 0) * 32], epoch * 16);
      fence_async();
      const uint32_t bar = BAR_FULL(sb, item), z = sb + SP_Z + item * 16384;
      mbar_expect_tx(bar, 16384);
      tma4d(z, &p.x1, 4 * pr, bar);
    }
  }
  __syncwarp();
  fence_regs(fe); fence_regs(tw);
  mbar_wait(BAR_Y(sb, 6), 0);
  TL(3);
  const uint64_t dT_n = mk_desc(sb + SP_T, 8192, 1024, 1);
#pragma unroll 1
  for (int rnd = 0; rnd < nrnd; rnd++) {
    const int item = wg + 3 * rnd, pr = 6 * sc + item;
    const uint32_t z = sb + SP_Z + item * 16384;
    uint32_t fa[16], fb[16];
    auto load_frag = [&](int off) {
#pragma unroll
      for (int i = 0; i < 4; i++) {
        const uint4 a = *reinterpret_cast<const uint4*>(smem + SP_TW + off + i * 2048 + tid * 16);
        fa[4 * i] = a.x; fa[4 * i + 1] = a.y; fa[4 * i + 2] = a.z; fa[4 * i + 3] = a.w;
      }
      fence_regs(fa);
    };
    load_frag(0);
    mbar_wait(BAR_FULL(sb, item), 0);
    TL(4 + 8 * rnd);
    if (rnd == 0 && wg > 0) bar_sync(3 + wg, 256);
    float aR[32], aI[32];
    {
      const uint64_t de = mk_desc(z, 4096, 512, 2);
      wg_fence();
#pragma unroll
      for (int kk = 0; kk < 4; kk++) {
        wgmma_rs_n64<1, 1>(aR, fe[4 * kk], fe[4 * kk + 1], fe[4 * kk + 2], fe[4 * kk + 3], de + kk * 64, kk != 0);
        wgmma_rs_n64<1, 1>(aI, fa[4 * kk], fa[4 * kk + 1], fa[4 * kk + 2], fa[4 * kk + 3], de + 512 + kk * 64, kk != 0);
      }
      wg_commit();
      if (rnd == 0 && wg < 2) bar_arrive(4 + wg, 256);
      wg_wait<0>();
      fence_regs(aR); fence_regs(aI);
    }
    TL(5 + 8 * rnd);
#pragma unroll
    for (int v = 0; v < 8; v++) {
      uint32_t* f = (v < 4 ? fa : fb) + 2 * (v & 3);
      const uint32_t* t = tw + 2 * (v & 3);
      const float *e = aR + 4 * v, *o = aI + 4 * v;
      const uint32_t er = pack2(e[0], e[1]), ei = pack2(e[2], e[3]), qr = pack2(o[0], o[1]), qi = pack2(o[2], o[3]);
      const uint32_t u0r = add2(er, qr), u0i = add2(ei, qi), u1r = sub2(er, qr), u1i = sub2(ei, qi);
      f[0] = fma2(u0r, t[0], mul2(u0i, t[8]));
      f[8] = fms2(u0i, t[0], mul2(u0r, t[8]));
      f[1] = fma2(u1r, t[1], mul2(u1i, t[9]));
      f[9] = fms2(u1i, t[1], mul2(u1r, t[9]));
    }
    fence_regs(fa); fence_regs(fb);
    wg_fence();
#pragma unroll
    for (int kk = 0; kk < 4; kk++) {
      wgmma_rs_n64<1, 1>(aR, fa[4 * kk], fa[4 * kk + 1], fa[4 * kk + 2], fa[4 * kk + 3], dT_n + kk * 128, kk != 0);
      wgmma_rs_n64<1, 1>(aI, fb[4 * kk], fb[4 * kk + 1], fb[4 * kk + 2], fb[4 * kk + 3], dT_n + kk * 128, kk != 0);
    }
    wg_commit();
    mbar_wait(BAR_Y(sb, item), 0);
    wg_wait<0>();
    fence_regs(aR); fence_regs(aI);
    TL(6 + 8 * rnd);
    {
      const uint8_t* wp = smem + SP_W + item * 16384 + q * 1024 + warp * 128 + (((lane >> 2) ^ (2 * q)) << 4);
#pragma unroll
      for (int jb = 0; jb < 4; jb++) {
#pragma unroll
        for (int h = 0; h < 2; h++) {
          const uint4 w = *reinterpret_cast<const uint4*>(wp + jb * 4096 + h * 512);
          const int i = 4 * jb + 2 * h;
          const uint32_t ar = pack2(aR[i], aR[i + 1]), ai = pack2(aR[16 + i], aR[17 + i]);
          const uint32_t br = pack2(aI[i], aI[i + 1]), bi = pack2(aI[16 + i], aI[17 + i]);
          fa[2 * jb + h] = fms2(ar, w.x, mul2(ai, w.y));
          fa[8 + 2 * jb + h] = fma2(ar, w.y, mul2(ai, w.x));
          fb[2 * jb + h] = fms2(br, w.z, mul2(bi, w.w));
          fb[8 + 2 * jb + h] = fma2(br, w.w, mul2(bi, w.z));
        }
      }
    }
    fence_regs(fa); fence_regs(fb);
    wg_fence();
#pragma unroll
    for (int kk = 0; kk < 4; kk++) {
      wgmma_rs_n64<1, 0>(aR, fa[4 * kk], fa[4 * kk + 1], fa[4 * kk + 2], fa[4 * kk + 3], dT_n + kk * 2, kk != 0);
      wgmma_rs_n64<1, 0>(aI, fb[4 * kk], fb[4 * kk + 1], fb[4 * kk + 2], fb[4 * kk + 3], dT_n + kk * 2, kk != 0);
    }
    wg_commit();
    wg_wait<0>();
    fence_regs(aR); fence_regs(aI);
    TL(7 + 8 * rnd);
#pragma unroll
    for (int v = 0; v < 8; v++) {
      const float* a = (v < 4 ? aR : aI) + 4 * (v & 3);
      const uint32_t* t = tw + 2 * (v & 3);
      const uint32_t u0r = pack2(a[0], a[1]), u1r = pack2(a[2], a[3]), u0i = pack2(a[16], a[17]), u1i = pack2(a[18], a[19]);
      const uint32_t t0r = fms2(u0r, t[0], mul2(u0i, t[8])), t0i = fma2(u0i, t[0], mul2(u0r, t[8]));
      const uint32_t t1r = fms2(u1r, t[1], mul2(u1i, t[9])), t1i = fma2(u1i, t[1], mul2(u1r, t[9]));
      fa[v] = add2(t0i, t1i); fa[8 + v] = add2(t0r, t1r);
      fb[v] = sub2(t0i, t1i); fb[8 + v] = sub2(t0r, t1r);
    }
    bar_sync(1 + wg, 128);
#pragma unroll
    for (int u = 0; u < 4; u++) {
      const uint32_t a = z + (32 * (u >> 1) + 8 * warp + (lane & 7)) * 128 + (((4 * (u & 1) + (lane >> 3)) ^ (lane & 7)) << 4);
      stmatrix_x4(a, fa[4 * u], fa[4 * u + 1], fa[4 * u + 2], fa[4 * u + 3]);
      stmatrix_x4(a + 8192, fb[4 * u], fb[4 * u + 1], fb[4 * u + 2], fb[4 * u + 3]);
    }
    load_frag(8192);
    fence_async_smem();
    bar_sync(1 + wg, 128);
    TL(8 + 8 * rnd);
    {
      const uint64_t de = mk_desc(z, 8192, 1024, 1);
      wg_fence();
#pragma unroll
      for (int kk = 0; kk < 4; kk++) {
        wgmma_rs_n64<1, 1>(aR, fe[4 * kk], fe[4 * kk + 1], fe[4 * kk + 2], fe[4 * kk + 3], de + kk * 128, kk != 0);
        wgmma_rs_n64<1, 1>(aI, fa[4 * kk], fa[4 * kk + 1], fa[4 * kk + 2], fa[4 * kk + 3], de + 512 + kk * 128, kk != 0);
      }
      wg_commit();
      wg_wait<0>();
      fence_regs(aR); fence_regs(aI);
    }
    TL(9 + 8 * rnd);
    const bool edge = pr == 0 || pr == 112;
    if (edge) {
#pragma unroll
      for (int i = 0; i < 16; i++) { aR[i] *= 0.5f; aI[i] *= 0.5f; }
    }
#pragma unroll
    for (int i = 0; i < 8; i++) {
      const float* a = ((i & 1) ? aI : aR) + 16 * (i >> 2) + 2 - (i & 2);
      *reinterpret_cast<uint4*>(smem + SP_W + item * 16384 + (i >> 1) * 4096 + (i & 1) * 64 + (tid >> 2) * 128 + q * 16) =
          make_uint4(pack2(a[0], a[1]), pack2(a[4], a[5]), pack2(a[8], a[9]), pack2(a[12], a[13]));
    }
    fence_async_smem();
    bar_sync(1 + wg, 128);
    if (tid == 0) {
      const uint32_t src = sb + SP_W + item * 16384;
      __nv_bfloat16* dst = p.s->yt + (size_t)(pr < 112 ? 4 * pr : 1) * S_;
      bulk_s2g(dst, src, edge ? 4096 : 16384);
      if (pr == 0) bulk_s2g(dst + 2 * S_, src + 8192, 8192);
      asm volatile("cp.async.bulk.commit_group;" ::: "memory");
      if (rnd == nrnd - 1) {
        asm volatile("cp.async.bulk.wait_group 0;" ::: "memory");
        TL(11);
        fence_async();
        fence_gpu();
        red_add(&p.s->cnt_y[(pr < 112 ? pr >> 4 : 0) * 32], 1);
        if (rnd) red_add(&p.s->cnt_y[((pr - 3) >> 4) * 32], 1);
      }
    }
    __syncwarp();
    TL(10 + 8 * rnd);
  }
  if (lane == 0) *my_epoch = epoch;
}

__global__ void __cluster_dims__(2, 1, 1) __launch_bounds__(384, 1)
fused_kernel(const __grid_constant__ Params p) {
  extern __shared__ __align__(1024) uint8_t smem[];
  const uint32_t sb = smem_u32(smem);
  TL(0);
  const uint32_t rank = blockIdx.x & 1;
  const int hc = blockIdx.x >> 1;
  int grp, jj;
  if (hc < 4) { grp = 8; jj = hc; }
  else if (hc < 36) { grp = (hc - 4) & 7; jj = (hc - 4) >> 3; }
  else if (hc < 57) { jj = (hc - 36) / 7; grp = 1 + (hc - 36) - 7 * jj; jj += 4; }
  else if (hc < 60) { grp = 0; jj = hc - 53; }
  else { grp = 8; jj = hc - 56; }
  const int mt = 2 * grp + rank, bid = 2 * (7 * grp + jj) + rank;
  if (threadIdx.x == 256) {
#pragma unroll
    for (int i = 0; i < NSTAGE; i++) { mbar_init(BAR_FULL(sb, i), 1); mbar_init(BAR_EMPTY(sb, i), 4); }
    asm volatile("fence.mbarrier_init.release.cluster;" ::: "memory");
  } else if (threadIdx.x == 320) {
#pragma unroll
    for (int i = 0; i < NSTAGE; i++) { mbar_init(BAR_X(sb, i), 1); mbar_init(BAR_Y(sb, i), 1); }
    mbar_init(BAR_XFREE(sb), 2);
    asm volatile("fence.mbarrier_init.release.cluster;" ::: "memory");
  } else if (threadIdx.x == 288) {
    prefetch_tmap(rank ? &p.wu : &p.wg); prefetch_tmap(&p.ct);
  }
  __syncwarp();
  asm volatile("barrier.cluster.arrive.relaxed.aligned;" ::: "memory");
  const int wg = __shfl_sync(0xffffffffu, threadIdx.x >> 7, 0);
  if (bid >= NFFN) {
    spectral_cta(sb, smem, p, bid - NFFN, wg);
  } else if (wg < 2) {
    asm volatile("setmaxnreg.inc.sync.aligned.u32 232;");
    asm volatile("barrier.cluster.wait.acquire.aligned;" ::: "memory");
    TL(1);
    ffn_consumer(sb, smem, p, bid, wg, threadIdx.x & 127, mt, jj);
  } else {
    asm volatile("setmaxnreg.dec.sync.aligned.u32 40;");
    if (threadIdx.x == 320) {
      mbar_expect_tx(BAR_X(sb, 0), 16384);
      tma2d(sb + SM_X, &p.x, 0, 128 * mt, BAR_X(sb, 0));
    }
    __syncwarp();
    asm volatile("barrier.cluster.wait.acquire.aligned;" ::: "memory");
    TL(1);
    if (threadIdx.x == 320) {
      constexpr int order[13] = {XORDER};
#pragma unroll
      for (int i = 0; i < 13; i++) {
        if (order[i] < 8) {
          ring_issue(sb, p, order[i], order[i], false, 0, jj, rank);
        } else {
          const int kb = order[i] - 10;
          mbar_expect_tx(BAR_X(sb, kb), 16384);
          tma2d(sb + SM_X + kb * 16384, &p.x, 64 * kb, 128 * mt, BAR_X(sb, kb));
        }
      }
      TL(2);
    } else if (threadIdx.x == 352) {
    }
    __syncwarp();
    ffn_producer(sb, smem, bid, p, (threadIdx.x >> 5) & 3, threadIdx.x & 31, mt, jj, rank);
  }
}

typedef CUresult (*EncodeFn)(CUtensorMap*, CUtensorMapDataType, cuuint32_t, void*, const cuuint64_t*, const cuuint64_t*,
                             const cuuint32_t*, const cuuint32_t*, CUtensorMapInterleave, CUtensorMapSwizzle,
                             CUtensorMapL2promotion, CUtensorMapFloatOOBfill);

void make_map(EncodeFn fn, CUtensorMap* m, const void* base, int rank, const cuuint64_t* dims, const cuuint64_t* strides,
              const cuuint32_t* box, CUtensorMapSwizzle sw) {
  const cuuint32_t es[4] = {1, 1, 1, 1};
  fn(m, CU_TENSOR_MAP_DATA_TYPE_BFLOAT16, rank, const_cast<void*>(base), dims, strides, box, es,
     CU_TENSOR_MAP_INTERLEAVE_NONE, sw, CU_TENSOR_MAP_L2_PROMOTION_L2_256B, CU_TENSOR_MAP_FLOAT_OOB_FILL_NONE);
}

}

extern "C" void kernel_launch(void* const* d_in, const int* in_sizes, int n_in, void* d_out, int out_size) {
  const __nv_bfloat16* x = (const __nv_bfloat16*)d_in[0];
  const __nv_bfloat16* w_r = (const __nv_bfloat16*)d_in[1];
  const __nv_bfloat16* w_i = (const __nv_bfloat16*)d_in[2];
  const __nv_bfloat16* wg = (const __nv_bfloat16*)d_in[4];
  const __nv_bfloat16* wu = (const __nv_bfloat16*)d_in[5];
  const __nv_bfloat16* wd = (const __nv_bfloat16*)d_in[6];
  const __nv_bfloat16* gate_w = (const __nv_bfloat16*)d_in[7];

  void* fnp = nullptr;
  cudaDriverEntryPointQueryResult qr;
  cudaGetDriverEntryPoint("cuTensorMapEncodeTiled", &fnp, cudaEnableDefault, &qr);
  EncodeFn fn = (EncodeFn)fnp;
  void *ctab, *spec, *scr;
  cudaGetSymbolAddress(&ctab, g_ctab);
  cudaGetSymbolAddress(&spec, g_spec);
  cudaGetSymbolAddress(&scr, g_scratch);
  const void* x1t = (const char*)scr + offsetof(Scratch, x1t);
  const void* yt = (const char*)scr + offsetof(Scratch, yt);
  Params p;
  p.s = (Scratch*)scr; p.out = (__nv_bfloat16*)d_out;
  p.px = x; p.w_r = w_r; p.w_i = w_i; p.gate_w = gate_w; p.pwg = wg; p.pwu = wu; p.pwd = wd;
  p.ctab = (const tab::Table*)ctab; p.spec = (const tab::Spec*)spec;
  {
    const cuuint64_t d[2] = {D_, S_}, s[1] = {D_ * 2};
    const cuuint32_t b[2] = {64, 128};
    make_map(fn, &p.x, x, 2, d, s, b, CU_TENSOR_MAP_SWIZZLE_128B);
  }
  {
    const cuuint64_t d[3] = {64, D_, F_ / 64}, s[2] = {F_ * 2, 128};
    const cuuint32_t b[3] = {64, 32, 2};
    make_map(fn, &p.wg, wg, 3, d, s, b, CU_TENSOR_MAP_SWIZZLE_128B);
    make_map(fn, &p.wu, wu, 3, d, s, b, CU_TENSOR_MAP_SWIZZLE_128B);
  }
  {
    const cuuint64_t d[2] = {D_, F_}, s[1] = {D_ * 2};
    const cuuint32_t b[2] = {64, 64};
    make_map(fn, &p.wd, wd, 2, d, s, b, CU_TENSOR_MAP_SWIZZLE_128B);
  }
  {
    const cuuint64_t d[2] = {D_, D_}, s[1] = {D_ * 2};
    const cuuint32_t b[2] = {64, 64};
    make_map(fn, &p.ct, ctab, 2, d, s, b, CU_TENSOR_MAP_SWIZZLE_128B);
  }
  {
    const cuuint64_t d[4] = {32, 32, D_ + 1, 2}, s[3] = {128, S_ * 2, 64};
    const cuuint32_t b[4] = {32, 32, 4, 2};
    make_map(fn, &p.x1, x1t, 4, d, s, b, CU_TENSOR_MAP_SWIZZLE_64B);
  }
  {
    const cuuint64_t d[3] = {64, D_, S_ / 64}, s[2] = {S_ * 2, 128};
    const cuuint32_t b[3] = {64, 64, 2};
    make_map(fn, &p.yt, yt, 3, d, s, b, CU_TENSOR_MAP_SWIZZLE_128B);
  }
  cudaFuncSetAttribute(fused_kernel, cudaFuncAttributeMaxDynamicSharedMemorySize, SM_TOTAL);
  fused_kernel<<<NCTA, 384, SM_TOTAL, cudaStreamPerThread>>>(p, x, w_r, w_i, gate_w, wd, (__nv_bfloat16*)d_out);
}
```

```cpp
#include <cuda_runtime.h>
#include <cuda_bf16.h>
#include <cuda.h>
#include <stdint.h>
#include <stddef.h>

namespace {

constexpr int S_ = 2048, D_ = 448, F_ = 1792, DF_ = 225;
constexpr int NFFN = 112, NSPEC = 20, NCTA = NFFN + NSPEC;
constexpr int NSTAGE = 7, STAGE_BYTES = 16384;
constexpr int SM_X = 0, SM_RING = 114688, SM_BAR = 229376, SM_TOTAL = SM_BAR + 512;
constexpr int SP_Z = 0, SP_W = 98304, SP_TW = 198656, SP_T = 215040, SLAB_BYTES = 16 * DF_ * 2;
constexpr uint32_t SPIN_LIMIT = 1u << 20;

namespace tab {
constexpr double PI = 3.14159265358979323846264338327950288;
constexpr double csin(double x) {
  double t = x, s = x;
  for (int i = 1; i < 20; i++) { t = -t * x * x / ((2 * i) * (2 * i + 1)); s += t; }
  return s;
}
constexpr double ccos(double x) {
  double t = 1, s = 1;
  for (int i = 1; i < 20; i++) { t = -t * x * x / ((2 * i - 1) * (2 * i)); s += t; }
  return s;
}
constexpr uint32_t to_bf16(double v) {
  uint32_t sign = v < 0 ? 0x8000u : 0u;
  double a = v < 0 ? -v : v;
  if (a < 1e-12) return 0;
  int e = 0;
  while (a >= 2.0) { a /= 2; e++; }
  while (a < 1.0) { a *= 2; e--; }
  double m = a * 128.0;
  int mi = (int)m;
  double fr = m - mi;
  if (fr > 0.5 || (fr == 0.5 && (mi & 1))) mi++;
  if (mi == 256) { mi = 128; e++; }
  return sign | (uint32_t)((e + 127) << 7) | (uint32_t)(mi - 128);
}
struct Base { uint32_t v[448]; };
constexpr Base make_base() {
  Base b{};
  for (int m = 0; m < 448; m++) {
    int mm = m > 224 ? m - 448 : m;
    double ang = 2 * PI * mm / 448.0;
    b.v[m] = to_bf16(ccos(ang)) | (to_bf16(-csin(ang)) << 16);
  }
  return b;
}
constexpr Base base = make_base();
struct Row { uint32_t v[224]; };
constexpr Row make_row(int d) {
  Row r{};
  r.v[0] = 0x3f80u | ((d & 1) ? 0xbf800000u : 0x3f800000u);
  int m = 0;
  for (int c = 1; c < 224; c++) { m += d; if (m >= 448) m -= 448; r.v[c] = base.v[m]; }
  return r;
}
struct Table { Row r[448]; };
constexpr Table make_table() {
  Table t{};
  for (int d = 0; d < 448; d++) t.r[d] = make_row(d);
  return t;
}
struct Cs { double c[2048], s[2048]; };
constexpr Cs make_cs() {
  Cs t{};
  for (int m = 0; m <= 256; m++) {
    const double a = 2 * PI * m / 2048.0, c = ccos(a), s = csin(a);
    t.c[m] = c; t.s[m] = s;
    t.c[512 - m] = s; t.s[512 - m] = c;
  }
  for (int m = 513; m < 2048; m++) { t.c[m] = -t.s[m - 512]; t.s[m] = t.c[m - 512]; }
  return t;
}
constexpr Cs cs = make_cs();
struct Spec {
  uint32_t fo[2048], fot[2048];
  uint16_t t32[4096];
  uint32_t fe[2048];
  uint32_t tw[2048];
};
constexpr uint32_t blk(int h, int c, int a) { return to_bf16(h == c ? cs.c[a & 2047] : (h ? -cs.s[a & 2047] : cs.s[a & 2047])); }
constexpr Spec make_spec() {
  Spec t{};
  for (int row = 0; row < 64; row++)
    for (int col = 0; col < 64; col++) {
      const int c = row & 31, k2 = col & 31, n2 = 8 * ((c >> 1) & 3) + 2 * (c >> 3) + (c & 1), m = 64 * ((n2 * k2) & 31);
      const double v = (row >> 5) == (col >> 5) ? cs.c[m] : (row < 32 ? -cs.s[m] : cs.s[m]);
      t.t32[row * 64 + (((col >> 3) ^ (row & 7)) << 3) + (col & 7)] = (uint16_t)to_bf16(v);
    }
  for (int th = 0; th < 128; th++)
    for (int i = 0; i < 16; i++) {
      const int r = 8 * (th >> 5) + ((th & 31) >> 2), h = i & 1, c = i >> 3, m = 8 * ((i >> 1) & 3) + 2 * (th & 3);
      const int o = ((i >> 2) * 128 + th) * 4 + (i & 3);
      t.fe[o] = blk(h, c, 64 * m * r) | (blk(h, c, 64 * (m + 1) * r) << 16);
      t.fo[o] = blk(h, c, 32 * (2 * m + 1) * r) | (blk(h, c, 32 * (2 * m + 3) * r) << 16);
      t.fot[o] = blk(h, c, 32 * (2 * r + 1) * m) | (blk(h, c, 32 * (2 * r + 1) * (m + 1)) << 16);
      const int k1 = r + 32 * h, n2 = 8 * (th & 3) + 2 * ((i >> 1) & 3);
      t.tw[o] = blk(0, c, n2 * k1) | (blk(0, c, (n2 + 1) * k1) << 16);
    }
  return t;
}
}
}

__device__ __align__(1024) const tab::Table g_ctab = tab::make_table();
__device__ __align__(1024) const tab::Spec g_spec = tab::make_spec();

struct Scratch {
  uint32_t cnt_w[32];
  uint32_t cnt_x1[7 * 32];
  uint32_t cnt_y[7 * 32];
  uint32_t epoch[NCTA * 12 + 240 + 256];
  uint32_t gate[S_];
  __nv_bfloat16 x1t[(D_ + 1) * S_];
  __nv_bfloat16 yt[D_ * S_];
  uint4 wt[114 * 1024];
  uint4 part[16 * 7 * 6 * 2 * 4 * 128];
};
static_assert(offsetof(Scratch, x1t) % 1024 == 0, "alignment");
__device__ __align__(1024) Scratch g_scratch;
#define TL(i)

namespace {

struct Params {
  Scratch* s;
  __nv_bfloat16* out;
  const __nv_bfloat16 *px, *w_r, *w_i, *gate_w, *pwg, *pwu, *pwd;
  const tab::Table* ctab;
  const tab::Spec* spec;
  CUtensorMap x, wg, wu, wd, ct, x1, yt;
};

__device__ __forceinline__ uint32_t smem_u32(const void* p) { return (uint32_t)__cvta_generic_to_shared(p); }
__device__ __forceinline__ void mbar_init(uint32_t bar, uint32_t cnt) {
  asm volatile("mbarrier.init.shared::cta.b64 [%0], %1;" ::"r"(bar), "r"(cnt) : "memory");
}
__device__ __forceinline__ void mbar_expect_tx(uint32_t bar, uint32_t bytes) {
  asm volatile("mbarrier.arrive.expect_tx.shared::cta.b64 _, [%0], %1;" ::"r"(bar), "r"(bytes) : "memory");
}
__device__ __forceinline__ void mbar_arrive(uint32_t bar) {
  asm volatile("mbarrier.arrive.shared::cta.b64 _, [%0];" ::"r"(bar) : "memory");
}
__device__ __forceinline__ void mbar_arrive_cluster(uint32_t bar, uint32_t cta) {
  asm volatile("{\n.reg .b32 ra;\nmapa.shared::cluster.u32 ra, %0, %1;\n"
               "mbarrier.arrive.shared::cluster.b64 _, [ra];\n}" ::"r"(bar), "r"(cta) : "memory");
}
__device__ __forceinline__ void mbar_wait(uint32_t bar, uint32_t parity) {
  uint32_t ok, n = 0;
  do {
    asm volatile("{\n.reg .pred p;\nmbarrier.try_wait.parity.shared::cta.b64 p, [%1], %2;\nselp.u32 %0, 1, 0, p;\n}"
                 : "=r"(ok) : "r"(bar), "r"(parity) : "memory");
  } while (!ok && ++n < SPIN_LIMIT);
}
__device__ __forceinline__ void mbar_wait_cluster(uint32_t bar, uint32_t parity) {
  uint32_t ok, n = 0;
  do {
    asm volatile("{\n.reg .pred p;\nmbarrier.try_wait.parity.acquire.cluster.shared::cta.b64 p, [%1], %2;\nselp.u32 %0, 1, 0, p;\n}"
                 : "=r"(ok) : "r"(bar), "r"(parity) : "memory");
  } while (!ok && ++n < SPIN_LIMIT);
}
__device__ __forceinline__ void tma2d(uint32_t dst, const CUtensorMap* m, int c0, int c1, uint32_t bar) {
  asm volatile("cp.async.bulk.tensor.2d.shared::cluster.global.mbarrier::complete_tx::bytes [%0], [%1, {%3, %4}], [%2];"
               ::"r"(dst), "l"(m), "r"(bar), "r"(c0), "r"(c1) : "memory");
}
__device__ __forceinline__ void tma3d(uint32_t dst, const CUtensorMap* m, int c0, int c1, int c2, uint32_t bar) {
  asm volatile("cp.async.bulk.tensor.3d.shared::cluster.global.mbarrier::complete_tx::bytes [%0], [%1, {%3, %4, %5}], [%2];"
               ::"r"(dst), "l"(m), "r"(bar), "r"(c0), "r"(c1), "r"(c2) : "memory");
}
__device__ __forceinline__ void tma4d(uint32_t dst, const CUtensorMap* m, int c2, uint32_t bar) {
  asm volatile("cp.async.bulk.tensor.4d.shared::cluster.global.mbarrier::complete_tx::bytes [%0], [%1, {%4, %4, %3, %4}], [%2];"
               ::"r"(dst), "l"(m), "r"(bar), "r"(c2), "r"(0) : "memory");
}
__device__ __forceinline__ void tma2d_mc(uint32_t dst, const CUtensorMap* m, int c0, int c1, uint32_t bar) {
  asm volatile("cp.async.bulk.tensor.2d.shared::cluster.global.mbarrier::complete_tx::bytes.multicast::cluster [%0], [%1, {%3, %4}], [%2], %5;"
               ::"r"(dst), "l"(m), "r"(bar), "r"(c0), "r"(c1), "h"((uint16_t)3) : "memory");
}
__device__ __forceinline__ void tma3d_mc(uint32_t dst, const CUtensorMap* m, int c0, int c1, int c2, uint32_t bar) {
  asm volatile("cp.async.bulk.tensor.3d.shared::cluster.global.mbarrier::complete_tx::bytes.multicast::cluster [%0], [%1, {%3, %4, %5}], [%2], %6;"
               ::"r"(dst), "l"(m), "r"(bar), "r"(c0), "r"(c1), "r"(c2), "h"((uint16_t)3) : "memory");
}
__device__ __forceinline__ void bulk_g2s(uint32_t dst, const void* src, uint32_t bytes, uint32_t bar) {
  asm volatile("cp.async.bulk.shared::cluster.global.mbarrier::complete_tx::bytes [%0], [%1], %2, [%3];"
               ::"r"(dst), "l"(src), "r"(bytes), "r"(bar) : "memory");
}
__device__ __forceinline__ void bulk_s2g(void* dst, uint32_t src, uint32_t bytes) {
  asm volatile("cp.async.bulk.global.shared::cta.bulk_group [%0], [%1], %2;" ::"l"(dst), "r"(src), "r"(bytes) : "memory");
}
__device__ __forceinline__ void prefetch_tmap(const CUtensorMap* m) {
  asm volatile("prefetch.tensormap [%0];" ::"l"(m) : "memory");
}
__device__ __forceinline__ void l2_prefetch(const void* p, uint32_t bytes) {
  asm volatile("cp.async.bulk.prefetch.L2.global [%0], %1;" ::"l"(p), "r"(bytes) : "memory");
}
__device__ __forceinline__ void wg_fence() { asm volatile("wgmma.fence.sync.aligned;" ::: "memory"); }
__device__ __forceinline__ void wg_commit() { asm volatile("wgmma.commit_group.sync.aligned;" ::: "memory"); }
template <int N> __device__ __forceinline__ void wg_wait() { asm volatile("wgmma.wait_group.sync.aligned %0;" ::"n"(N) : "memory"); }
template <int N> __device__ __forceinline__ void fence_regs(float (&d)[N]) {
#pragma unroll
  for (int i = 0; i < N; i++) asm volatile("" : "+f"(d[i])::"memory");
}
template <int N> __device__ __forceinline__ void fence_regs(uint32_t (&d)[N]) {
#pragma unroll
  for (int i = 0; i < N; i++) asm volatile("" : "+r"(d[i])::"memory");
}
__device__ __forceinline__ void bar_sync(int id, int n) { asm volatile("bar.sync %0, %1;" ::"r"(id), "r"(n) : "memory"); }
__device__ __forceinline__ void bar_arrive(int id, int n) { asm volatile("bar.arrive %0, %1;" ::"r"(id), "r"(n) : "memory"); }
__device__ __forceinline__ void fence_gpu() { asm volatile("fence.acq_rel.gpu;" ::: "memory"); }
__device__ __forceinline__ void fence_async() { asm volatile("fence.proxy.async;" ::: "memory"); }
__device__ __forceinline__ void fence_async_smem() { asm volatile("fence.proxy.async.shared::cta;" ::: "memory"); }
__device__ __forceinline__ void red_add(uint32_t* p, uint32_t v) {
  asm volatile("red.relaxed.gpu.global.add.u32 [%0], %1;" ::"l"(p), "r"(v) : "memory");
}
__device__ __forceinline__ uint32_t ld_relaxed(const uint32_t* p) {
  uint32_t v;
  asm volatile("ld.relaxed.gpu.global.u32 %0, [%1];" : "=r"(v) : "l"(p) : "memory");
  return v;
}
__device__ __forceinline__ void wait_counter(const uint32_t* p, uint32_t target) {
  uint32_t v, n = 0;
  while (true) {
    asm volatile("ld.acquire.gpu.global.u32 %0, [%1];" : "=r"(v) : "l"(p) : "memory");
    if ((int32_t)(v - target) >= 0 || ++n > SPIN_LIMIT) break;
  }
}
__device__ __forceinline__ uint4 ld_relaxed(const uint4* p) {
  uint4 v;
  asm volatile("ld.relaxed.gpu.global.v4.u32 {%0, %1, %2, %3}, [%4];" : "=r"(v.x), "=r"(v.y), "=r"(v.z), "=r"(v.w) : "l"(p) : "memory");
  return v;
}
__device__ __forceinline__ void st_relaxed(uint4* p, uint4 v) {
  asm volatile("st.relaxed.gpu.global.v4.u32 [%0], {%1, %2, %3, %4};" ::"l"(p), "r"(v.x), "r"(v.y), "r"(v.z), "r"(v.w) : "memory");
}
__device__ __forceinline__ void st_relaxed(uint32_t* p, uint32_t v) {
  asm volatile("st.relaxed.gpu.global.u32 [%0], %1;" ::"l"(p), "r"(v) : "memory");
}
__device__ __forceinline__ uint32_t pack2(float lo, float hi) {
  uint32_t r;
  asm("cvt.rn.bf16x2.f32 %0, %1, %2;" : "=r"(r) : "f"(hi), "f"(lo));
  return r;
}
__device__ __forceinline__ uint32_t mul2(uint32_t a, uint32_t b) {
  uint32_t r;
  asm("mul.rn.bf16x2 %0, %1, %2;" : "=r"(r) : "r"(a), "r"(b));
  return r;
}
__device__ __forceinline__ uint32_t fma2(uint32_t a, uint32_t b, uint32_t c) {
  uint32_t r;
  asm("fma.rn.bf16x2 %0, %1, %2, %3;" : "=r"(r) : "r"(a), "r"(b), "r"(c));
  return r;
}
__device__ __forceinline__ uint32_t add2(uint32_t a, uint32_t b) {
  uint32_t r;
  asm("add.rn.bf16x2 %0, %1, %2;" : "=r"(r) : "r"(a), "r"(b));
  return r;
}
__device__ __forceinline__ uint32_t sub2(uint32_t a, uint32_t b) {
  uint32_t r;
  asm("sub.rn.bf16x2 %0, %1, %2;" : "=r"(r) : "r"(a), "r"(b));
  return r;
}
__device__ __forceinline__ uint32_t fms2(uint32_t a, uint32_t b, uint32_t c) {
  uint32_t r;
  asm("{\n.reg .b32 n;\nneg.bf16x2 n, %3;\nfma.rn.bf16x2 %0, %1, %2, n;\n}" : "=r"(r) : "r"(a), "r"(b), "r"(c));
  return r;
}
__device__ __forceinline__ float bf_lo(uint32_t v) { return __uint_as_float(v << 16); }
__device__ __forceinline__ float bf_hi(uint32_t v) { return __uint_as_float(v & 0xffff0000u); }
__device__ __forceinline__ float bf_round(float v) { return bf_lo(pack2(v, 0.f)); }
__device__ __forceinline__ float tanh_fast(float v) {
  float r;
  asm("tanh.approx.f32 %0, %1;" : "=f"(r) : "f"(v));
  return r;
}
__device__ __forceinline__ uint64_t mk_desc(uint32_t addr, uint32_t lbo, uint32_t sbo, uint32_t mode) {
  return (uint64_t)((addr & 0x3FFFF) >> 4) | ((uint64_t)(lbo >> 4) << 16) | ((uint64_t)(sbo >> 4) << 32) | ((uint64_t)mode << 62);
}
__device__ __forceinline__ void stmatrix_x4(uint32_t addr, uint32_t r0, uint32_t r1, uint32_t r2, uint32_t r3) {
  asm volatile("stmatrix.sync.aligned.m8n8.x4.shared.b16 [%0], {%1, %2, %3, %4};" ::"r"(addr), "r"(r0), "r"(r1), "r"(r2), "r"(r3) : "memory");
}

template <int TA, int TB>
__device__ __forceinline__ void wgmma_ss_n256(float (&d)[128], uint64_t da, uint64_t db, int sd) {
  asm volatile("{\n.reg .pred p;\nsetp.ne.b32 p, %130, 0;\n"
      "wgmma.mma_async.sync.aligned.m64n256k16.f32.bf16.bf16 {"
      "%0, %1, %2, %3, %4, %5, %6, %7, %8, %9, %10, %11, %12, %13, %14, %15, %16, %17, %18, %19, %20, %21, %22, %23, "
      "%24, %25, %26, %27, %28, %29, %30, %31, %32, %33, %34, %35, %36, %37, %38, %39, %40, %41, %42, %43, %44, %45, "
      "%46, %47, %48, %49, %50, %51, %52, %53, %54, %55, %56, %57, %58, %59, %60, %61, %62, %63, %64, %65, %66, %67, "
      "%68, %69, %70, %71, %72, %73, %74, %75, %76, %77, %78, %79, %80, %81, %82, %83, %84, %85, %86, %87, %88, %89, "
      "%90, %91, %92, %93, %94, %95, %96, %97, %98, %99, %100, %101, %102, %103, %104, %105, %106, %107, %108, %109, "
      "%110, %111, %112, %113, %114, %115, %116, %117, %118, %119, %120, %121, %122, %123, %124, %125, %126, %127"
      "}, %128, %129, p, 1, 1, %131, %132;\n}\n"
      : "+f"(d[0]), "+f"(d[1]), "+f"(d[2]), "+f"(d[3]), "+f"(d[4]), "+f"(d[5]), "+f"(d[6]), "+f"(d[7]), "+f"(d[8]),
        "+f"(d[9]), "+f"(d[10]), "+f"(d[11]), "+f"(d[12]), "+f"(d[13]), "+f"(d[14]), "+f"(d[15]), "+f"(d[16]),
        "+f"(d[17]), "+f"(d[18]), "+f"(d[19]), "+f"(d[20]), "+f"(d[21]), "+f"(d[22]), "+f"(d[23]), "+f"(d[24]),
        "+f"(d[25]), "+f"(d[26]), "+f"(d[27]), "+f"(d[28]), "+f"(d[29]), "+f"(d[30]), "+f"(d[31]), "+f"(d[32]),
        "+f"(d[33]), "+f"(d[34]), "+f"(d[35]), "+f"(d[36]), "+f"(d[37]), "+f"(d[38]), "+f"(d[39]), "+f"(d[40]),
        "+f"(d[41]), "+f"(d[42]), "+f"(d[43]), "+f"(d[44]), "+f"(d[45]), "+f"(d[46]), "+f"(d[47]), "+f"(d[48]),
        "+f"(d[49]), "+f"(d[50]), "+f"(d[51]), "+f"(d[52]), "+f"(d[53]), "+f"(d[54]), "+f"(d[55]), "+f"(d[56]),
        "+f"(d[57]), "+f"(d[58]), "+f"(d[59]), "+f"(d[60]), "+f"(d[61]), "+f"(d[62]), "+f"(d[63]), "+f"(d[64]),
        "+f"(d[65]), "+f"(d[66]), "+f"(d[67]), "+f"(d[68]), "+f"(d[69]), "+f"(d[70]), "+f"(d[71]), "+f"(d[72]),
        "+f"(d[73]), "+f"(d[74]), "+f"(d[75]), "+f"(d[76]), "+f"(d[77]), "+f"(d[78]), "+f"(d[79]), "+f"(d[80]),
        "+f"(d[81]), "+f"(d[82]), "+f"(d[83]), "+f"(d[84]), "+f"(d[85]), "+f"(d[86]), "+f"(d[87]), "+f"(d[88]),
        "+f"(d[89]), "+f"(d[90]), "+f"(d[91]), "+f"(d[92]), "+f"(d[93]), "+f"(d[94]), "+f"(d[95]), "+f"(d[96]),
        "+f"(d[97]), "+f"(d[98]), "+f"(d[99]), "+f"(d[100]), "+f"(d[101]), "+f"(d[102]), "+f"(d[103]), "+f"(d[104]),
        "+f"(d[105]), "+f"(d[106]), "+f"(d[107]), "+f"(d[108]), "+f"(d[109]), "+f"(d[110]), "+f"(d[111]),
        "+f"(d[112]), "+f"(d[113]), "+f"(d[114]), "+f"(d[115]), "+f"(d[116]), "+f"(d[117]), "+f"(d[118]),
        "+f"(d[119]), "+f"(d[120]), "+f"(d[121]), "+f"(d[122]), "+f"(d[123]), "+f"(d[124]), "+f"(d[125]),
        "+f"(d[126]), "+f"(d[127])
      : "l"(da), "l"(db), "r"(sd), "n"(TA), "n"(TB));
}
template <int TA, int TB>
__device__ __forceinline__ void wgmma_ss_n128(float (&d)[64], uint64_t da, uint64_t db, int sd) {
  asm volatile("{\n.reg .pred p;\nsetp.ne.b32 p, %66, 0;\n"
      "wgmma.mma_async.sync.aligned.m64n128k16.f32.bf16.bf16 {"
      "%0, %1, %2, %3, %4, %5, %6, %7, %8, %9, %10, %11, %12, %13, %14, %15, %16, %17, %18, %19, %20, %21, %22, %23, "
      "%24, %25, %26, %27, %28, %29, %30, %31, %32, %33, %34, %35, %36, %37, %38, %39, %40, %41, %42, %43, %44, %45, "
      "%46, %47, %48, %49, %50, %51, %52, %53, %54, %55, %56, %57, %58, %59, %60, %61, %62, %63"
      "}, %64, %65, p, 1, 1, %67, %68;\n}\n"
      : "+f"(d[0]), "+f"(d[1]), "+f"(d[2]), "+f"(d[3]), "+f"(d[4]), "+f"(d[5]), "+f"(d[6]), "+f"(d[7]), "+f"(d[8]),
        "+f"(d[9]), "+f"(d[10]), "+f"(d[11]), "+f"(d[12]), "+f"(d[13]), "+f"(d[14]), "+f"(d[15]), "+f"(d[16]),
        "+f"(d[17]), "+f"(d[18]), "+f"(d[19]), "+f"(d[20]), "+f"(d[21]), "+f"(d[22]), "+f"(d[23]), "+f"(d[24]),
        "+f"(d[25]), "+f"(d[26]), "+f"(d[27]), "+f"(d[28]), "+f"(d[29]), "+f"(d[30]), "+f"(d[31]), "+f"(d[32]),
        "+f"(d[33]), "+f"(d[34]), "+f"(d[35]), "+f"(d[36]), "+f"(d[37]), "+f"(d[38]), "+f"(d[39]), "+f"(d[40]),
        "+f"(d[41]), "+f"(d[42]), "+f"(d[43]), "+f"(d[44]), "+f"(d[45]), "+f"(d[46]), "+f"(d[47]), "+f"(d[48]),
        "+f"(d[49]), "+f"(d[50]), "+f"(d[51]), "+f"(d[52]), "+f"(d[53]), "+f"(d[54]), "+f"(d[55]), "+f"(d[56]),
        "+f"(d[57]), "+f"(d[58]), "+f"(d[59]), "+f"(d[60]), "+f"(d[61]), "+f"(d[62]), "+f"(d[63])
      : "l"(da), "l"(db), "r"(sd), "n"(TA), "n"(TB));
}
template <int TA, int TB>
__device__ __forceinline__ void wgmma_ss_n64(float (&d)[32], uint64_t da, uint64_t db, int sd) {
  asm volatile("{\n.reg .pred p;\nsetp.ne.b32 p, %34, 0;\n"
      "wgmma.mma_async.sync.aligned.m64n64k16.f32.bf16.bf16 {"
      "%0, %1, %2, %3, %4, %5, %6, %7, %8, %9, %10, %11, %12, %13, %14, %15, %16, %17, %18, %19, %20, %21, %22, %23, "
      "%24, %25, %26, %27, %28, %29, %30, %31"
      "}, %32, %33, p, 1, 1, %35, %36;\n}\n"
      : "+f"(d[0]), "+f"(d[1]), "+f"(d[2]), "+f"(d[3]), "+f"(d[4]), "+f"(d[5]), "+f"(d[6]), "+f"(d[7]), "+f"(d[8]),
        "+f"(d[9]), "+f"(d[10]), "+f"(d[11]), "+f"(d[12]), "+f"(d[13]), "+f"(d[14]), "+f"(d[15]), "+f"(d[16]),
        "+f"(d[17]), "+f"(d[18]), "+f"(d[19]), "+f"(d[20]), "+f"(d[21]), "+f"(d[22]), "+f"(d[23]), "+f"(d[24]),
        "+f"(d[25]), "+f"(d[26]), "+f"(d[27]), "+f"(d[28]), "+f"(d[29]), "+f"(d[30]), "+f"(d[31])
      : "l"(da), "l"(db), "r"(sd), "n"(TA), "n"(TB));
}
template <int SA, int TB>
__device__ __forceinline__ void wgmma_rs_n64(float (&d)[32], uint32_t a0, uint32_t a1, uint32_t a2, uint32_t a3, uint64_t db, int sd) {
  asm volatile("{\n.reg .pred p;\nsetp.ne.b32 p, %37, 0;\n"
      "wgmma.mma_async.sync.aligned.m64n64k16.f32.bf16.bf16 {"
      "%0, %1, %2, %3, %4, %5, %6, %7, %8, %9, %10, %11, %12, %13, %14, %15, %16, %17, %18, %19, %20, %21, %22, %23, "
      "%24, %25, %26, %27, %28, %29, %30, %31"
      "}, {%32, %33, %34, %35}, %36, p, %38, 1, %39;\n}\n"
      : "+f"(d[0]), "+f"(d[1]), "+f"(d[2]), "+f"(d[3]), "+f"(d[4]), "+f"(d[5]), "+f"(d[6]), "+f"(d[7]), "+f"(d[8]),
        "+f"(d[9]), "+f"(d[10]), "+f"(d[11]), "+f"(d[12]), "+f"(d[13]), "+f"(d[14]), "+f"(d[15]), "+f"(d[16]),
        "+f"(d[17]), "+f"(d[18]), "+f"(d[19]), "+f"(d[20]), "+f"(d[21]), "+f"(d[22]), "+f"(d[23]), "+f"(d[24]),
        "+f"(d[25]), "+f"(d[26]), "+f"(d[27]), "+f"(d[28]), "+f"(d[29]), "+f"(d[30]), "+f"(d[31])
      : "r"(a0), "r"(a1), "r"(a2), "r"(a3), "l"(db), "r"(sd), "n"(SA), "n"(TB));
}

__device__ __forceinline__ uint32_t BAR_FULL(uint32_t sb, int i) { return sb + SM_BAR + 8 * i; }
__device__ __forceinline__ uint32_t BAR_EMPTY(uint32_t sb, int i) { return sb + SM_BAR + 64 + 8 * i; }
__device__ __forceinline__ uint32_t BAR_X(uint32_t sb, int i) { return sb + SM_BAR + 128 + 8 * i; }
__device__ __forceinline__ uint32_t BAR_Y(uint32_t sb, int i) { return sb + SM_BAR + 192 + 8 * i; }
__device__ __forceinline__ uint32_t BAR_XFREE(uint32_t sb) { return sb + SM_BAR + 256; }

#define CMASK 0x194u
#define XORDER 0, 1, 11, 2, 3, 12, 13, 4, 5, 14, 6, 15, 16
#define XSPREAD 2
#define PFAT 3
#define SKEW 3
constexpr int Q_G1B = 18, Q_G2 = 32, Q_P3 = 46, Q_END = 50;

struct Ring {
  uint32_t slot, phase;
  __device__ __forceinline__ void next() { if (++slot == NSTAGE) { slot = 0; phase ^= 1; } }
};

__device__ __forceinline__ void release_slot(uint32_t sb, uint32_t slot, int tid, int times) {
  if (tid < 2 * times) mbar_arrive_cluster(BAR_EMPTY(sb, slot), tid & 1);
}

__device__ __forceinline__ void ffn_consumer(uint32_t sb, const uint8_t* smem, const Params& p, int bid, int wg, int tid, int mt, int jj) {
  const int lane = tid & 31, warp = tid >> 5, q = lane & 3, r0 = 16 * warp + (lane >> 2);
  uint32_t* const my_epoch = &p.s->epoch[blockIdx.x * 12 + (threadIdx.x >> 5)];
  const uint32_t epoch = ld_relaxed(my_epoch) + 1;
  Ring rg{0, 0};
  uint32_t u[64];
  float acc[128];
  uint32_t prev = 0, cmask = CMASK;
  int st = 0;
  auto g1_stage = [&](uint32_t slot, int s) {
    const uint64_t da = mk_desc(sb + SM_X + (s >> 1) * 16384 + wg * 8192 + (s & 1) * 64, 16, 1024, 1);
    const uint64_t db = mk_desc(sb + SM_RING + slot * STAGE_BYTES, 4096, 1024, 1);
    wg_fence();
    wgmma_ss_n256<0, 1>(acc, da, db, s != 0);
    wgmma_ss_n256<0, 1>(acc, da + 2, db + 128, 1);
    wg_commit();
  };
  if (wg == 1) {
    float ap[64];
    constexpr int QX = 32 - __builtin_clz(CMASK);
    constexpr int NPRE = QX + XSPREAD;
    uint4* const x1dst = reinterpret_cast<uint4*>(p.s->x1t + (size_t)(64 * jj + r0 + 8) * S_ + 128 * mt + 8 * q);
    const int x1lo = 64 * jj + r0 == 1 ? (D_ - 9) * (S_ / 8) : -S_;
#pragma unroll
    for (int qi = 0; qi < NPRE; qi++) {
      const int slot = qi % NSTAGE, nc = __builtin_popcount(CMASK & ((1u << qi) - 1));
      if (qi == 0) TL(60);
      mbar_wait(BAR_FULL(sb, slot), (qi / NSTAGE) & 1);
      if (qi == 0) TL(61);
      if ((CMASK >> qi) & 1) {
#pragma unroll
        for (int kb = 2 * nc; kb < 2 * nc + 2 && kb < 7; kb++) {
          const uint64_t da = mk_desc(sb + SM_RING + slot * STAGE_BYTES + (kb & 1) * 8192, 8192, 1024, 1);
          const uint64_t db = mk_desc(sb + SM_X + kb * 16384, 16, 1024, 1);
          mbar_wait(BAR_X(sb, kb), 0);
          TL(16 + kb);
          wg_fence();
#pragma unroll
          for (int kk = 0; kk < 4; kk++) wgmma_ss_n128<1, 0>(ap, da + kk * 128, db + kk * 2, (kb | kk) != 0);
          wg_commit();
        }
      } else {
        if (((qi - nc) & 1) == 0 && qi - nc >= 4 * nc) mbar_wait(BAR_X(sb, (qi - nc) >> 1), 0);
        TL(32 + qi - nc);
        g1_stage(slot, qi - nc);
      }
      if (qi > 0) {
        wg_wait<1>();
        release_slot(sb, (qi - 1) % NSTAGE, tid, ((CMASK >> (qi - 1)) & 1) ? 2 : 1);
      }
      if (qi >= QX) {
        if (qi == QX) { fence_regs(ap); TL(2); }
#pragma unroll
        for (int t = (qi - QX) * (4 / XSPREAD); t < (qi - QX + 1) * (4 / XSPREAD); t++)
#pragma unroll
        for (int h = 0; h < 2; h++)
          x1dst[(h ? 0 : x1lo) + 4 * t] = make_uint4(pack2(ap[16 * t + 2 * h], ap[16 * t + 2 * h + 1]), pack2(ap[16 * t + 4 + 2 * h], ap[16 * t + 5 + 2 * h]),
                                             pack2(ap[16 * t + 8 + 2 * h], ap[16 * t + 9 + 2 * h]), pack2(ap[16 * t + 12 + 2 * h], ap[16 * t + 13 + 2 * h]));
      }
    }
    bar_arrive(7, 160);
    st = NPRE - 4; cmask = 0; prev = (NPRE - 1) % NSTAGE;
    rg.slot = NPRE % NSTAGE; rg.phase = (NPRE / NSTAGE) & 1;
  }
#pragma unroll 1
  for (int pass = 0; pass < 2; pass++) {
#pragma unroll 1
    for (; st < 14; st++) {
      while (cmask & 1) { cmask >>= 1; rg.next(); }
      cmask >>= 1;
      if (pass == 0 && (st & 1) == 0) mbar_wait(BAR_X(sb, st >> 1), 0);
      if (st == 14 - SKEW && wg == 1) bar_sync(9 + pass, 256);
      mbar_wait(BAR_FULL(sb, rg.slot), rg.phase);
      TL(32 + 14 * pass + st);
      g1_stage(rg.slot, st);
      wg_wait<1>();
      if (st > 0) release_slot(sb, prev, tid, 1);
      prev = rg.slot;
      rg.next();
    }
    st = 0;
    if (wg == 0) bar_arrive(9 + pass, 256);
    wg_wait<0>();
    fence_regs(acc);
    release_slot(sb, prev, tid, 1);
    if (pass == 1 && tid == 0) mbar_arrive(BAR_XFREE(sb));
    TL(3 + 2 * pass);
#pragma unroll
    for (int i = 0; i < 32; i++) {
      const float g0 = 0.5f * acc[2 * i], g1 = 0.5f * acc[2 * i + 1];
      const float s0 = fmaf(g0, tanh_fast(g0), g0), s1 = fmaf(g1, tanh_fast(g1), g1);
      u[32 + i] = pack2(s0 * acc[64 + 2 * i], s1 * acc[64 + 2 * i + 1]);
    }
    if (pass == 0) {
#pragma unroll
      for (int i = 0; i < 32; i++) u[i] = u[32 + i];
    }
    TL(4 + 2 * pass);
  }
  fence_regs(u);
  float accA[32], accB[32];
  rg.slot = Q_G2 % NSTAGE; rg.phase = (Q_G2 / NSTAGE) & 1;
  auto stage = [&](float (&acc)[32], int st) {
    mbar_wait(BAR_FULL(sb, rg.slot), rg.phase);
    const uint64_t db = mk_desc(sb + SM_RING + rg.slot * STAGE_BYTES, 8192, 1024, 1);
    wg_fence();
#pragma unroll
    for (int kk = 0; kk < 8; kk++) {
      const uint32_t* a = u + 32 * st + 4 * kk;
      wgmma_rs_n64<1, 1>(acc, a[0], a[1], a[2], a[3], db + kk * 128, (st | kk) != 0);
    }
    wg_commit();
  };
  auto retire = [&](bool rel) {
    wg_wait<1>();
    if (rel) release_slot(sb, prev, tid, 1);
    prev = rg.slot;
    rg.next();
  };
  const uint32_t par = epoch & 1;
  auto put = [&](float (&acc)[32], int c) {
    fence_regs(acc);
    int o = jj + 1 + c;
    if (o >= 7) o -= 7;
    uint4* dst = p.s->part + ((((mt * 7 + o) * 6 + c) * 2 + wg) * 4) * 128 + tid;
#pragma unroll
    for (int v = 0; v < 4; v++) {
      const float* a = acc + 8 * v;
      st_relaxed(dst + v * 128, make_uint4((pack2(a[0], a[1]) & ~1u) | par, pack2(a[2], a[3]), pack2(a[4], a[5]), pack2(a[6], a[7])));
    }
  };
  const uint4* const src = p.s->part + (((mt * 7 + jj) * 6 * 2 + wg) * 4) * 128 + tid;
  auto gload = [&](uint4 (&pv)[8], int c) {
#pragma unroll
    for (int i = 0; i < 8; i++) pv[i] = ld_relaxed(src + ((2 * c + (i >> 2)) * 8 + (i & 3)) * 128);
  };
  auto gsum = [&](uint4 (&pv)[8], int c) {
    for (uint32_t n = 0; n < SPIN_LIMIT; n++) {
      uint32_t bad = 0;
#pragma unroll
      for (int i = 0; i < 8; i++) bad |= pv[i].x ^ par;
      if (!__any_sync(0xffffffffu, bad & 1)) break;
      gload(pv, c);
    }
    TL(24 + c);
#pragma unroll
    for (int i = 0; i < 8; i++) {
      const float t[8] = {bf_lo(pv[i].x), bf_hi(pv[i].x), bf_lo(pv[i].y), bf_hi(pv[i].y), bf_lo(pv[i].z), bf_hi(pv[i].z), bf_lo(pv[i].w), bf_hi(pv[i].w)};
#pragma unroll
      for (int k = 0; k < 8; k++) accA[8 * (i & 3) + k] += t[k];
    }
  };
#pragma unroll
  for (int c2 = 0; c2 < 4; c2++) {
    stage(accA, 0);
    retire(c2 == 1 || c2 == 2);
    stage(accA, 1);
    if (c2 > 0) put(accB, 2 * c2 - 1);
    TL(7 + c2);
    if (c2 == 3) break;
    retire(true);
    stage(accB, 0);
    retire(true);
    stage(accB, 1);
    put(accA, 2 * c2);
    retire(true);
  }
  rg.next();
  wg_wait<0>();
  fence_regs(accA);
  uint4 pv0[8], pv1[8], pv2[8];
  const int row = 128 * mt + 64 * wg + r0;
  uint32_t gt0 = ld_relaxed(&p.s->gate[row]), gt1 = ld_relaxed(&p.s->gate[row + 8]);
  gload(pv0, 0);
  gload(pv1, 1);
  TL(15);
#pragma unroll 1
  for (int kb = 0; kb < 7; kb++) {
    if ((kb & 1) == 0) mbar_wait(BAR_FULL(sb, rg.slot), rg.phase);
    mbar_wait(BAR_Y(sb, kb), 0);
    const uint64_t da = mk_desc(sb + SM_X + kb * 16384 + wg * 8192, 8192, 1024, 1);
    const uint64_t db = mk_desc(sb + SM_RING + rg.slot * STAGE_BYTES + (kb & 1) * 8192, 16, 1024, 1);
    wg_fence();
#pragma unroll
    for (int kk = 0; kk < 4; kk++) wgmma_ss_n64<1, 0>(accB, da + kk * 128, db + kk * 2, (kb | kk) != 0);
    wg_commit();
    if (kb & 1) rg.next();
  }
  TL(11);
  gload(pv2, 2);
  gsum(pv0, 0);
  gsum(pv1, 1);
  for (uint32_t n = 0; (((gt0 ^ epoch) | (gt1 ^ epoch)) & 0xffffu) && n < SPIN_LIMIT; n++) {
    gt0 = ld_relaxed(&p.s->gate[row]); gt1 = ld_relaxed(&p.s->gate[row + 8]);
  }
  gsum(pv2, 2);
  const float ga0 = bf_hi(gt0), ga1 = bf_hi(gt1);
  TL(12);
  wg_wait<0>();
  fence_regs(accB);
  TL(13);
  const float gb0 = bf_round(1.f - ga0), gb1 = bf_round(1.f - ga1);
  const float gs0 = ga0 * (2.f / (float)(S_ * D_)), gs1 = ga1 * (2.f / (float)(S_ * D_));
  uint4* const o = reinterpret_cast<uint4*>(p.out + (size_t)row * D_ + 64 * jj + 8 * q);
#pragma unroll
  for (int h = 0; h < 2; h++) {
    const float gs = h ? gs1 : gs0, gb = h ? gb1 : gb0;
#pragma unroll
    for (int k = 0; k < 2; k++) {
      uint32_t w[4];
#pragma unroll
      for (int j = 0; j < 4; j++) {
        const int i = 16 * k + 4 * j + 2 * h;
        w[j] = pack2(fmaf(gs, accB[i], gb * accA[i]), fmaf(gs, accB[i + 1], gb * accA[i + 1]));
      }
      const bool o1 = q & 1, o2 = q & 2;
      uint32_t a = __shfl_xor_sync(0xffffffffu, o1 ? w[0] : w[1], 1), b = __shfl_xor_sync(0xffffffffu, o1 ? w[2] : w[3], 1);
      if (o1) { w[0] = a; w[2] = b; } else { w[1] = a; w[3] = b; }
      a = __shfl_xor_sync(0xffffffffu, o2 ? w[0] : w[2], 2); b = __shfl_xor_sync(0xffffffffu, o2 ? w[1] : w[3], 2);
      if (o2) { w[0] = a; w[1] = b; } else { w[2] = a; w[3] = b; }
      o[h * D_ + 4 * k] = make_uint4(w[0], w[1], w[2], w[3]);
    }
  }
  if (lane == 0) *my_epoch = epoch;
  TL(14);
}

__device__ __forceinline__ void ring_issue(uint32_t sb, const Params& p, int qi, uint32_t slot, bool wait, uint32_t phase, int jj, uint32_t rank) {
  const CUtensorMap* m;
  int c0, c1, c2 = 0;
  bool half = false, is3d = false;
  if (qi < Q_G2) {
    const int nc = __popc(CMASK & ((1u << qi) - 1));
    if ((CMASK >> qi) & 1) {
      m = &p.ct; c0 = 64 * jj; c1 = 128 * nc + 64 * rank; half = nc == 3;
    } else {
      const int pass = qi >= Q_G1B;
      m = rank ? &p.wu : &p.wg; c0 = 0; c1 = 32 * (qi - nc - 14 * pass); c2 = 4 * jj + 2 * pass; is3d = true;
    }
  } else if (qi < Q_P3) {
    int o = jj + 1 + ((qi - Q_G2) >> 1);
    if (o >= 7) o -= 7;
    m = &p.wd; c0 = 64 * o; c1 = 256 * jj + 128 * (qi & 1) + 64 * rank;
  } else {
    m = &p.ct; c0 = 128 * (qi - Q_P3) + 64 * rank; c1 = 64 * jj; half = qi == Q_END - 1;
  }
  const uint32_t bar = BAR_FULL(sb, slot);
  const uint32_t dst = sb + SM_RING + slot * STAGE_BYTES + rank * 8192;
  if (wait) mbar_wait_cluster(BAR_EMPTY(sb, slot), phase);
  mbar_expect_tx(bar, half ? 8192 : 16384);
  if (is3d) tma3d_mc(dst, m, c0, c1, c2, bar);
  else if (!(half && rank)) tma2d_mc(dst, m, c0, c1, bar);
}

__device__ __forceinline__ void ffn_producer(uint32_t sb, const uint8_t* smem, int bid, const Params& p, int warp, int lane, int mt, int jj, uint32_t rank) {
  if (warp < 2) {
    if (lane == 0) {
      uint32_t slot = warp, phase = 0;
#pragma unroll 1
      for (int qi = NSTAGE + warp; qi < Q_END; qi += 2) {
        ring_issue(sb, p, qi, slot, true, phase, jj, rank);
        TL(10 + qi);
        slot += 2;
        if (slot >= NSTAGE) { slot -= NSTAGE; phase ^= 1; }
      }
    }
  } else {
    const int wg = warp - 2;
    if (wg == 0) {
      if (lane == 0) { prefetch_tmap(&p.wd); prefetch_tmap(&p.yt); }
      uint32_t* const my_epoch = &p.s->epoch[blockIdx.x * 12 + 10];
      const uint32_t epoch = ld_relaxed(my_epoch) + 1;
      {
        const uint4* gw4 = reinterpret_cast<const uint4*>(p.gate_w);
        const uint4 ga = __ldg(gw4 + lane), gb = lane < 24 ? __ldg(gw4 + 32 + lane) : make_uint4(0, 0, 0, 0);
        if (lane < 7) mbar_wait(BAR_X(sb, lane), 0);
        __syncwarp();
        float mine = 0.f;
#pragma unroll 1
        for (int u = 0; u < 19; u++) {
          const int r = min(19 * jj + u, 127);
          const uint8_t* xr = smem + SM_X + (lane >> 3) * 16384 + r * 128 + (((lane ^ r) & 7) << 4);
          const uint4 xa = *reinterpret_cast<const uint4*>(xr);
          const uint4 xb = lane < 24 ? *reinterpret_cast<const uint4*>(xr + 65536) : make_uint4(0, 0, 0, 0);
          float s = 0.f;
          auto dot2 = [&](uint32_t a, uint32_t b) {
            const uint32_t pr = mul2(a, b);
            s += bf_lo(pr) + bf_hi(pr);
          };
          dot2(xa.x, ga.x); dot2(xa.y, ga.y); dot2(xa.z, ga.z); dot2(xa.w, ga.w);
          dot2(xb.x, gb.x); dot2(xb.y, gb.y); dot2(xb.z, gb.z); dot2(xb.w, gb.w);
#pragma unroll
          for (int o = 16; o > 0; o >>= 1) s += __shfl_xor_sync(0xffffffffu, s, o);
          if (lane == u) mine = s;
        }
        if (lane < 19 && 19 * jj + lane < 128)
          st_relaxed(&p.s->gate[128 * mt + 19 * jj + lane], pack2(0.f, 1.f / (1.f + __expf(-bf_round(mine)))) | (epoch & 0xffffu));
      }
      TL(9);
      mbar_wait(BAR_XFREE(sb), 0);
      TL(3);
      bool todo = lane < 7;
      uint32_t n = 0;
      while (__any_sync(0xffffffffu, todo)) {
        if (todo) {
          uint32_t v;
          asm volatile("ld.acquire.gpu.global.u32 %0, [%1];" : "=r"(v) : "l"(&p.s->cnt_y[lane * 32]) : "memory");
          if ((int32_t)(v - epoch * (lane ? 16 : 17)) >= 0 || ++n > SPIN_LIMIT) {
            fence_async();
            mbar_expect_tx(BAR_Y(sb, lane), 16384);
            tma3d(sb + SM_X + lane * 16384, &p.yt, 0, 64 * lane, 2 * mt, BAR_Y(sb, lane));
            todo = false;
          }
        }
      }
      TL(4);
      if (lane == 0) *my_epoch = epoch;
    } else {
      mbar_wait(BAR_X(sb, PFAT), 0);
      if (lane < 6) {
        int row = 176 + 3 * bid + (lane >> 1);
        if (row >= D_) row -= D_;
        l2_prefetch(((lane & 1) ? p.pwu : p.pwg) + row * F_, F_ * 2);
      }
      TL(2);
      bar_sync(7, 160);
      if (lane == 0) { fence_gpu(); red_add(&p.s->cnt_x1[jj * 32], 1); l2_prefetch(p.pwd + bid * 16 * D_, 32 * D_); }
      TL(3);
    }
  }
}

__device__ __forceinline__ void spectral_cta(uint32_t sb, uint8_t* smem, const Params& p, int sc, int wg) {
  const int t384 = threadIdx.x, lane = t384 & 31, warp12 = t384 >> 5, tid = t384 & 127;
  const int warp = tid >> 5, q = lane & 3;
  const int sl0 = 6 * sc + min(sc, 8), nsl = sc < 8 ? 7 : 6;
  if (t384 == 320) {
#pragma unroll 1
    for (int i = 0; i < nsl; i++) {
      mbar_expect_tx(BAR_X(sb, i), 2 * SLAB_BYTES);
      const int row = 128 * ((sl0 + i) >> 3) + 8 * ((sl0 + i) & 7);
      const uint32_t dst = sb + SP_Z + 2 * i * SLAB_BYTES;
      bulk_g2s(dst, p.w_r + row * DF_, SLAB_BYTES / 2, BAR_X(sb, i));
      bulk_g2s(dst + SLAB_BYTES / 2, p.w_r + (row + 64) * DF_, SLAB_BYTES / 2, BAR_X(sb, i));
      bulk_g2s(dst + SLAB_BYTES, p.w_i + row * DF_, SLAB_BYTES / 2, BAR_X(sb, i));
      bulk_g2s(dst + 3 * SLAB_BYTES / 2, p.w_i + (row + 64) * DF_, SLAB_BYTES / 2, BAR_X(sb, i));
    }
    if (sc < 19) {
      mbar_expect_tx(BAR_Y(sb, 6), 24576);
      bulk_g2s(sb + SP_TW, p.spec, 24576, BAR_Y(sb, 6));
      prefetch_tmap(&p.x1);
    }
  }
  uint32_t* const my_epoch = &p.s->epoch[blockIdx.x * 12 + warp12];
  const uint32_t epoch = ld_relaxed(my_epoch) + 1;
  uint32_t fe[16], tw[16];
#pragma unroll
  for (int i = 0; i < 4; i++) {
    const uint4 a = __ldg(reinterpret_cast<const uint4*>(p.spec->fe) + i * 128 + tid);
    const uint4 b = __ldg(reinterpret_cast<const uint4*>(p.spec->tw) + i * 128 + tid);
    fe[4 * i] = a.x; fe[4 * i + 1] = a.y; fe[4 * i + 2] = a.z; fe[4 * i + 3] = a.w;
    tw[4 * i] = b.x; tw[4 * i + 1] = b.y; tw[4 * i + 2] = b.z; tw[4 * i + 3] = b.w;
  }
  __syncwarp();
  asm volatile("barrier.cluster.wait.acquire.aligned;" ::: "memory");
#pragma unroll 2
  for (int un = wg; un < 8 * nsl; un += 3) {
    const int i = un >> 3, sl = sl0 + i, pr = 16 * (un & 7) + 4 * (lane >> 3) + warp, r = lane & 7;
    mbar_wait(BAR_X(sb, i), 0);
    if (pr < 113) {
      const uint16_t* w = reinterpret_cast<const uint16_t*>(smem + SP_Z + 2 * i * SLAB_BYTES) + r * DF_ + 2 * pr;
      const uint32_t m = pr < 112 ? 0xffffffffu : 0u;
      p.s->wt[pr * 1024 + sl * 8 + (r ^ ((sl >> 2) & 6))] =
          make_uint4(w[0] | ((uint32_t)w[8 * DF_] << 16), w[16 * DF_] | ((uint32_t)w[24 * DF_] << 16),
                     (w[1] | ((uint32_t)w[8 * DF_ + 1] << 16)) & m, (w[16 * DF_ + 1] | ((uint32_t)w[24 * DF_ + 1] << 16)) & m);
    }
  }
  __syncthreads();
  if (t384 == 352) { fence_gpu(); red_add(&p.s->cnt_w[0], 1); }
  TL(1);
  if (sc == 19) return;
  const int nrnd = (sc == 18 && wg == 2) ? 1 : 2;
  if (tid == 32) {
    wait_counter(&p.s->cnt_w[0], epoch * NSPEC);
    fence_async();
    for (int rnd = 0; rnd < nrnd; rnd++) {
      const int item = wg + 3 * rnd;
      mbar_expect_tx(BAR_Y(sb, item), 16384);
      bulk_g2s(sb + SP_W + item * 16384, p.s->wt + (6 * sc + item) * 1024, 16384, BAR_Y(sb, item));
    }
  } else if (tid == 0) {
#pragma unroll 1
    for (int rnd = 0; rnd < nrnd; rnd++) {
      const int item = wg + 3 * rnd, pr = 6 * sc + item;
      wait_counter(&p.s->cnt_x1[(pr < 112 ? pr >> 4 : 0) * 32], epoch * 16);
      fence_async();
      const uint32_t bar = BAR_FULL(sb, item), z = sb + SP_Z + item * 16384;
      mbar_expect_tx(bar, 16384);
      tma4d(z, &p.x1, 4 * pr, bar);
    }
  }
  __syncwarp();
  fence_regs(fe); fence_regs(tw);
  mbar_wait(BAR_Y(sb, 6), 0);
  TL(3);
  const uint64_t dT_n = mk_desc(sb + SP_T, 8192, 1024, 1);
#pragma unroll 1
  for (int rnd = 0; rnd < nrnd; rnd++) {
    const int item = wg + 3 * rnd, pr = 6 * sc + item;
    const uint32_t z = sb + SP_Z + item * 16384;
    uint32_t fa[16], fb[16];
    auto load_frag = [&](int off) {
#pragma unroll
      for (int i = 0; i < 4; i++) {
        const uint4 a = *reinterpret_cast<const uint4*>(smem + SP_TW + off + i * 2048 + tid * 16);
        fa[4 * i] = a.x; fa[4 * i + 1] = a.y; fa[4 * i + 2] = a.z; fa[4 * i + 3] = a.w;
      }
      fence_regs(fa);
    };
    load_frag(0);
    mbar_wait(BAR_FULL(sb, item), 0);
    TL(4 + 8 * rnd);
    if (rnd == 0 && wg > 0) bar_sync(3 + wg, 256);
    float aR[32], aI[32];
    {
      const uint64_t de = mk_desc(z, 4096, 512, 2);
      wg_fence();
#pragma unroll
      for (int kk = 0; kk < 4; kk++) {
        wgmma_rs_n64<1, 1>(aR, fe[4 * kk], fe[4 * kk + 1], fe[4 * kk + 2], fe[4 * kk + 3], de + kk * 64, kk != 0);
        wgmma_rs_n64<1, 1>(aI, fa[4 * kk], fa[4 * kk + 1], fa[4 * kk + 2], fa[4 * kk + 3], de + 512 + kk * 64, kk != 0);
      }
      wg_commit();
      if (rnd == 0 && wg < 2) bar_arrive(4 + wg, 256);
      wg_wait<0>();
      fence_regs(aR); fence_regs(aI);
    }
    TL(5 + 8 * rnd);
#pragma unroll
    for (int v = 0; v < 8; v++) {
      uint32_t* f = (v < 4 ? fa : fb) + 2 * (v & 3);
      const uint32_t* t = tw + 2 * (v & 3);
      const float *e = aR + 4 * v, *o = aI + 4 * v;
      const uint32_t er = pack2(e[0], e[1]), ei = pack2(e[2], e[3]), qr = pack2(o[0], o[1]), qi = pack2(o[2], o[3]);
      const uint32_t u0r = add2(er, qr), u0i = add2(ei, qi), u1r = sub2(er, qr), u1i = sub2(ei, qi);
      f[0] = fma2(u0r, t[0], mul2(u0i, t[8]));
      f[8] = fms2(u0i, t[0], mul2(u0r, t[8]));
      f[1] = fma2(u1r, t[1], mul2(u1i, t[9]));
      f[9] = fms2(u1i, t[1], mul2(u1r, t[9]));
    }
    fence_regs(fa); fence_regs(fb);
    wg_fence();
#pragma unroll
    for (int kk = 0; kk < 4; kk++) {
      wgmma_rs_n64<1, 1>(aR, fa[4 * kk], fa[4 * kk + 1], fa[4 * kk + 2], fa[4 * kk + 3], dT_n + kk * 128, kk != 0);
      wgmma_rs_n64<1, 1>(aI, fb[4 * kk], fb[4 * kk + 1], fb[4 * kk + 2], fb[4 * kk + 3], dT_n + kk * 128, kk != 0);
    }
    wg_commit();
    mbar_wait(BAR_Y(sb, item), 0);
    wg_wait<0>();
    fence_regs(aR); fence_regs(aI);
    TL(6 + 8 * rnd);
    {
      const uint8_t* wp = smem + SP_W + item * 16384 + q * 1024 + warp * 128 + (((lane >> 2) ^ (2 * q)) << 4);
#pragma unroll
      for (int jb = 0; jb < 4; jb++) {
#pragma unroll
        for (int h = 0; h < 2; h++) {
          const uint4 w = *reinterpret_cast<const uint4*>(wp + jb * 4096 + h * 512);
          const int i = 4 * jb + 2 * h;
          const uint32_t ar = pack2(aR[i], aR[i + 1]), ai = pack2(aR[16 + i], aR[17 + i]);
          const uint32_t br = pack2(aI[i], aI[i + 1]), bi = pack2(aI[16 + i], aI[17 + i]);
          fa[2 * jb + h] = fms2(ar, w.x, mul2(ai, w.y));
          fa[8 + 2 * jb + h] = fma2(ar, w.y, mul2(ai, w.x));
          fb[2 * jb + h] = fms2(br, w.z, mul2(bi, w.w));
          fb[8 + 2 * jb + h] = fma2(br, w.w, mul2(bi, w.z));
        }
      }
    }
    fence_regs(fa); fence_regs(fb);
    wg_fence();
#pragma unroll
    for (int kk = 0; kk < 4; kk++) {
      wgmma_rs_n64<1, 0>(aR, fa[4 * kk], fa[4 * kk + 1], fa[4 * kk + 2], fa[4 * kk + 3], dT_n + kk * 2, kk != 0);
      wgmma_rs_n64<1, 0>(aI, fb[4 * kk], fb[4 * kk + 1], fb[4 * kk + 2], fb[4 * kk + 3], dT_n + kk * 2, kk != 0);
    }
    wg_commit();
    wg_wait<0>();
    fence_regs(aR); fence_regs(aI);
    TL(7 + 8 * rnd);
#pragma unroll
    for (int v = 0; v < 8; v++) {
      const float* a = (v < 4 ? aR : aI) + 4 * (v & 3);
      const uint32_t* t = tw + 2 * (v & 3);
      const uint32_t u0r = pack2(a[0], a[1]), u1r = pack2(a[2], a[3]), u0i = pack2(a[16], a[17]), u1i = pack2(a[18], a[19]);
      const uint32_t t0r = fms2(u0r, t[0], mul2(u0i, t[8])), t0i = fma2(u0i, t[0], mul2(u0r, t[8]));
      const uint32_t t1r = fms2(u1r, t[1], mul2(u1i, t[9])), t1i = fma2(u1i, t[1], mul2(u1r, t[9]));
      fa[v] = add2(t0i, t1i); fa[8 + v] = add2(t0r, t1r);
      fb[v] = sub2(t0i, t1i); fb[8 + v] = sub2(t0r, t1r);
    }
    bar_sync(1 + wg, 128);
#pragma unroll
    for (int u = 0; u < 4; u++) {
      const uint32_t a = z + (32 * (u >> 1) + 8 * warp + (lane & 7)) * 128 + (((4 * (u & 1) + (lane >> 3)) ^ (lane & 7)) << 4);
      stmatrix_x4(a, fa[4 * u], fa[4 * u + 1], fa[4 * u + 2], fa[4 * u + 3]);
      stmatrix_x4(a + 8192, fb[4 * u], fb[4 * u + 1], fb[4 * u + 2], fb[4 * u + 3]);
    }
    load_frag(8192);
    fence_async_smem();
    bar_sync(1 + wg, 128);
    TL(8 + 8 * rnd);
    {
      const uint64_t de = mk_desc(z, 8192, 1024, 1);
      wg_fence();
#pragma unroll
      for (int kk = 0; kk < 4; kk++) {
        wgmma_rs_n64<1, 1>(aR, fe[4 * kk], fe[4 * kk + 1], fe[4 * kk + 2], fe[4 * kk + 3], de + kk * 128, kk != 0);
        wgmma_rs_n64<1, 1>(aI, fa[4 * kk], fa[4 * kk + 1], fa[4 * kk + 2], fa[4 * kk + 3], de + 512 + kk * 128, kk != 0);
      }
      wg_commit();
      wg_wait<0>();
      fence_regs(aR); fence_regs(aI);
    }
    TL(9 + 8 * rnd);
    const bool edge = pr == 0 || pr == 112;
    if (edge) {
#pragma unroll
      for (int i = 0; i < 16; i++) { aR[i] *= 0.5f; aI[i] *= 0.5f; }
    }
#pragma unroll
    for (int i = 0; i < 8; i++) {
      const float* a = ((i & 1) ? aI : aR) + 16 * (i >> 2) + 2 - (i & 2);
      *reinterpret_cast<uint4*>(smem + SP_W + item * 16384 + (i >> 1) * 4096 + (i & 1) * 64 + (tid >> 2) * 128 + q * 16) =
          make_uint4(pack2(a[0], a[1]), pack2(a[4], a[5]), pack2(a[8], a[9]), pack2(a[12], a[13]));
    }
    fence_async_smem();
    bar_sync(1 + wg, 128);
    if (tid == 0) {
      const uint32_t src = sb + SP_W + item * 16384;
      __nv_bfloat16* dst = p.s->yt + (size_t)(pr < 112 ? 4 * pr : 1) * S_;
      bulk_s2g(dst, src, edge ? 4096 : 16384);
      if (pr == 0) bulk_s2g(dst + 2 * S_, src + 8192, 8192);
      asm volatile("cp.async.bulk.commit_group;" ::: "memory");
      if (rnd == nrnd - 1) {
        asm volatile("cp.async.bulk.wait_group 0;" ::: "memory");
        TL(11);
        fence_async();
        fence_gpu();
        red_add(&p.s->cnt_y[(pr < 112 ? pr >> 4 : 0) * 32], 1);
        if (rnd) red_add(&p.s->cnt_y[((pr - 3) >> 4) * 32], 1);
      }
    }
    __syncwarp();
    TL(10 + 8 * rnd);
  }
  if (lane == 0) *my_epoch = epoch;
}

__global__ void __cluster_dims__(2, 1, 1) __launch_bounds__(384, 1)
fused_kernel(const __grid_constant__ Params p) {
  extern __shared__ __align__(1024) uint8_t smem[];
  const uint32_t sb = smem_u32(smem);
  TL(0);
  const uint32_t rank = blockIdx.x & 1;
  const int hc = blockIdx.x >> 1;
  int grp, jj;
  if (hc < 4) { grp = 8; jj = hc; }
  else if (hc < 36) { grp = (hc - 4) & 7; jj = (hc - 4) >> 3; }
  else if (hc < 57) { jj = (hc - 36) / 7; grp = 1 + (hc - 36) - 7 * jj; jj += 4; }
  else if (hc < 60) { grp = 0; jj = hc - 53; }
  else { grp = 8; jj = hc - 56; }
  const int mt = 2 * grp + rank, bid = 2 * (7 * grp + jj) + rank;
  if (threadIdx.x == 256) {
#pragma unroll
    for (int i = 0; i < NSTAGE; i++) { mbar_init(BAR_FULL(sb, i), 1); mbar_init(BAR_EMPTY(sb, i), 4); }
    asm volatile("fence.mbarrier_init.release.cluster;" ::: "memory");
  } else if (threadIdx.x == 320) {
#pragma unroll
    for (int i = 0; i < NSTAGE; i++) { mbar_init(BAR_X(sb, i), 1); mbar_init(BAR_Y(sb, i), 1); }
    mbar_init(BAR_XFREE(sb), 2);
    asm volatile("fence.mbarrier_init.release.cluster;" ::: "memory");
  } else if (threadIdx.x == 288) {
    prefetch_tmap(rank ? &p.wu : &p.wg); prefetch_tmap(&p.ct);
  }
  __syncwarp();
  asm volatile("barrier.cluster.arrive.relaxed.aligned;" ::: "memory");
  const int wg = __shfl_sync(0xffffffffu, threadIdx.x >> 7, 0);
  if (bid >= NFFN) {
    spectral_cta(sb, smem, p, bid - NFFN, wg);
  } else if (wg < 2) {
    asm volatile("setmaxnreg.inc.sync.aligned.u32 232;");
    asm volatile("barrier.cluster.wait.acquire.aligned;" ::: "memory");
    TL(1);
    ffn_consumer(sb, smem, p, bid, wg, threadIdx.x & 127, mt, jj);
  } else {
    asm volatile("setmaxnreg.dec.sync.aligned.u32 40;");
    if (threadIdx.x == 320) {
      mbar_expect_tx(BAR_X(sb, 0), 16384);
      tma2d(sb + SM_X, &p.x, 0, 128 * mt, BAR_X(sb, 0));
    }
    __syncwarp();
    asm volatile("barrier.cluster.wait.acquire.aligned;" ::: "memory");
    TL(1);
    if (threadIdx.x == 320) {
      constexpr int order[13] = {XORDER};
#pragma unroll
      for (int i = 0; i < 13; i++) {
        if (order[i] < 8) {
          ring_issue(sb, p, order[i], order[i], false, 0, jj, rank);
        } else {
          const int kb = order[i] - 10;
          mbar_expect_tx(BAR_X(sb, kb), 16384);
          tma2d(sb + SM_X + kb * 16384, &p.x, 64 * kb, 128 * mt, BAR_X(sb, kb));
        }
      }
      TL(2);
    } else if (threadIdx.x == 352) {
    }
    __syncwarp();
    ffn_producer(sb, smem, bid, p, (threadIdx.x >> 5) & 3, threadIdx.x & 31, mt, jj, rank);
  }
}

typedef CUresult (*EncodeFn)(CUtensorMap*, CUtensorMapDataType, cuuint32_t, void*, const cuuint64_t*, const cuuint64_t*,
                             const cuuint32_t*, const cuuint32_t*, CUtensorMapInterleave, CUtensorMapSwizzle,
                             CUtensorMapL2promotion, CUtensorMapFloatOOBfill);

void make_map(EncodeFn fn, CUtensorMap* m, const void* base, int rank, const cuuint64_t* dims, const cuuint64_t* strides,
              const cuuint32_t* box, CUtensorMapSwizzle sw) {
  const cuuint32_t es[4] = {1, 1, 1, 1};
  fn(m, CU_TENSOR_MAP_DATA_TYPE_BFLOAT16, rank, const_cast<void*>(base), dims, strides, box, es,
     CU_TENSOR_MAP_INTERLEAVE_NONE, sw, CU_TENSOR_MAP_L2_PROMOTION_L2_256B, CU_TENSOR_MAP_FLOAT_OOB_FILL_NONE);
}

}

extern "C" void kernel_launch(void* const* d_in, const int* in_sizes, int n_in, void* d_out, int out_size) {
  const __nv_bfloat16* x = (const __nv_bfloat16*)d_in[0];
  const __nv_bfloat16* w_r = (const __nv_bfloat16*)d_in[1];
  const __nv_bfloat16* w_i = (const __nv_bfloat16*)d_in[2];
  const __nv_bfloat16* wg = (const __nv_bfloat16*)d_in[4];
  const __nv_bfloat16* wu = (const __nv_bfloat16*)d_in[5];
  const __nv_bfloat16* wd = (const __nv_bfloat16*)d_in[6];
  const __nv_bfloat16* gate_w = (const __nv_bfloat16*)d_in[7];

  void* fnp = nullptr;
  cudaDriverEntryPointQueryResult qr;
  cudaGetDriverEntryPoint("cuTensorMapEncodeTiled", &fnp, cudaEnableDefault, &qr);
  EncodeFn fn = (EncodeFn)fnp;
  void *ctab, *spec, *scr;
  cudaGetSymbolAddress(&ctab, g_ctab);
  cudaGetSymbolAddress(&spec, g_spec);
  cudaGetSymbolAddress(&scr, g_scratch);
  const void* x1t = (const char*)scr + offsetof(Scratch, x1t);
  const void* yt = (const char*)scr + offsetof(Scratch, yt);
  Params p;
  p.s = (Scratch*)scr; p.out = (__nv_bfloat16*)d_out;
  p.px = x; p.w_r = w_r; p.w_i = w_i; p.gate_w = gate_w; p.pwg = wg; p.pwu = wu; p.pwd = wd;
  p.ctab = (const tab::Table*)ctab; p.spec = (const tab::Spec*)spec;
  {
    const cuuint64_t d[2] = {D_, S_}, s[1] = {D_ * 2};
    const cuuint32_t b[2] = {64, 128};
    make_map(fn, &p.x, x, 2, d, s, b, CU_TENSOR_MAP_SWIZZLE_128B);
  }
  {
    const cuuint64_t d[3] = {64, D_, F_ / 64}, s[2] = {F_ * 2, 128};
    const cuuint32_t b[3] = {64, 32, 2};
    make_map(fn, &p.wg, wg, 3, d, s, b, CU_TENSOR_MAP_SWIZZLE_128B);
    make_map(fn, &p.wu, wu, 3, d, s, b, CU_TENSOR_MAP_SWIZZLE_128B);
  }
  {
    const cuuint64_t d[2] = {D_, F_}, s[1] = {D_ * 2};
    const cuuint32_t b[2] = {64, 64};
    make_map(fn, &p.wd, wd, 2, d, s, b, CU_TENSOR_MAP_SWIZZLE_128B);
  }
  {
    const cuuint64_t d[2] = {D_, D_}, s[1] = {D_ * 2};
    const cuuint32_t b[2] = {64, 64};
    make_map(fn, &p.ct, ctab, 2, d, s, b, CU_TENSOR_MAP_SWIZZLE_128B);
  }
  {
    const cuuint64_t d[4] = {32, 32, D_ + 1, 2}, s[3] = {128, S_ * 2, 64};
    const cuuint32_t b[4] = {32, 32, 4, 2};
    make_map(fn, &p.x1, x1t, 4, d, s, b, CU_TENSOR_MAP_SWIZZLE_64B);
  }
  {
    const cuuint64_t d[3] = {64, D_, S_ / 64}, s[2] = {S_ * 2, 128};
    const cuuint32_t b[3] = {64, 64, 2};
    make_map(fn, &p.yt, yt, 3, d, s, b, CU_TENSOR_MAP_SWIZZLE_128B);
  }
  cudaFuncSetAttribute(fused_kernel, cudaFuncAttributeMaxDynamicSharedMemorySize, SM_TOTAL);
  fused_kernel<<<NCTA, 384, SM_TOTAL, cudaStreamPerThread>>>(p, x, w_r, w_i, gate_w, wd, (__nv_bfloat16*)d_out);
}
```

```cpp
#include <cuda_runtime.h>
#include <cuda_bf16.h>
#include <cuda.h>
#include <stdint.h>
#include <stddef.h>

namespace {

constexpr int S_ = 2048, D_ = 448, F_ = 1792, DF_ = 225;
constexpr int NFFN = 112, NSPEC = 20, NCTA = NFFN + NSPEC;
constexpr int NSTAGE = 7, STAGE_BYTES = 16384;
constexpr int SM_X = 0, SM_RING = 114688, SM_BAR = 229376, SM_TOTAL = SM_BAR + 512;
constexpr int SP_Z = 0, SP_W = 98304, SP_TW = 198656, SP_T = 215040, SLAB_BYTES = 16 * DF_ * 2;
constexpr uint32_t SPIN_LIMIT = 1u << 20;

namespace tab {
constexpr double PI = 3.14159265358979323846264338327950288;
constexpr double csin(double x) {
  double t = x, s = x;
  for (int i = 1; i < 20; i++) { t = -t * x * x / ((2 * i) * (2 * i + 1)); s += t; }
  return s;
}
constexpr double ccos(double x) {
  double t = 1, s = 1;
  for (int i = 1; i < 20; i++) { t = -t * x * x / ((2 * i - 1) * (2 * i)); s += t; }
  return s;
}
constexpr uint32_t to_bf16(double v) {
  uint32_t sign = v < 0 ? 0x8000u : 0u;
  double a = v < 0 ? -v : v;
  if (a < 1e-12) return 0;
  int e = 0;
  while (a >= 2.0) { a /= 2; e++; }
  while (a < 1.0) { a *= 2; e--; }
  double m = a * 128.0;
  int mi = (int)m;
  double fr = m - mi;
  if (fr > 0.5 || (fr == 0.5 && (mi & 1))) mi++;
  if (mi == 256) { mi = 128; e++; }
  return sign | (uint32_t)((e + 127) << 7) | (uint32_t)(mi - 128);
}
struct Base { uint32_t v[448]; };
constexpr Base make_base() {
  Base b{};
  for (int m = 0; m < 448; m++) {
    int mm = m > 224 ? m - 448 : m;
    double ang = 2 * PI * mm / 448.0;
    b.v[m] = to_bf16(ccos(ang)) | (to_bf16(-csin(ang)) << 16);
  }
  return b;
}
constexpr Base base = make_base();
struct Row { uint32_t v[224]; };
constexpr Row make_row(int d) {
  Row r{};
  r.v[0] = 0x3f80u | ((d & 1) ? 0xbf800000u : 0x3f800000u);
  int m = 0;
  for (int c = 1; c < 224; c++) { m += d; if (m >= 448) m -= 448; r.v[c] = base.v[m]; }
  return r;
}
struct Table { Row r[448]; };
constexpr Table make_table() {
  Table t{};
  for (int d = 0; d < 448; d++) t.r[d] = make_row(d);
  return t;
}
struct Cs { double c[2048], s[2048]; };
constexpr Cs make_cs() {
  Cs t{};
  for (int m = 0; m <= 256; m++) {
    const double a = 2 * PI * m / 2048.0, c = ccos(a), s = csin(a);
    t.c[m] = c; t.s[m] = s;
    t.c[512 - m] = s; t.s[512 - m] = c;
  }
  for (int m = 513; m < 2048; m++) { t.c[m] = -t.s[m - 512]; t.s[m] = t.c[m - 512]; }
  return t;
}
constexpr Cs cs = make_cs();
struct Spec {
  uint32_t fo[2048], fot[2048];
  uint16_t t32[4096];
  uint32_t fe[2048];
  uint32_t tw[2048];
};
constexpr uint32_t blk(int h, int c, int a) { return to_bf16(h == c ? cs.c[a & 2047] : (h ? -cs.s[a & 2047] : cs.s[a & 2047])); }
constexpr Spec make_spec() {
  Spec t{};
  for (int row = 0; row < 64; row++)
    for (int col = 0; col < 64; col++) {
      const int c = row & 31, k2 = col & 31, n2 = 8 * ((c >> 1) & 3) + 2 * (c >> 3) + (c & 1), m = 64 * ((n2 * k2) & 31);
      const double v = (row >> 5) == (col >> 5) ? cs.c[m] : (row < 32 ? -cs.s[m] : cs.s[m]);
      t.t32[row * 64 + (((col >> 3) ^ (row & 7)) << 3) + (col & 7)] = (uint16_t)to_bf16(v);
    }
  for (int th = 0; th < 128; th++)
    for (int i = 0; i < 16; i++) {
      const int r = 8 * (th >> 5) + ((th & 31) >> 2), h = i & 1, c = i >> 3, m = 8 * ((i >> 1) & 3) + 2 * (th & 3);
      const int o = ((i >> 2) * 128 + th) * 4 + (i & 3);
      t.fe[o] = blk(h, c, 64 * m * r) | (blk(h, c, 64 * (m + 1) * r) << 16);
      t.fo[o] = blk(h, c, 32 * (2 * m + 1) * r) | (blk(h, c, 32 * (2 * m + 3) * r) << 16);
      t.fot[o] = blk(h, c, 32 * (2 * r + 1) * m) | (blk(h, c, 32 * (2 * r + 1) * (m + 1)) << 16);
      const int k1 = r + 32 * h, n2 = 8 * (th & 3) + 2 * ((i >> 1) & 3);
      t.tw[o] = blk(0, c, n2 * k1) | (blk(0, c, (n2 + 1) * k1) << 16);
    }
  return t;
}
}
}

__device__ __align__(1024) const tab::Table g_ctab = tab::make_table();
__device__ __align__(1024) const tab::Spec g_spec = tab::make_spec();

struct Scratch {
  uint32_t cnt_w[32];
  uint32_t cnt_x1[7 * 32];
  uint32_t cnt_y[7 * 32];
  uint32_t epoch[NCTA * 12 + 240 + 256];
  uint32_t gate[S_];
  uint4 x1t[113 * 1024];
  __nv_bfloat16 yt[D_ * S_];
  uint4 wt[114 * 1024];
  uint4 part[16 * 7 * 6 * 2 * 4 * 128];
};
static_assert(offsetof(Scratch, x1t) % 1024 == 0, "alignment");
__device__ __align__(1024) Scratch g_scratch;
#define TL(i)

namespace {

struct Params {
  Scratch* s;
  __nv_bfloat16* out;
  const __nv_bfloat16 *px, *w_r, *w_i, *gate_w, *pwg, *pwu, *pwd;
  const tab::Table* ctab;
  const tab::Spec* spec;
  CUtensorMap x, wg, wu, wd, ct, yt;
};

__device__ __forceinline__ uint32_t smem_u32(const void* p) { return (uint32_t)__cvta_generic_to_shared(p); }
__device__ __forceinline__ void mbar_init(uint32_t bar, uint32_t cnt) {
  asm volatile("mbarrier.init.shared::cta.b64 [%0], %1;" ::"r"(bar), "r"(cnt) : "memory");
}
__device__ __forceinline__ void mbar_expect_tx(uint32_t bar, uint32_t bytes) {
  asm volatile("mbarrier.arrive.expect_tx.shared::cta.b64 _, [%0], %1;" ::"r"(bar), "r"(bytes) : "memory");
}
__device__ __forceinline__ void mbar_arrive(uint32_t bar) {
  asm volatile("mbarrier.arrive.shared::cta.b64 _, [%0];" ::"r"(bar) : "memory");
}
__device__ __forceinline__ void mbar_arrive_cluster(uint32_t bar, uint32_t cta) {
  asm volatile("{\n.reg .b32 ra;\nmapa.shared::cluster.u32 ra, %0, %1;\n"
               "mbarrier.arrive.shared::cluster.b64 _, [ra];\n}" ::"r"(bar), "r"(cta) : "memory");
}
__device__ __forceinline__ void mbar_wait(uint32_t bar, uint32_t parity) {
  uint32_t ok, n = 0;
  do {
    asm volatile("{\n.reg .pred p;\nmbarrier.try_wait.parity.shared::cta.b64 p, [%1], %2;\nselp.u32 %0, 1, 0, p;\n}"
                 : "=r"(ok) : "r"(bar), "r"(parity) : "memory");
  } while (!ok && ++n < SPIN_LIMIT);
}
__device__ __forceinline__ void mbar_wait_cluster(uint32_t bar, uint32_t parity) {
  uint32_t ok, n = 0;
  do {
    asm volatile("{\n.reg .pred p;\nmbarrier.try_wait.parity.acquire.cluster.shared::cta.b64 p, [%1], %2;\nselp.u32 %0, 1, 0, p;\n}"
                 : "=r"(ok) : "r"(bar), "r"(parity) : "memory");
  } while (!ok && ++n < SPIN_LIMIT);
}
__device__ __forceinline__ void tma2d(uint32_t dst, const CUtensorMap* m, int c0, int c1, uint32_t bar) {
  asm volatile("cp.async.bulk.tensor.2d.shared::cluster.global.mbarrier::complete_tx::bytes [%0], [%1, {%3, %4}], [%2];"
               ::"r"(dst), "l"(m), "r"(bar), "r"(c0), "r"(c1) : "memory");
}
__device__ __forceinline__ void tma3d(uint32_t dst, const CUtensorMap* m, int c0, int c1, int c2, uint32_t bar) {
  asm volatile("cp.async.bulk.tensor.3d.shared::cluster.global.mbarrier::complete_tx::bytes [%0], [%1, {%3, %4, %5}], [%2];"
               ::"r"(dst), "l"(m), "r"(bar), "r"(c0), "r"(c1), "r"(c2) : "memory");
}
__device__ __forceinline__ void tma2d_mc(uint32_t dst, const CUtensorMap* m, int c0, int c1, uint32_t bar) {
  asm volatile("cp.async.bulk.tensor.2d.shared::cluster.global.mbarrier::complete_tx::bytes.multicast::cluster [%0], [%1, {%3, %4}], [%2], %5;"
               ::"r"(dst), "l"(m), "r"(bar), "r"(c0), "r"(c1), "h"((uint16_t)3) : "memory");
}
__device__ __forceinline__ void tma3d_mc(uint32_t dst, const CUtensorMap* m, int c0, int c1, int c2, uint32_t bar) {
  asm volatile("cp.async.bulk.tensor.3d.shared::cluster.global.mbarrier::complete_tx::bytes.multicast::cluster [%0], [%1, {%3, %4, %5}], [%2], %6;"
               ::"r"(dst), "l"(m), "r"(bar), "r"(c0), "r"(c1), "r"(c2), "h"((uint16_t)3) : "memory");
}
__device__ __forceinline__ void bulk_g2s(uint32_t dst, const void* src, uint32_t bytes, uint32_t bar) {
  asm volatile("cp.async.bulk.shared::cluster.global.mbarrier::complete_tx::bytes [%0], [%1], %2, [%3];"
               ::"r"(dst), "l"(src), "r"(bytes), "r"(bar) : "memory");
}
__device__ __forceinline__ void bulk_s2g(void* dst, uint32_t src, uint32_t bytes) {
  asm volatile("cp.async.bulk.global.shared::cta.bulk_group [%0], [%1], %2;" ::"l"(dst), "r"(src), "r"(bytes) : "memory");
}
__device__ __forceinline__ void prefetch_tmap(const CUtensorMap* m) {
  asm volatile("prefetch.tensormap [%0];" ::"l"(m) : "memory");
}
__device__ __forceinline__ void l2_prefetch(const void* p, uint32_t bytes) {
  asm volatile("cp.async.bulk.prefetch.L2.global [%0], %1;" ::"l"(p), "r"(bytes) : "memory");
}
__device__ __forceinline__ void wg_fence() { asm volatile("wgmma.fence.sync.aligned;" ::: "memory"); }
__device__ __forceinline__ void wg_commit() { asm volatile("wgmma.commit_group.sync.aligned;" ::: "memory"); }
template <int N> __device__ __forceinline__ void wg_wait() { asm volatile("wgmma.wait_group.sync.aligned %0;" ::"n"(N) : "memory"); }
template <int N> __device__ __forceinline__ void fence_regs(float (&d)[N]) {
#pragma unroll
  for (int i = 0; i < N; i++) asm volatile("" : "+f"(d[i])::"memory");
}
template <int N> __device__ __forceinline__ void fence_regs(uint32_t (&d)[N]) {
#pragma unroll
  for (int i = 0; i < N; i++) asm volatile("" : "+r"(d[i])::"memory");
}
__device__ __forceinline__ void bar_sync(int id, int n) { asm volatile("bar.sync %0, %1;" ::"r"(id), "r"(n) : "memory"); }
__device__ __forceinline__ void bar_arrive(int id, int n) { asm volatile("bar.arrive %0, %1;" ::"r"(id), "r"(n) : "memory"); }
__device__ __forceinline__ void fence_gpu() { asm volatile("fence.acq_rel.gpu;" ::: "memory"); }
__device__ __forceinline__ void fence_async() { asm volatile("fence.proxy.async;" ::: "memory"); }
__device__ __forceinline__ void fence_async_smem() { asm volatile("fence.proxy.async.shared::cta;" ::: "memory"); }
__device__ __forceinline__ void red_add(uint32_t* p, uint32_t v) {
  asm volatile("red.relaxed.gpu.global.add.u32 [%0], %1;" ::"l"(p), "r"(v) : "memory");
}
__device__ __forceinline__ uint32_t ld_relaxed(const uint32_t* p) {
  uint32_t v;
  asm volatile("ld.relaxed.gpu.global.u32 %0, [%1];" : "=r"(v) : "l"(p) : "memory");
  return v;
}
__device__ __forceinline__ void wait_counter(const uint32_t* p, uint32_t target) {
  uint32_t v, n = 0;
  while (true) {
    asm volatile("ld.acquire.gpu.global.u32 %0, [%1];" : "=r"(v) : "l"(p) : "memory");
    if ((int32_t)(v - target) >= 0 || ++n > SPIN_LIMIT) break;
  }
}
__device__ __forceinline__ uint4 ld_relaxed(const uint4* p) {
  uint4 v;
  asm volatile("ld.relaxed.gpu.global.v4.u32 {%0, %1, %2, %3}, [%4];" : "=r"(v.x), "=r"(v.y), "=r"(v.z), "=r"(v.w) : "l"(p) : "memory");
  return v;
}
__device__ __forceinline__ void st_relaxed(uint4* p, uint4 v) {
  asm volatile("st.relaxed.gpu.global.v4.u32 [%0], {%1, %2, %3, %4};" ::"l"(p), "r"(v.x), "r"(v.y), "r"(v.z), "r"(v.w) : "memory");
}
__device__ __forceinline__ void st_relaxed(uint32_t* p, uint32_t v) {
  asm volatile("st.relaxed.gpu.global.u32 [%0], %1;" ::"l"(p), "r"(v) : "memory");
}
__device__ __forceinline__ uint32_t pack2(float lo, float hi) {
  uint32_t r;
  asm("cvt.rn.bf16x2.f32 %0, %1, %2;" : "=r"(r) : "f"(hi), "f"(lo));
  return r;
}
__device__ __forceinline__ uint32_t mul2(uint32_t a, uint32_t b) {
  uint32_t r;
  asm("mul.rn.bf16x2 %0, %1, %2;" : "=r"(r) : "r"(a), "r"(b));
  return r;
}
__device__ __forceinline__ uint32_t fma2(uint32_t a, uint32_t b, uint32_t c) {
  uint32_t r;
  asm("fma.rn.bf16x2 %0, %1, %2, %3;" : "=r"(r) : "r"(a), "r"(b), "r"(c));
  return r;
}
__device__ __forceinline__ uint32_t add2(uint32_t a, uint32_t b) {
  uint32_t r;
  asm("add.rn.bf16x2 %0, %1, %2;" : "=r"(r) : "r"(a), "r"(b));
  return r;
}
__device__ __forceinline__ uint32_t sub2(uint32_t a, uint32_t b) {
  uint32_t r;
  asm("sub.rn.bf16x2 %0, %1, %2;" : "=r"(r) : "r"(a), "r"(b));
  return r;
}
__device__ __forceinline__ uint32_t fms2(uint32_t a, uint32_t b, uint32_t c) {
  uint32_t r;
  asm("{\n.reg .b32 n;\nneg.bf16x2 n, %3;\nfma.rn.bf16x2 %0, %1, %2, n;\n}" : "=r"(r) : "r"(a), "r"(b), "r"(c));
  return r;
}
__device__ __forceinline__ float bf_lo(uint32_t v) { return __uint_as_float(v << 16); }
__device__ __forceinline__ float bf_hi(uint32_t v) { return __uint_as_float(v & 0xffff0000u); }
__device__ __forceinline__ float bf_round(float v) { return bf_lo(pack2(v, 0.f)); }
__device__ __forceinline__ float tanh_fast(float v) {
  float r;
  asm("tanh.approx.f32 %0, %1;" : "=f"(r) : "f"(v));
  return r;
}
__device__ __forceinline__ uint64_t mk_desc(uint32_t addr, uint32_t lbo, uint32_t sbo, uint32_t mode) {
  return (uint64_t)((addr & 0x3FFFF) >> 4) | ((uint64_t)(lbo >> 4) << 16) | ((uint64_t)(sbo >> 4) << 32) | ((uint64_t)mode << 62);
}
__device__ __forceinline__ void stmatrix_x4(uint32_t addr, uint32_t r0, uint32_t r1, uint32_t r2, uint32_t r3) {
  asm volatile("stmatrix.sync.aligned.m8n8.x4.shared.b16 [%0], {%1, %2, %3, %4};" ::"r"(addr), "r"(r0), "r"(r1), "r"(r2), "r"(r3) : "memory");
}

template <int TA, int TB>
__device__ __forceinline__ void wgmma_ss_n256(float (&d)[128], uint64_t da, uint64_t db, int sd) {
  asm volatile("{\n.reg .pred p;\nsetp.ne.b32 p, %130, 0;\n"
      "wgmma.mma_async.sync.aligned.m64n256k16.f32.bf16.bf16 {"
      "%0, %1, %2, %3, %4, %5, %6, %7, %8, %9, %10, %11, %12, %13, %14, %15, %16, %17, %18, %19, %20, %21, %22, %23, "
      "%24, %25, %26, %27, %28, %29, %30, %31, %32, %33, %34, %35, %36, %37, %38, %39, %40, %41, %42, %43, %44, %45, "
      "%46, %47, %48, %49, %50, %51, %52, %53, %54, %55, %56, %57, %58, %59, %60, %61, %62, %63, %64, %65, %66, %67, "
      "%68, %69, %70, %71, %72, %73, %74, %75, %76, %77, %78, %79, %80, %81, %82, %83, %84, %85, %86, %87, %88, %89, "
      "%90, %91, %92, %93, %94, %95, %96, %97, %98, %99, %100, %101, %102, %103, %104, %105, %106, %107, %108, %109, "
      "%110, %111, %112, %113, %114, %115, %116, %117, %118, %119, %120, %121, %122, %123, %124, %125, %126, %127"
      "}, %128, %129, p, 1, 1, %131, %132;\n}\n"
      : "+f"(d[0]), "+f"(d[1]), "+f"(d[2]), "+f"(d[3]), "+f"(d[4]), "+f"(d[5]), "+f"(d[6]), "+f"(d[7]), "+f"(d[8]),
        "+f"(d[9]), "+f"(d[10]), "+f"(d[11]), "+f"(d[12]), "+f"(d[13]), "+f"(d[14]), "+f"(d[15]), "+f"(d[16]),
        "+f"(d[17]), "+f"(d[18]), "+f"(d[19]), "+f"(d[20]), "+f"(d[21]), "+f"(d[22]), "+f"(d[23]), "+f"(d[24]),
        "+f"(d[25]), "+f"(d[26]), "+f"(d[27]), "+f"(d[28]), "+f"(d[29]), "+f"(d[30]), "+f"(d[31]), "+f"(d[32]),
        "+f"(d[33]), "+f"(d[34]), "+f"(d[35]), "+f"(d[36]), "+f"(d[37]), "+f"(d[38]), "+f"(d[39]), "+f"(d[40]),
        "+f"(d[41]), "+f"(d[42]), "+f"(d[43]), "+f"(d[44]), "+f"(d[45]), "+f"(d[46]), "+f"(d[47]), "+f"(d[48]),
        "+f"(d[49]), "+f"(d[50]), "+f"(d[51]), "+f"(d[52]), "+f"(d[53]), "+f"(d[54]), "+f"(d[55]), "+f"(d[56]),
        "+f"(d[57]), "+f"(d[58]), "+f"(d[59]), "+f"(d[60]), "+f"(d[61]), "+f"(d[62]), "+f"(d[63]), "+f"(d[64]),
        "+f"(d[65]), "+f"(d[66]), "+f"(d[67]), "+f"(d[68]), "+f"(d[69]), "+f"(d[70]), "+f"(d[71]), "+f"(d[72]),
        "+f"(d[73]), "+f"(d[74]), "+f"(d[75]), "+f"(d[76]), "+f"(d[77]), "+f"(d[78]), "+f"(d[79]), "+f"(d[80]),
        "+f"(d[81]), "+f"(d[82]), "+f"(d[83]), "+f"(d[84]), "+f"(d[85]), "+f"(d[86]), "+f"(d[87]), "+f"(d[88]),
        "+f"(d[89]), "+f"(d[90]), "+f"(d[91]), "+f"(d[92]), "+f"(d[93]), "+f"(d[94]), "+f"(d[95]), "+f"(d[96]),
        "+f"(d[97]), "+f"(d[98]), "+f"(d[99]), "+f"(d[100]), "+f"(d[101]), "+f"(d[102]), "+f"(d[103]), "+f"(d[104]),
        "+f"(d[105]), "+f"(d[106]), "+f"(d[107]), "+f"(d[108]), "+f"(d[109]), "+f"(d[110]), "+f"(d[111]),
        "+f"(d[112]), "+f"(d[113]), "+f"(d[114]), "+f"(d[115]), "+f"(d[116]), "+f"(d[117]), "+f"(d[118]),
        "+f"(d[119]), "+f"(d[120]), "+f"(d[121]), "+f"(d[122]), "+f"(d[123]), "+f"(d[124]), "+f"(d[125]),
        "+f"(d[126]), "+f"(d[127])
      : "l"(da), "l"(db), "r"(sd), "n"(TA), "n"(TB));
}
template <int TA, int TB>
__device__ __forceinline__ void wgmma_ss_n128(float (&d)[64], uint64_t da, uint64_t db, int sd) {
  asm volatile("{\n.reg .pred p;\nsetp.ne.b32 p, %66, 0;\n"
      "wgmma.mma_async.sync.aligned.m64n128k16.f32.bf16.bf16 {"
      "%0, %1, %2, %3, %4, %5, %6, %7, %8, %9, %10, %11, %12, %13, %14, %15, %16, %17, %18, %19, %20, %21, %22, %23, "
      "%24, %25, %26, %27, %28, %29, %30, %31, %32, %33, %34, %35, %36, %37, %38, %39, %40, %41, %42, %43, %44, %45, "
      "%46, %47, %48, %49, %50, %51, %52, %53, %54, %55, %56, %57, %58, %59, %60, %61, %62, %63"
      "}, %64, %65, p, 1, 1, %67, %68;\n}\n"
      : "+f"(d[0]), "+f"(d[1]), "+f"(d[2]), "+f"(d[3]), "+f"(d[4]), "+f"(d[5]), "+f"(d[6]), "+f"(d[7]), "+f"(d[8]),
        "+f"(d[9]), "+f"(d[10]), "+f"(d[11]), "+f"(d[12]), "+f"(d[13]), "+f"(d[14]), "+f"(d[15]), "+f"(d[16]),
        "+f"(d[17]), "+f"(d[18]), "+f"(d[19]), "+f"(d[20]), "+f"(d[21]), "+f"(d[22]), "+f"(d[23]), "+f"(d[24]),
        "+f"(d[25]), "+f"(d[26]), "+f"(d[27]), "+f"(d[28]), "+f"(d[29]), "+f"(d[30]), "+f"(d[31]), "+f"(d[32]),
        "+f"(d[33]), "+f"(d[34]), "+f"(d[35]), "+f"(d[36]), "+f"(d[37]), "+f"(d[38]), "+f"(d[39]), "+f"(d[40]),
        "+f"(d[41]), "+f"(d[42]), "+f"(d[43]), "+f"(d[44]), "+f"(d[45]), "+f"(d[46]), "+f"(d[47]), "+f"(d[48]),
        "+f"(d[49]), "+f"(d[50]), "+f"(d[51]), "+f"(d[52]), "+f"(d[53]), "+f"(d[54]), "+f"(d[55]), "+f"(d[56]),
        "+f"(d[57]), "+f"(d[58]), "+f"(d[59]), "+f"(d[60]), "+f"(d[61]), "+f"(d[62]), "+f"(d[63])
      : "l"(da), "l"(db), "r"(sd), "n"(TA), "n"(TB));
}
template <int TA, int TB>
__device__ __forceinline__ void wgmma_ss_n64(float (&d)[32], uint64_t da, uint64_t db, int sd) {
  asm volatile("{\n.reg .pred p;\nsetp.ne.b32 p, %34, 0;\n"
      "wgmma.mma_async.sync.aligned.m64n64k16.f32.bf16.bf16 {"
      "%0, %1, %2, %3, %4, %5, %6, %7, %8, %9, %10, %11, %12, %13, %14, %15, %16, %17, %18, %19, %20, %21, %22, %23, "
      "%24, %25, %26, %27, %28, %29, %30, %31"
      "}, %32, %33, p, 1, 1, %35, %36;\n}\n"
      : "+f"(d[0]), "+f"(d[1]), "+f"(d[2]), "+f"(d[3]), "+f"(d[4]), "+f"(d[5]), "+f"(d[6]), "+f"(d[7]), "+f"(d[8]),
        "+f"(d[9]), "+f"(d[10]), "+f"(d[11]), "+f"(d[12]), "+f"(d[13]), "+f"(d[14]), "+f"(d[15]), "+f"(d[16]),
        "+f"(d[17]), "+f"(d[18]), "+f"(d[19]), "+f"(d[20]), "+f"(d[21]), "+f"(d[22]), "+f"(d[23]), "+f"(d[24]),
        "+f"(d[25]), "+f"(d[26]), "+f"(d[27]), "+f"(d[28]), "+f"(d[29]), "+f"(d[30]), "+f"(d[31])
      : "l"(da), "l"(db), "r"(sd), "n"(TA), "n"(TB));
}
template <int SA, int TB>
__device__ __forceinline__ void wgmma_rs_n64(float (&d)[32], uint32_t a0, uint32_t a1, uint32_t a2, uint32_t a3, uint64_t db, int sd) {
  asm volatile("{\n.reg .pred p;\nsetp.ne.b32 p, %37, 0;\n"
      "wgmma.mma_async.sync.aligned.m64n64k16.f32.bf16.bf16 {"
      "%0, %1, %2, %3, %4, %5, %6, %7, %8, %9, %10, %11, %12, %13, %14, %15, %16, %17, %18, %19, %20, %21, %22, %23, "
      "%24, %25, %26, %27, %28, %29, %30, %31"
      "}, {%32, %33, %34, %35}, %36, p, %38, 1, %39;\n}\n"
      : "+f"(d[0]), "+f"(d[1]), "+f"(d[2]), "+f"(d[3]), "+f"(d[4]), "+f"(d[5]), "+f"(d[6]), "+f"(d[7]), "+f"(d[8]),
        "+f"(d[9]), "+f"(d[10]), "+f"(d[11]), "+f"(d[12]), "+f"(d[13]), "+f"(d[14]), "+f"(d[15]), "+f"(d[16]),
        "+f"(d[17]), "+f"(d[18]), "+f"(d[19]), "+f"(d[20]), "+f"(d[21]), "+f"(d[22]), "+f"(d[23]), "+f"(d[24]),
        "+f"(d[25]), "+f"(d[26]), "+f"(d[27]), "+f"(d[28]), "+f"(d[29]), "+f"(d[30]), "+f"(d[31])
      : "r"(a0), "r"(a1), "r"(a2), "r"(a3), "l"(db), "r"(sd), "n"(SA), "n"(TB));
}

__device__ __forceinline__ uint32_t BAR_FULL(uint32_t sb, int i) { return sb + SM_BAR + 8 * i; }
__device__ __forceinline__ uint32_t BAR_EMPTY(uint32_t sb, int i) { return sb + SM_BAR + 64 + 8 * i; }
__device__ __forceinline__ uint32_t BAR_X(uint32_t sb, int i) { return sb + SM_BAR + 128 + 8 * i; }
__device__ __forceinline__ uint32_t BAR_Y(uint32_t sb, int i) { return sb + SM_BAR + 192 + 8 * i; }
__device__ __forceinline__ uint32_t BAR_XFREE(uint32_t sb) { return sb + SM_BAR + 256; }

#define CMASK 0x194u
#define XORDER 0, 1, 11, 2, 3, 12, 13, 4, 5, 14, 6, 15, 16
#define XSPREAD 2
#define PFAT 3
#define SKEW 3
constexpr int Q_G1B = 18, Q_G2 = 32, Q_P3 = 46, Q_END = 50;

struct Ring {
  uint32_t slot, phase;
  __device__ __forceinline__ void next() { if (++slot == NSTAGE) { slot = 0; phase ^= 1; } }
};

__device__ __forceinline__ void release_slot(uint32_t sb, uint32_t slot, int tid, int times) {
  if (tid < 2 * times) mbar_arrive_cluster(BAR_EMPTY(sb, slot), tid & 1);
}

__device__ __forceinline__ void ffn_consumer(uint32_t sb, const uint8_t* smem, const Params& p, int bid, int wg, int tid, int mt, int jj) {
  const int lane = tid & 31, warp = tid >> 5, q = lane & 3, r0 = 16 * warp + (lane >> 2);
  uint32_t* const my_epoch = &p.s->epoch[blockIdx.x * 12 + (threadIdx.x >> 5)];
  const uint32_t epoch = ld_relaxed(my_epoch) + 1;
  Ring rg{0, 0};
  uint32_t u[64];
  float acc[128];
  uint32_t prev = 0, cmask = CMASK;
  int st = 0;
  auto g1_stage = [&](uint32_t slot, int s) {
    const uint64_t da = mk_desc(sb + SM_X + (s >> 1) * 16384 + wg * 8192 + (s & 1) * 64, 16, 1024, 1);
    const uint64_t db = mk_desc(sb + SM_RING + slot * STAGE_BYTES, 4096, 1024, 1);
    wg_fence();
    wgmma_ss_n256<0, 1>(acc, da, db, s != 0);
    wgmma_ss_n256<0, 1>(acc, da + 2, db + 128, 1);
    wg_commit();
  };
  if (wg == 1) {
    float ap[64];
    constexpr int QX = 32 - __builtin_clz(CMASK);
    constexpr int NPRE = QX + XSPREAD;
    uint4* const x1dst = p.s->x1t + ((64 * jj + r0 + 8) >> 2) * 1024 + (r0 & 3) * 128 + 8 * mt + (q ^ (mt & 3));
    const int x1lo = 64 * jj + r0 == 1 ? 110 * 1024 - 128 : -2048;
#pragma unroll
    for (int qi = 0; qi < NPRE; qi++) {
      const int slot = qi % NSTAGE, nc = __builtin_popcount(CMASK & ((1u << qi) - 1));
      if (qi == 0) TL(60);
      mbar_wait(BAR_FULL(sb, slot), (qi / NSTAGE) & 1);
      if (qi == 0) TL(61);
      if ((CMASK >> qi) & 1) {
#pragma unroll
        for (int kb = 2 * nc; kb < 2 * nc + 2 && kb < 7; kb++) {
          const uint64_t da = mk_desc(sb + SM_RING + slot * STAGE_BYTES + (kb & 1) * 8192, 8192, 1024, 1);
          const uint64_t db = mk_desc(sb + SM_X + kb * 16384, 16, 1024, 1);
          mbar_wait(BAR_X(sb, kb), 0);
          TL(16 + kb);
          wg_fence();
#pragma unroll
          for (int kk = 0; kk < 4; kk++) wgmma_ss_n128<1, 0>(ap, da + kk * 128, db + kk * 2, (kb | kk) != 0);
          wg_commit();
        }
      } else {
        if (((qi - nc) & 1) == 0 && qi - nc >= 4 * nc) mbar_wait(BAR_X(sb, (qi - nc) >> 1), 0);
        TL(32 + qi - nc);
        g1_stage(slot, qi - nc);
      }
      if (qi > 0) {
        wg_wait<1>();
        release_slot(sb, (qi - 1) % NSTAGE, tid, ((CMASK >> (qi - 1)) & 1) ? 2 : 1);
      }
      if (qi >= QX) {
        if (qi == QX) { fence_regs(ap); TL(2); }
#pragma unroll
        for (int t = (qi - QX) * (4 / XSPREAD); t < (qi - QX + 1) * (4 / XSPREAD); t++)
#pragma unroll
        for (int h = 0; h < 2; h++)
          x1dst[(h ? 0 : x1lo) + 512 * (t & 1) + 4 * (t >> 1)] = make_uint4(pack2(ap[16 * t + 2 * h], ap[16 * t + 2 * h + 1]), pack2(ap[16 * t + 4 + 2 * h], ap[16 * t + 5 + 2 * h]),
                                             pack2(ap[16 * t + 8 + 2 * h], ap[16 * t + 9 + 2 * h]), pack2(ap[16 * t + 12 + 2 * h], ap[16 * t + 13 + 2 * h]));
      }
    }
    bar_arrive(7, 160);
    st = NPRE - 4; cmask = 0; prev = (NPRE - 1) % NSTAGE;
    rg.slot = NPRE % NSTAGE; rg.phase = (NPRE / NSTAGE) & 1;
  }
#pragma unroll 1
  for (int pass = 0; pass < 2; pass++) {
#pragma unroll 1
    for (; st < 14; st++) {
      while (cmask & 1) { cmask >>= 1; rg.next(); }
      cmask >>= 1;
      if (pass == 0 && (st & 1) == 0) mbar_wait(BAR_X(sb, st >> 1), 0);
      if (st == 14 - SKEW && wg == 1) bar_sync(9 + pass, 256);
      mbar_wait(BAR_FULL(sb, rg.slot), rg.phase);
      TL(32 + 14 * pass + st);
      g1_stage(rg.slot, st);
      wg_wait<1>();
      if (st > 0) release_slot(sb, prev, tid, 1);
      prev = rg.slot;
      rg.next();
    }
    st = 0;
    if (wg == 0) bar_arrive(9 + pass, 256);
    wg_wait<0>();
    fence_regs(acc);
    release_slot(sb, prev, tid, 1);
    if (pass == 1 && tid == 0) mbar_arrive(BAR_XFREE(sb));
    TL(3 + 2 * pass);
#pragma unroll
    for (int i = 0; i < 32; i++) {
      const float g0 = 0.5f * acc[2 * i], g1 = 0.5f * acc[2 * i + 1];
      const float s0 = fmaf(g0, tanh_fast(g0), g0), s1 = fmaf(g1, tanh_fast(g1), g1);
      u[32 + i] = pack2(s0 * acc[64 + 2 * i], s1 * acc[64 + 2 * i + 1]);
    }
    if (pass == 0) {
#pragma unroll
      for (int i = 0; i < 32; i++) u[i] = u[32 + i];
    }
    TL(4 + 2 * pass);
  }
  fence_regs(u);
  float accA[32], accB[32];
  rg.slot = Q_G2 % NSTAGE; rg.phase = (Q_G2 / NSTAGE) & 1;
  auto stage = [&](float (&acc)[32], int st) {
    mbar_wait(BAR_FULL(sb, rg.slot), rg.phase);
    const uint64_t db = mk_desc(sb + SM_RING + rg.slot * STAGE_BYTES, 8192, 1024, 1);
    wg_fence();
#pragma unroll
    for (int kk = 0; kk < 8; kk++) {
      const uint32_t* a = u + 32 * st + 4 * kk;
      wgmma_rs_n64<1, 1>(acc, a[0], a[1], a[2], a[3], db + kk * 128, (st | kk) != 0);
    }
    wg_commit();
  };
  auto retire = [&](bool rel) {
    wg_wait<1>();
    if (rel) release_slot(sb, prev, tid, 1);
    prev = rg.slot;
    rg.next();
  };
  const uint32_t par = epoch & 1;
  auto put = [&](float (&acc)[32], int c) {
    fence_regs(acc);
    int o = jj + 1 + c;
    if (o >= 7) o -= 7;
    uint4* dst = p.s->part + ((((mt * 7 + o) * 6 + c) * 2 + wg) * 4) * 128 + tid;
#pragma unroll
    for (int v = 0; v < 4; v++) {
      const float* a = acc + 8 * v;
      st_relaxed(dst + v * 128, make_uint4((pack2(a[0], a[1]) & ~1u) | par, pack2(a[2], a[3]), pack2(a[4], a[5]), pack2(a[6], a[7])));
    }
  };
  const uint4* const src = p.s->part + (((mt * 7 + jj) * 6 * 2 + wg) * 4) * 128 + tid;
  auto gload = [&](uint4 (&pv)[8], int c) {
#pragma unroll
    for (int i = 0; i < 8; i++) pv[i] = ld_relaxed(src + ((2 * c + (i >> 2)) * 8 + (i & 3)) * 128);
  };
  auto gsum = [&](uint4 (&pv)[8], int c) {
#pragma unroll 1
    for (uint32_t n = 0; n < SPIN_LIMIT; n++) {
      uint32_t bad = 0;
#pragma unroll
      for (int i = 0; i < 8; i++) bad |= pv[i].x ^ par;
      if (!__any_sync(0xffffffffu, bad & 1)) break;
      gload(pv, c);
    }
    TL(24 + c);
#pragma unroll
    for (int i = 0; i < 8; i++) {
      const float t[8] = {bf_lo(pv[i].x), bf_hi(pv[i].x), bf_lo(pv[i].y), bf_hi(pv[i].y), bf_lo(pv[i].z), bf_hi(pv[i].z), bf_lo(pv[i].w), bf_hi(pv[i].w)};
#pragma unroll
      for (int k = 0; k < 8; k++) accA[8 * (i & 3) + k] += t[k];
    }
  };
#pragma unroll
  for (int c2 = 0; c2 < 4; c2++) {
    stage(accA, 0);
    retire(c2 == 1 || c2 == 2);
    stage(accA, 1);
    if (c2 > 0) put(accB, 2 * c2 - 1);
    TL(7 + c2);
    if (c2 == 3) break;
    retire(true);
    stage(accB, 0);
    retire(true);
    stage(accB, 1);
    put(accA, 2 * c2);
    retire(true);
  }
  rg.next();
  wg_wait<0>();
  fence_regs(accA);
  uint4 pv0[8], pv1[8], pv2[8];
  const int row = 128 * mt + 64 * wg + r0;
  uint32_t gt0 = ld_relaxed(&p.s->gate[row]), gt1 = ld_relaxed(&p.s->gate[row + 8]);
  gload(pv0, 0);
  gload(pv1, 1);
  TL(15);
#pragma unroll 1
  for (int kb = 0; kb < 7; kb++) {
    if ((kb & 1) == 0) mbar_wait(BAR_FULL(sb, rg.slot), rg.phase);
    mbar_wait(BAR_Y(sb, kb), 0);
    const uint64_t da = mk_desc(sb + SM_X + kb * 16384 + wg * 8192, 8192, 1024, 1);
    const uint64_t db = mk_desc(sb + SM_RING + rg.slot * STAGE_BYTES + (kb & 1) * 8192, 16, 1024, 1);
    wg_fence();
#pragma unroll
    for (int kk = 0; kk < 4; kk++) wgmma_ss_n64<1, 0>(accB, da + kk * 128, db + kk * 2, (kb | kk) != 0);
    wg_commit();
    if (kb & 1) rg.next();
  }
  TL(11);
  gload(pv2, 2);
  gsum(pv0, 0);
  gsum(pv1, 1);
  for (uint32_t n = 0; (((gt0 ^ epoch) | (gt1 ^ epoch)) & 0xffffu) && n < SPIN_LIMIT; n++) {
    gt0 = ld_relaxed(&p.s->gate[row]); gt1 = ld_relaxed(&p.s->gate[row + 8]);
  }
  gsum(pv2, 2);
  const float ga0 = bf_hi(gt0), ga1 = bf_hi(gt1);
  TL(12);
  wg_wait<0>();
  fence_regs(accB);
  TL(13);
  const float gb0 = bf_round(1.f - ga0), gb1 = bf_round(1.f - ga1);
  const float gs0 = ga0 * (2.f / (float)(S_ * D_)), gs1 = ga1 * (2.f / (float)(S_ * D_));
  uint4* const o = reinterpret_cast<uint4*>(p.out + (size_t)row * D_ + 64 * jj + 8 * q);
#pragma unroll
  for (int h = 0; h < 2; h++) {
    const float gs = h ? gs1 : gs0, gb = h ? gb1 : gb0;
#pragma unroll
    for (int k = 0; k < 2; k++) {
      uint32_t w[4];
#pragma unroll
      for (int j = 0; j < 4; j++) {
        const int i = 16 * k + 4 * j + 2 * h;
        w[j] = pack2(fmaf(gs, accB[i], gb * accA[i]), fmaf(gs, accB[i + 1], gb * accA[i + 1]));
      }
      const bool o1 = q & 1, o2 = q & 2;
      uint32_t a = __shfl_xor_sync(0xffffffffu, o1 ? w[0] : w[1], 1), b = __shfl_xor_sync(0xffffffffu, o1 ? w[2] : w[3], 1);
      if (o1) { w[0] = a; w[2] = b; } else { w[1] = a; w[3] = b; }
      a = __shfl_xor_sync(0xffffffffu, o2 ? w[0] : w[2], 2); b = __shfl_xor_sync(0xffffffffu, o2 ? w[1] : w[3], 2);
      if (o2) { w[0] = a; w[1] = b; } else { w[2] = a; w[3] = b; }
      o[h * D_ + 4 * k] = make_uint4(w[0], w[1], w[2], w[3]);
    }
  }
  if (lane == 0) *my_epoch = epoch;
  TL(14);
}

__device__ __forceinline__ void ring_issue(uint32_t sb, const Params& p, int qi, uint32_t slot, bool wait, uint32_t phase, int jj, uint32_t rank) {
  const CUtensorMap* m;
  int c0, c1, c2 = 0;
  bool half = false, is3d = false;
  if (qi < Q_G2) {
    const int nc = __popc(CMASK & ((1u << qi) - 1));
    if ((CMASK >> qi) & 1) {
      m = &p.ct; c0 = 64 * jj; c1 = 128 * nc + 64 * rank; half = nc == 3;
    } else {
      const int pass = qi >= Q_G1B;
      m = rank ? &p.wu : &p.wg; c0 = 0; c1 = 32 * (qi - nc - 14 * pass); c2 = 4 * jj + 2 * pass; is3d = true;
    }
  } else if (qi < Q_P3) {
    int o = jj + 1 + ((qi - Q_G2) >> 1);
    if (o >= 7) o -= 7;
    m = &p.wd; c0 = 64 * o; c1 = 256 * jj + 128 * (qi & 1) + 64 * rank;
  } else {
    m = &p.ct; c0 = 128 * (qi - Q_P3) + 64 * rank; c1 = 64 * jj; half = qi == Q_END - 1;
  }
  const uint32_t bar = BAR_FULL(sb, slot);
  const uint32_t dst = sb + SM_RING + slot * STAGE_BYTES + rank * 8192;
  if (wait) mbar_wait_cluster(BAR_EMPTY(sb, slot), phase);
  mbar_expect_tx(bar, half ? 8192 : 16384);
  if (is3d) tma3d_mc(dst, m, c0, c1, c2, bar);
  else if (!(half && rank)) tma2d_mc(dst, m, c0, c1, bar);
}

__device__ __forceinline__ void ffn_producer(uint32_t sb, const uint8_t* smem, int bid, const Params& p, int warp, int lane, int mt, int jj, uint32_t rank) {
  if (warp < 2) {
    if (lane == 0) {
      uint32_t slot = warp, phase = 0;
#pragma unroll 1
      for (int qi = NSTAGE + warp; qi < Q_END; qi += 2) {
        ring_issue(sb, p, qi, slot, true, phase, jj, rank);
        TL(10 + qi);
        slot += 2;
        if (slot >= NSTAGE) { slot -= NSTAGE; phase ^= 1; }
      }
    }
  } else {
    const int wg = warp - 2;
    if (wg == 0) {
      if (lane == 0) { prefetch_tmap(&p.wd); prefetch_tmap(&p.yt); }
      uint32_t* const my_epoch = &p.s->epoch[blockIdx.x * 12 + 10];
      const uint32_t epoch = ld_relaxed(my_epoch) + 1;
      {
        const uint4* gw4 = reinterpret_cast<const uint4*>(p.gate_w);
        const uint4 ga = __ldg(gw4 + lane), gb = lane < 24 ? __ldg(gw4 + 32 + lane) : make_uint4(0, 0, 0, 0);
        if (lane < 7) mbar_wait(BAR_X(sb, lane), 0);
        __syncwarp();
        float mine = 0.f;
#pragma unroll 1
        for (int u = 0; u < 19; u++) {
          const int r = min(19 * jj + u, 127);
          const uint8_t* xr = smem + SM_X + (lane >> 3) * 16384 + r * 128 + (((lane ^ r) & 7) << 4);
          const uint4 xa = *reinterpret_cast<const uint4*>(xr);
          const uint4 xb = lane < 24 ? *reinterpret_cast<const uint4*>(xr + 65536) : make_uint4(0, 0, 0, 0);
          float s = 0.f;
          auto dot2 = [&](uint32_t a, uint32_t b) {
            const uint32_t pr = mul2(a, b);
            s += bf_lo(pr) + bf_hi(pr);
          };
          dot2(xa.x, ga.x); dot2(xa.y, ga.y); dot2(xa.z, ga.z); dot2(xa.w, ga.w);
          dot2(xb.x, gb.x); dot2(xb.y, gb.y); dot2(xb.z, gb.z); dot2(xb.w, gb.w);
#pragma unroll
          for (int o = 16; o > 0; o >>= 1) s += __shfl_xor_sync(0xffffffffu, s, o);
          if (lane == u) mine = s;
        }
        if (lane < 19 && 19 * jj + lane < 128)
          st_relaxed(&p.s->gate[128 * mt + 19 * jj + lane], pack2(0.f, 1.f / (1.f + __expf(-bf_round(mine)))) | (epoch & 0xffffu));
      }
      TL(9);
      mbar_wait(BAR_XFREE(sb), 0);
      TL(3);
      bool todo = lane < 7;
      uint32_t n = 0;
      while (__any_sync(0xffffffffu, todo)) {
        if (todo) {
          uint32_t v;
          asm volatile("ld.acquire.gpu.global.u32 %0, [%1];" : "=r"(v) : "l"(&p.s->cnt_y[lane * 32]) : "memory");
          if ((int32_t)(v - epoch * (lane ? 16 : 17)) >= 0 || ++n > SPIN_LIMIT) {
            mbar_expect_tx(BAR_Y(sb, lane), 16384);
            tma3d(sb + SM_X + lane * 16384, &p.yt, 0, 64 * lane, 2 * mt, BAR_Y(sb, lane));
            todo = false;
          }
        }
      }
      TL(4);
      if (lane == 0) *my_epoch = epoch;
    } else {
      mbar_wait(BAR_X(sb, PFAT), 0);
      if (lane < 6) {
        int row = 176 + 3 * bid + (lane >> 1);
        if (row >= D_) row -= D_;
        l2_prefetch(((lane & 1) ? p.pwu : p.pwg) + row * F_, F_ * 2);
      }
      TL(2);
      bar_sync(7, 160);
      if (lane == 0) { fence_gpu(); red_add(&p.s->cnt_x1[jj * 32], 1); l2_prefetch(p.pwd + bid * 16 * D_, 32 * D_); }
      TL(3);
    }
  }
}

__device__ __forceinline__ void spectral_cta(uint32_t sb, uint8_t* smem, const Params& p, int sc, int wg) {
  const int t384 = threadIdx.x, lane = t384 & 31, warp12 = t384 >> 5, tid = t384 & 127;
  const int warp = tid >> 5, q = lane & 3;
  const int sl0 = 6 * sc + min(sc, 8), nsl = sc < 8 ? 7 : 6;
  if (t384 == 320) {
#pragma unroll 1
    for (int i = 0; i < nsl; i++) {
      mbar_expect_tx(BAR_X(sb, i), 2 * SLAB_BYTES);
      const int row = 128 * ((sl0 + i) >> 3) + 8 * ((sl0 + i) & 7);
      const uint32_t dst = sb + SP_Z + 2 * i * SLAB_BYTES;
      bulk_g2s(dst, p.w_r + row * DF_, SLAB_BYTES / 2, BAR_X(sb, i));
      bulk_g2s(dst + SLAB_BYTES / 2, p.w_r + (row + 64) * DF_, SLAB_BYTES / 2, BAR_X(sb, i));
      bulk_g2s(dst + SLAB_BYTES, p.w_i + row * DF_, SLAB_BYTES / 2, BAR_X(sb, i));
      bulk_g2s(dst + 3 * SLAB_BYTES / 2, p.w_i + (row + 64) * DF_, SLAB_BYTES / 2, BAR_X(sb, i));
    }
    if (sc < 19) {
      mbar_expect_tx(BAR_Y(sb, 6), 24576);
      bulk_g2s(sb + SP_TW, p.spec, 24576, BAR_Y(sb, 6));
    }
  }
  uint32_t* const my_epoch = &p.s->epoch[blockIdx.x * 12 + warp12];
  const uint32_t epoch = ld_relaxed(my_epoch) + 1;
  uint32_t fe[16], tw[16];
#pragma unroll
  for (int i = 0; i < 4; i++) {
    const uint4 a = __ldg(reinterpret_cast<const uint4*>(p.spec->fe) + i * 128 + tid);
    const uint4 b = __ldg(reinterpret_cast<const uint4*>(p.spec->tw) + i * 128 + tid);
    fe[4 * i] = a.x; fe[4 * i + 1] = a.y; fe[4 * i + 2] = a.z; fe[4 * i + 3] = a.w;
    tw[4 * i] = b.x; tw[4 * i + 1] = b.y; tw[4 * i + 2] = b.z; tw[4 * i + 3] = b.w;
  }
  __syncwarp();
  asm volatile("barrier.cluster.wait.acquire.aligned;" ::: "memory");
#pragma unroll 2
  for (int un = wg; un < 8 * nsl; un += 3) {
    const int i = un >> 3, sl = sl0 + i, pr = 16 * (un & 7) + 4 * (lane >> 3) + warp, r = lane & 7;
    mbar_wait(BAR_X(sb, i), 0);
    if (pr < 113) {
      const uint16_t* w = reinterpret_cast<const uint16_t*>(smem + SP_Z + 2 * i * SLAB_BYTES) + r * DF_ + 2 * pr;
      const uint32_t m = pr < 112 ? 0xffffffffu : 0u;
      p.s->wt[pr * 1024 + sl * 8 + (r ^ ((sl >> 2) & 6))] =
          make_uint4(w[0] | ((uint32_t)w[8 * DF_] << 16), w[16 * DF_] | ((uint32_t)w[24 * DF_] << 16),
                     (w[1] | ((uint32_t)w[8 * DF_ + 1] << 16)) & m, (w[16 * DF_ + 1] | ((uint32_t)w[24 * DF_ + 1] << 16)) & m);
    }
  }
  __syncthreads();
  if (t384 == 352) { fence_gpu(); red_add(&p.s->cnt_w[0], 1); }
  TL(1);
  if (sc == 19) return;
  const int nrnd = (sc == 18 && wg == 2) ? 1 : 2;
  if (tid == 32) {
    wait_counter(&p.s->cnt_w[0], epoch * NSPEC);
    fence_async();
    for (int rnd = 0; rnd < nrnd; rnd++) {
      const int item = wg + 3 * rnd;
      mbar_expect_tx(BAR_Y(sb, item), 16384);
      bulk_g2s(sb + SP_W + item * 16384, p.s->wt + (6 * sc + item) * 1024, 16384, BAR_Y(sb, item));
    }
  } else if (tid == 0) {
#pragma unroll 1
    for (int rnd = 0; rnd < nrnd; rnd++) {
      const int item = wg + 3 * rnd, pr = 6 * sc + item;
      wait_counter(&p.s->cnt_x1[(pr < 112 ? pr >> 4 : 0) * 32], epoch * 16);
      fence_async();
      const uint32_t bar = BAR_FULL(sb, item), z = sb + SP_Z + item * 16384;
      mbar_expect_tx(bar, 16384);
      bulk_g2s(z, p.s->x1t + pr * 1024, 16384, bar);
    }
  }
  __syncwarp();
  fence_regs(fe); fence_regs(tw);
  mbar_wait(BAR_Y(sb, 6), 0);
  TL(3);
  const uint64_t dT_n = mk_desc(sb + SP_T, 8192, 1024, 1);
#pragma unroll 1
  for (int rnd = 0; rnd < nrnd; rnd++) {
    const int item = wg + 3 * rnd, pr = 6 * sc + item;
    const uint32_t z = sb + SP_Z + item * 16384;
    uint32_t fa[16], fb[16];
    auto load_frag = [&](int off) {
#pragma unroll
      for (int i = 0; i < 4; i++) {
        const uint4 a = *reinterpret_cast<const uint4*>(smem + SP_TW + off + i * 2048 + tid * 16);
        fa[4 * i] = a.x; fa[4 * i + 1] = a.y; fa[4 * i + 2] = a.z; fa[4 * i + 3] = a.w;
      }
      fence_regs(fa);
    };
    load_frag(0);
    mbar_wait(BAR_FULL(sb, item), 0);
    TL(4 + 8 * rnd);
    if (rnd == 0 && wg > 0) bar_sync(3 + wg, 256);
    float aR[32], aI[32];
    {
      const uint64_t de = mk_desc(z, 4096, 512, 2);
      wg_fence();
#pragma unroll
      for (int kk = 0; kk < 4; kk++) {
        wgmma_rs_n64<1, 1>(aR, fe[4 * kk], fe[4 * kk + 1], fe[4 * kk + 2], fe[4 * kk + 3], de + kk * 64, kk != 0);
        wgmma_rs_n64<1, 1>(aI, fa[4 * kk], fa[4 * kk + 1], fa[4 * kk + 2], fa[4 * kk + 3], de + 512 + kk * 64, kk != 0);
      }
      wg_commit();
      if (rnd == 0 && wg < 2) bar_arrive(4 + wg, 256);
      wg_wait<0>();
      fence_regs(aR); fence_regs(aI);
    }
    TL(5 + 8 * rnd);
#pragma unroll
    for (int v = 0; v < 8; v++) {
      uint32_t* f = (v < 4 ? fa : fb) + 2 * (v & 3);
      const uint32_t* t = tw + 2 * (v & 3);
      const float *e = aR + 4 * v, *o = aI + 4 * v;
      const uint32_t er = pack2(e[0], e[1]), ei = pack2(e[2], e[3]), qr = pack2(o[0], o[1]), qi = pack2(o[2], o[3]);
      const uint32_t u0r = add2(er, qr), u0i = add2(ei, qi), u1r = sub2(er, qr), u1i = sub2(ei, qi);
      f[0] = fma2(u0r, t[0], mul2(u0i, t[8]));
      f[8] = fms2(u0i, t[0], mul2(u0r, t[8]));
      f[1] = fma2(u1r, t[1], mul2(u1i, t[9]));
      f[9] = fms2(u1i, t[1], mul2(u1r, t[9]));
    }
    fence_regs(fa); fence_regs(fb);
    wg_fence();
#pragma unroll
    for (int kk = 0; kk < 4; kk++) {
      wgmma_rs_n64<1, 1>(aR, fa[4 * kk], fa[4 * kk + 1], fa[4 * kk + 2], fa[4 * kk + 3], dT_n + kk * 128, kk != 0);
      wgmma_rs_n64<1, 1>(aI, fb[4 * kk], fb[4 * kk + 1], fb[4 * kk + 2], fb[4 * kk + 3], dT_n + kk * 128, kk != 0);
    }
    wg_commit();
    mbar_wait(BAR_Y(sb, item), 0);
    wg_wait<0>();
    fence_regs(aR); fence_regs(aI);
    TL(6 + 8 * rnd);
    {
      const uint8_t* wp = smem + SP_W + item * 16384 + q * 1024 + warp * 128 + (((lane >> 2) ^ (2 * q)) << 4);
#pragma unroll
      for (int jb = 0; jb < 4; jb++) {
#pragma unroll
        for (int h = 0; h < 2; h++) {
          const uint4 w = *reinterpret_cast<const uint4*>(wp + jb * 4096 + h * 512);
          const int i = 4 * jb + 2 * h;
          const uint32_t ar = pack2(aR[i], aR[i + 1]), ai = pack2(aR[16 + i], aR[17 + i]);
          const uint32_t br = pack2(aI[i], aI[i + 1]), bi = pack2(aI[16 + i], aI[17 + i]);
          fa[2 * jb + h] = fms2(ar, w.x, mul2(ai, w.y));
          fa[8 + 2 * jb + h] = fma2(ar, w.y, mul2(ai, w.x));
          fb[2 * jb + h] = fms2(br, w.z, mul2(bi, w.w));
          fb[8 + 2 * jb + h] = fma2(br, w.w, mul2(bi, w.z));
        }
      }
    }
    fence_regs(fa); fence_regs(fb);
    wg_fence();
#pragma unroll
    for (int kk = 0; kk < 4; kk++) {
      wgmma_rs_n64<1, 0>(aR, fa[4 * kk], fa[4 * kk + 1], fa[4 * kk + 2], fa[4 * kk + 3], dT_n + kk * 2, kk != 0);
      wgmma_rs_n64<1, 0>(aI, fb[4 * kk], fb[4 * kk + 1], fb[4 * kk + 2], fb[4 * kk + 3], dT_n + kk * 2, kk != 0);
    }
    wg_commit();
    wg_wait<0>();
    fence_regs(aR); fence_regs(aI);
    TL(7 + 8 * rnd);
#pragma unroll
    for (int v = 0; v < 8; v++) {
      const float* a = (v < 4 ? aR : aI) + 4 * (v & 3);
      const uint32_t* t = tw + 2 * (v & 3);
      const uint32_t u0r = pack2(a[0], a[1]), u1r = pack2(a[2], a[3]), u0i = pack2(a[16], a[17]), u1i = pack2(a[18], a[19]);
      const uint32_t t0r = fms2(u0r, t[0], mul2(u0i, t[8])), t0i = fma2(u0i, t[0], mul2(u0r, t[8]));
      const uint32_t t1r = fms2(u1r, t[1], mul2(u1i, t[9])), t1i = fma2(u1i, t[1], mul2(u1r, t[9]));
      fa[v] = add2(t0i, t1i); fa[8 + v] = add2(t0r, t1r);
      fb[v] = sub2(t0i, t1i); fb[8 + v] = sub2(t0r, t1r);
    }
    bar_sync(1 + wg, 128);
#pragma unroll
    for (int u = 0; u < 4; u++) {
      const uint32_t a = z + (32 * (u >> 1) + 8 * warp + (lane & 7)) * 128 + (((4 * (u & 1) + (lane >> 3)) ^ (lane & 7)) << 4);
      stmatrix_x4(a, fa[4 * u], fa[4 * u + 1], fa[4 * u + 2], fa[4 * u + 3]);
      stmatrix_x4(a + 8192, fb[4 * u], fb[4 * u + 1], fb[4 * u + 2], fb[4 * u + 3]);
    }
    load_frag(8192);
    fence_async_smem();
    bar_sync(1 + wg, 128);
    TL(8 + 8 * rnd);
    {
      const uint64_t de = mk_desc(z, 8192, 1024, 1);
      wg_fence();
#pragma unroll
      for (int kk = 0; kk < 4; kk++) {
        wgmma_rs_n64<1, 1>(aR, fe[4 * kk], fe[4 * kk + 1], fe[4 * kk + 2], fe[4 * kk + 3], de + kk * 128, kk != 0);
        wgmma_rs_n64<1, 1>(aI, fa[4 * kk], fa[4 * kk + 1], fa[4 * kk + 2], fa[4 * kk + 3], de + 512 + kk * 128, kk != 0);
      }
      wg_commit();
      wg_wait<0>();
      fence_regs(aR); fence_regs(aI);
    }
    TL(9 + 8 * rnd);
    const bool edge = pr == 0 || pr == 112;
    if (edge) {
#pragma unroll
      for (int i = 0; i < 16; i++) { aR[i] *= 0.5f; aI[i] *= 0.5f; }
    }
#pragma unroll
    for (int i = 0; i < 8; i++) {
      const float* a = ((i & 1) ? aI : aR) + 16 * (i >> 2) + 2 - (i & 2);
      *reinterpret_cast<uint4*>(smem + SP_W + item * 16384 + (i >> 1) * 4096 + (i & 1) * 64 + (tid >> 2) * 128 + q * 16) =
          make_uint4(pack2(a[0], a[1]), pack2(a[4], a[5]), pack2(a[8], a[9]), pack2(a[12], a[13]));
    }
    fence_async_smem();
    bar_sync(1 + wg, 128);
    if (tid == 0) {
      const uint32_t src = sb + SP_W + item * 16384;
      __nv_bfloat16* dst = p.s->yt + (size_t)(pr < 112 ? 4 * pr : 1) * S_;
      bulk_s2g(dst, src, edge ? 4096 : 16384);
      if (pr == 0) bulk_s2g(dst + 2 * S_, src + 8192, 8192);
      asm volatile("cp.async.bulk.commit_group;" ::: "memory");
      if (rnd == nrnd - 1) {
        asm volatile("cp.async.bulk.wait_group 0;" ::: "memory");
        TL(11);
        fence_async();
        fence_gpu();
        red_add(&p.s->cnt_y[(pr < 112 ? pr >> 4 : 0) * 32], 1);
        if (rnd) red_add(&p.s->cnt_y[((pr - 3) >> 4) * 32], 1);
      }
    }
    __syncwarp();
    TL(10 + 8 * rnd);
  }
  if (lane == 0) *my_epoch = epoch;
}

__global__ void __cluster_dims__(2, 1, 1) __launch_bounds__(384, 1)
fused_kernel(const __grid_constant__ Params p) {
  extern __shared__ __align__(1024) uint8_t smem[];
  const uint32_t sb = smem_u32(smem);
  TL(0);
  const uint32_t rank = blockIdx.x & 1;
  const int hc = blockIdx.x >> 1;
  int grp, jj;
  if (hc < 4) { grp = 8; jj = hc; }
  else if (hc < 36) { grp = (hc - 4) & 7; jj = (hc - 4) >> 3; }
  else if (hc < 57) { jj = (hc - 36) / 7; grp = 1 + (hc - 36) - 7 * jj; jj += 4; }
  else if (hc < 60) { grp = 0; jj = hc - 53; }
  else { grp = 8; jj = hc - 56; }
  const int mt = 2 * grp + rank, bid = 2 * (7 * grp + jj) + rank;
  if (threadIdx.x == 256) {
#pragma unroll
    for (int i = 0; i < NSTAGE; i++) { mbar_init(BAR_FULL(sb, i), 1); mbar_init(BAR_EMPTY(sb, i), 4); }
    asm volatile("fence.mbarrier_init.release.cluster;" ::: "memory");
  } else if (threadIdx.x == 320) {
#pragma unroll
    for (int i = 0; i < NSTAGE; i++) { mbar_init(BAR_X(sb, i), 1); mbar_init(BAR_Y(sb, i), 1); }
    mbar_init(BAR_XFREE(sb), 2);
    asm volatile("fence.mbarrier_init.release.cluster;" ::: "memory");
  } else if (threadIdx.x == 288) {
    prefetch_tmap(rank ? &p.wu : &p.wg); prefetch_tmap(&p.ct);
  }
  __syncwarp();
  asm volatile("barrier.cluster.arrive.relaxed.aligned;" ::: "memory");
  const int wg = __shfl_sync(0xffffffffu, threadIdx.x >> 7, 0);
  if (bid >= NFFN) {
    spectral_cta(sb, smem, p, bid - NFFN, wg);
  } else if (wg < 2) {
    asm volatile("setmaxnreg.inc.sync.aligned.u32 232;");
    asm volatile("barrier.cluster.wait.acquire.aligned;" ::: "memory");
    TL(1);
    ffn_consumer(sb, smem, p, bid, wg, threadIdx.x & 127, mt, jj);
  } else {
    asm volatile("setmaxnreg.dec.sync.aligned.u32 40;");
    if (threadIdx.x == 320) {
      mbar_expect_tx(BAR_X(sb, 0), 16384);
      tma2d(sb + SM_X, &p.x, 0, 128 * mt, BAR_X(sb, 0));
    }
    __syncwarp();
    asm volatile("barrier.cluster.wait.acquire.aligned;" ::: "memory");
    TL(1);
    if (threadIdx.x == 320) {
      constexpr int order[13] = {XORDER};
#pragma unroll
      for (int i = 0; i < 13; i++) {
        if (order[i] < 8) {
          ring_issue(sb, p, order[i], order[i], false, 0, jj, rank);
        } else {
          const int kb = order[i] - 10;
          mbar_expect_tx(BAR_X(sb, kb), 16384);
          tma2d(sb + SM_X + kb * 16384, &p.x, 64 * kb, 128 * mt, BAR_X(sb, kb));
        }
      }
      TL(2);
    } else if (threadIdx.x == 352) {
    }
    __syncwarp();
    ffn_producer(sb, smem, bid, p, (threadIdx.x >> 5) & 3, threadIdx.x & 31, mt, jj, rank);
  }
}

typedef CUresult (*EncodeFn)(CUtensorMap*, CUtensorMapDataType, cuuint32_t, void*, const cuuint64_t*, const cuuint64_t*,
                             const cuuint32_t*, const cuuint32_t*, CUtensorMapInterleave, CUtensorMapSwizzle,
                             CUtensorMapL2promotion, CUtensorMapFloatOOBfill);

void make_map(EncodeFn fn, CUtensorMap* m, const void* base, int rank, const cuuint64_t* dims, const cuuint64_t* strides,
              const cuuint32_t* box, CUtensorMapSwizzle sw) {
  const cuuint32_t es[4] = {1, 1, 1, 1};
  fn(m, CU_TENSOR_MAP_DATA_TYPE_BFLOAT16, rank, const_cast<void*>(base), dims, strides, box, es,
     CU_TENSOR_MAP_INTERLEAVE_NONE, sw, CU_TENSOR_MAP_L2_PROMOTION_L2_256B, CU_TENSOR_MAP_FLOAT_OOB_FILL_NONE);
}

}

extern "C" void kernel_launch(void* const* d_in, const int* in_sizes, int n_in, void* d_out, int out_size) {
  const __nv_bfloat16* x = (const __nv_bfloat16*)d_in[0];
  const __nv_bfloat16* w_r = (const __nv_bfloat16*)d_in[1];
  const __nv_bfloat16* w_i = (const __nv_bfloat16*)d_in[2];
  const __nv_bfloat16* wg = (const __nv_bfloat16*)d_in[4];
  const __nv_bfloat16* wu = (const __nv_bfloat16*)d_in[5];
  const __nv_bfloat16* wd = (const __nv_bfloat16*)d_in[6];
  const __nv_bfloat16* gate_w = (const __nv_bfloat16*)d_in[7];

  void* fnp = nullptr;
  cudaDriverEntryPointQueryResult qr;
  cudaGetDriverEntryPoint("cuTensorMapEncodeTiled", &fnp, cudaEnableDefault, &qr);
  EncodeFn fn = (EncodeFn)fnp;
  void *ctab, *spec, *scr;
  cudaGetSymbolAddress(&ctab, g_ctab);
  cudaGetSymbolAddress(&spec, g_spec);
  cudaGetSymbolAddress(&scr, g_scratch);
  const void* yt = (const char*)scr + offsetof(Scratch, yt);
  Params p;
  p.s = (Scratch*)scr; p.out = (__nv_bfloat16*)d_out;
  p.px = x; p.w_r = w_r; p.w_i = w_i; p.gate_w = gate_w; p.pwg = wg; p.pwu = wu; p.pwd = wd;
  p.ctab = (const tab::Table*)ctab; p.spec = (const tab::Spec*)spec;
  {
    const cuuint64_t d[2] = {D_, S_}, s[1] = {D_ * 2};
    const cuuint32_t b[2] = {64, 128};
    make_map(fn, &p.x, x, 2, d, s, b, CU_TENSOR_MAP_SWIZZLE_128B);
  }
  {
    const cuuint64_t d[3] = {64, D_, F_ / 64}, s[2] = {F_ * 2, 128};
    const cuuint32_t b[3] = {64, 32, 2};
    make_map(fn, &p.wg, wg, 3, d, s, b, CU_TENSOR_MAP_SWIZZLE_128B);
    make_map(fn, &p.wu, wu, 3, d, s, b, CU_TENSOR_MAP_SWIZZLE_128B);
  }
  {
    const cuuint64_t d[2] = {D_, F_}, s[1] = {D_ * 2};
    const cuuint32_t b[2] = {64, 64};
    make_map(fn, &p.wd, wd, 2, d, s, b, CU_TENSOR_MAP_SWIZZLE_128B);
  }
  {
    const cuuint64_t d[2] = {D_, D_}, s[1] = {D_ * 2};
    const cuuint32_t b[2] = {64, 64};
    make_map(fn, &p.ct, ctab, 2, d, s, b, CU_TENSOR_MAP_SWIZZLE_128B);
  }
  {
    const cuuint64_t d[3] = {64, D_, S_ / 64}, s[2] = {S_ * 2, 128};
    const cuuint32_t b[3] = {64, 64, 2};
    make_map(fn, &p.yt, yt, 3, d, s, b, CU_TENSOR_MAP_SWIZZLE_128B);
  }
  cudaFuncSetAttribute(fused_kernel, cudaFuncAttributeMaxDynamicSharedMemorySize, SM_TOTAL);
  fused_kernel<<<NCTA, 384, SM_TOTAL, cudaStreamPerThread>>>(p, x, w_r, w_i, gate_w, wd, (__nv_bfloat16*)d_out);
}
```

```cpp
#include <cuda_runtime.h>
#include <cuda_bf16.h>
#include <cuda.h>
#include <stdint.h>
#include <stddef.h>

namespace {

constexpr int S_ = 2048, D_ = 448, F_ = 1792, DF_ = 225;
constexpr int NFFN = 112, NSPEC = 20, NCTA = NFFN + NSPEC;
constexpr int NSTAGE = 7, STAGE_BYTES = 16384;
constexpr int SM_X = 0, SM_RING = 114688, SM_BAR = 229376, SM_TOTAL = SM_BAR + 512;
constexpr int SP_Z = 0, SP_W = 98304, SP_TW = 198656, SP_T = 215040, SLAB_BYTES = 16 * DF_ * 2;
constexpr uint32_t SPIN_LIMIT = 1u << 20;

namespace tab {
constexpr double PI = 3.14159265358979323846264338327950288;
constexpr double csin(double x) {
  double t = x, s = x;
  for (int i = 1; i < 20; i++) { t = -t * x * x / ((2 * i) * (2 * i + 1)); s += t; }
  return s;
}
constexpr double ccos(double x) {
  double t = 1, s = 1;
  for (int i = 1; i < 20; i++) { t = -t * x * x / ((2 * i - 1) * (2 * i)); s += t; }
  return s;
}
constexpr uint32_t to_bf16(double v) {
  uint32_t sign = v < 0 ? 0x8000u : 0u;
  double a = v < 0 ? -v : v;
  if (a < 1e-12) return 0;
  int e = 0;
  while (a >= 2.0) { a /= 2; e++; }
  while (a < 1.0) { a *= 2; e--; }
  double m = a * 128.0;
  int mi = (int)m;
  double fr = m - mi;
  if (fr > 0.5 || (fr == 0.5 && (mi & 1))) mi++;
  if (mi == 256) { mi = 128; e++; }
  return sign | (uint32_t)((e + 127) << 7) | (uint32_t)(mi - 128);
}
struct Base { uint32_t v[448]; };
constexpr Base make_base() {
  Base b{};
  for (int m = 0; m < 448; m++) {
    int mm = m > 224 ? m - 448 : m;
    double ang = 2 * PI * mm / 448.0;
    b.v[m] = to_bf16(ccos(ang)) | (to_bf16(-csin(ang)) << 16);
  }
  return b;
}
constexpr Base base = make_base();
struct Row { uint32_t v[224]; };
constexpr Row make_row(int d) {
  Row r{};
  r.v[0] = 0x3f80u | ((d & 1) ? 0xbf800000u : 0x3f800000u);
  int m = 0;
  for (int c = 1; c < 224; c++) { m += d; if (m >= 448) m -= 448; r.v[c] = base.v[m]; }
  return r;
}
struct Table { Row r[448]; };
constexpr Table make_table() {
  Table t{};
  for (int d = 0; d < 448; d++) t.r[d] = make_row(d);
  return t;
}
struct Cs { double c[2048], s[2048]; };
constexpr Cs make_cs() {
  Cs t{};
  for (int m = 0; m <= 256; m++) {
    const double a = 2 * PI * m / 2048.0, c = ccos(a), s = csin(a);
    t.c[m] = c; t.s[m] = s;
    t.c[512 - m] = s; t.s[512 - m] = c;
  }
  for (int m = 513; m < 2048; m++) { t.c[m] = -t.s[m - 512]; t.s[m] = t.c[m - 512]; }
  return t;
}
constexpr Cs cs = make_cs();
struct Spec {
  uint32_t fo[2048], fot[2048];
  uint16_t t32[4096];
  uint32_t fe[2048];
  uint32_t tw[2048];
};
constexpr uint32_t blk(int h, int c, int a) { return to_bf16(h == c ? cs.c[a & 2047] : (h ? -cs.s[a & 2047] : cs.s[a & 2047])); }
constexpr Spec make_spec() {
  Spec t{};
  for (int row = 0; row < 64; row++)
    for (int col = 0; col < 64; col++) {
      const int c = row & 31, k2 = col & 31, n2 = 8 * ((c >> 1) & 3) + 2 * (c >> 3) + (c & 1), m = 64 * ((n2 * k2) & 31);
      const double v = (row >> 5) == (col >> 5) ? cs.c[m] : (row < 32 ? -cs.s[m] : cs.s[m]);
      t.t32[row * 64 + (((col >> 3) ^ (row & 7)) << 3) + (col & 7)] = (uint16_t)to_bf16(v);
    }
  for (int th = 0; th < 128; th++)
    for (int i = 0; i < 16; i++) {
      const int r = 8 * (th >> 5) + ((th & 31) >> 2), h = i & 1, c = i >> 3, m = 8 * ((i >> 1) & 3) + 2 * (th & 3);
      const int o = ((i >> 2) * 128 + th) * 4 + (i & 3);
      t.fe[o] = blk(h, c, 64 * m * r) | (blk(h, c, 64 * (m + 1) * r) << 16);
      t.fo[o] = blk(h, c, 32 * (2 * m + 1) * r) | (blk(h, c, 32 * (2 * m + 3) * r) << 16);
      t.fot[o] = blk(h, c, 32 * (2 * r + 1) * m) | (blk(h, c, 32 * (2 * r + 1) * (m + 1)) << 16);
      const int k1 = r + 32 * h, n2 = 8 * (th & 3) + 2 * ((i >> 1) & 3);
      t.tw[o] = blk(0, c, n2 * k1) | (blk(0, c, (n2 + 1) * k1) << 16);
    }
  return t;
}
}
}

__device__ __align__(1024) const tab::Table g_ctab = tab::make_table();
__device__ __align__(1024) const tab::Spec g_spec = tab::make_spec();

struct Scratch {
  uint32_t cnt_w[32];
  uint32_t cnt_x1[7 * 32];
  uint32_t cnt_y[7 * 32];
  uint32_t epoch[NCTA * 12 + 240 + 256];
  uint32_t gate[S_];
  uint4 x1t[113 * 1024];
  __nv_bfloat16 yt[D_ * S_];
  uint4 wt[114 * 1024];
  uint4 part[16 * 7 * 6 * 2 * 4 * 128];
};
static_assert(offsetof(Scratch, x1t) % 1024 == 0, "alignment");
__device__ __align__(1024) Scratch g_scratch;
#define TL(i)

namespace {

struct Params {
  Scratch* s;
  __nv_bfloat16* out;
  const __nv_bfloat16 *px, *w_r, *w_i, *gate_w, *pwg, *pwu, *pwd;
  const tab::Table* ctab;
  const tab::Spec* spec;
  CUtensorMap x, wg, wu, wd, ct, yt;
};

__device__ __forceinline__ uint32_t smem_u32(const void* p) { return (uint32_t)__cvta_generic_to_shared(p); }
__device__ __forceinline__ void mbar_init(uint32_t bar, uint32_t cnt) {
  asm volatile("mbarrier.init.shared::cta.b64 [%0], %1;" ::"r"(bar), "r"(cnt) : "memory");
}
__device__ __forceinline__ void mbar_expect_tx(uint32_t bar, uint32_t bytes) {
  asm volatile("mbarrier.arrive.expect_tx.shared::cta.b64 _, [%0], %1;" ::"r"(bar), "r"(bytes) : "memory");
}
__device__ __forceinline__ void mbar_arrive(uint32_t bar) {
  asm volatile("mbarrier.arrive.shared::cta.b64 _, [%0];" ::"r"(bar) : "memory");
}
__device__ __forceinline__ void mbar_arrive_cluster(uint32_t bar, uint32_t cta) {
  asm volatile("{\n.reg .b32 ra;\nmapa.shared::cluster.u32 ra, %0, %1;\n"
               "mbarrier.arrive.shared::cluster.b64 _, [ra];\n}" ::"r"(bar), "r"(cta) : "memory");
}
__device__ __forceinline__ void mbar_wait(uint32_t bar, uint32_t parity) {
  uint32_t ok, n = 0;
  do {
    asm volatile("{\n.reg .pred p;\nmbarrier.try_wait.parity.shared::cta.b64 p, [%1], %2;\nselp.u32 %0, 1, 0, p;\n}"
                 : "=r"(ok) : "r"(bar), "r"(parity) : "memory");
  } while (!ok && ++n < SPIN_LIMIT);
}
__device__ __forceinline__ void mbar_wait_cluster(uint32_t bar, uint32_t parity) {
  uint32_t ok, n = 0;
  do {
    asm volatile("{\n.reg .pred p;\nmbarrier.try_wait.parity.acquire.cluster.shared::cta.b64 p, [%1], %2;\nselp.u32 %0, 1, 0, p;\n}"
                 : "=r"(ok) : "r"(bar), "r"(parity) : "memory");
  } while (!ok && ++n < SPIN_LIMIT);
}
__device__ __forceinline__ void tma2d(uint32_t dst, const CUtensorMap* m, int c0, int c1, uint32_t bar) {
  asm volatile("cp.async.bulk.tensor.2d.shared::cluster.global.mbarrier::complete_tx::bytes [%0], [%1, {%3, %4}], [%2];"
               ::"r"(dst), "l"(m), "r"(bar), "r"(c0), "r"(c1) : "memory");
}
__device__ __forceinline__ void tma3d(uint32_t dst, const CUtensorMap* m, int c0, int c1, int c2, uint32_t bar) {
  asm volatile("cp.async.bulk.tensor.3d.shared::cluster.global.mbarrier::complete_tx::bytes [%0], [%1, {%3, %4, %5}], [%2];"
               ::"r"(dst), "l"(m), "r"(bar), "r"(c0), "r"(c1), "r"(c2) : "memory");
}
__device__ __forceinline__ void tma2d_mc(uint32_t dst, const CUtensorMap* m, int c0, int c1, uint32_t bar) {
  asm volatile("cp.async.bulk.tensor.2d.shared::cluster.global.mbarrier::complete_tx::bytes.multicast::cluster [%0], [%1, {%3, %4}], [%2], %5;"
               ::"r"(dst), "l"(m), "r"(bar), "r"(c0), "r"(c1), "h"((uint16_t)3) : "memory");
}
__device__ __forceinline__ void tma3d_mc(uint32_t dst, const CUtensorMap* m, int c0, int c1, int c2, uint32_t bar) {
  asm volatile("cp.async.bulk.tensor.3d.shared::cluster.global.mbarrier::complete_tx::bytes.multicast::cluster [%0], [%1, {%3, %4, %5}], [%2], %6;"
               ::"r"(dst), "l"(m), "r"(bar), "r"(c0), "r"(c1), "r"(c2), "h"((uint16_t)3) : "memory");
}
__device__ __forceinline__ void bulk_g2s(uint32_t dst, const void* src, uint32_t bytes, uint32_t bar) {
  asm volatile("cp.async.bulk.shared::cluster.global.mbarrier::complete_tx::bytes [%0], [%1], %2, [%3];"
               ::"r"(dst), "l"(src), "r"(bytes), "r"(bar) : "memory");
}
__device__ __forceinline__ void bulk_s2g(void* dst, uint32_t src, uint32_t bytes) {
  asm volatile("cp.async.bulk.global.shared::cta.bulk_group [%0], [%1], %2;" ::"l"(dst), "r"(src), "r"(bytes) : "memory");
}
__device__ __forceinline__ void prefetch_tmap(const CUtensorMap* m) {
  asm volatile("prefetch.tensormap [%0];" ::"l"(m) : "memory");
}
__device__ __forceinline__ void l2_prefetch(const void* p, uint32_t bytes) {
  asm volatile("cp.async.bulk.prefetch.L2.global [%0], %1;" ::"l"(p), "r"(bytes) : "memory");
}
__device__ __forceinline__ void wg_fence() { asm volatile("wgmma.fence.sync.aligned;" ::: "memory"); }
__device__ __forceinline__ void wg_commit() { asm volatile("wgmma.commit_group.sync.aligned;" ::: "memory"); }
template <int N> __device__ __forceinline__ void wg_wait() { asm volatile("wgmma.wait_group.sync.aligned %0;" ::"n"(N) : "memory"); }
template <int N> __device__ __forceinline__ void fence_regs(float (&d)[N]) {
#pragma unroll
  for (int i = 0; i < N; i++) asm volatile("" : "+f"(d[i])::"memory");
}
template <int N> __device__ __forceinline__ void fence_regs(uint32_t (&d)[N]) {
#pragma unroll
  for (int i = 0; i < N; i++) asm volatile("" : "+r"(d[i])::"memory");
}
__device__ __forceinline__ void bar_sync(int id, int n) { asm volatile("bar.sync %0, %1;" ::"r"(id), "r"(n) : "memory"); }
__device__ __forceinline__ void bar_arrive(int id, int n) { asm volatile("bar.arrive %0, %1;" ::"r"(id), "r"(n) : "memory"); }
__device__ __forceinline__ void fence_gpu() { asm volatile("fence.acq_rel.gpu;" ::: "memory"); }
__device__ __forceinline__ void fence_async() { asm volatile("fence.proxy.async;" ::: "memory"); }
__device__ __forceinline__ void fence_async_smem() { asm volatile("fence.proxy.async.shared::cta;" ::: "memory"); }
__device__ __forceinline__ void red_add(uint32_t* p, uint32_t v) {
  asm volatile("red.relaxed.gpu.global.add.u32 [%0], %1;" ::"l"(p), "r"(v) : "memory");
}
__device__ __forceinline__ uint32_t ld_relaxed(const uint32_t* p) {
  uint32_t v;
  asm volatile("ld.relaxed.gpu.global.u32 %0, [%1];" : "=r"(v) : "l"(p) : "memory");
  return v;
}
__device__ __forceinline__ void wait_counter(const uint32_t* p, uint32_t target) {
  uint32_t v, n = 0;
  while (true) {
    asm volatile("ld.acquire.gpu.global.u32 %0, [%1];" : "=r"(v) : "l"(p) : "memory");
    if ((int32_t)(v - target) >= 0 || ++n > SPIN_LIMIT) break;
  }
}
__device__ __forceinline__ uint4 ld_relaxed(const uint4* p) {
  uint4 v;
  asm volatile("ld.relaxed.gpu.global.v4.u32 {%0, %1, %2, %3}, [%4];" : "=r"(v.x), "=r"(v.y), "=r"(v.z), "=r"(v.w) : "l"(p) : "memory");
  return v;
}
__device__ __forceinline__ void st_relaxed(uint4* p, uint4 v) {
  asm volatile("st.relaxed.gpu.global.v4.u32 [%0], {%1, %2, %3, %4};" ::"l"(p), "r"(v.x), "r"(v.y), "r"(v.z), "r"(v.w) : "memory");
}
__device__ __forceinline__ void st_relaxed(uint32_t* p, uint32_t v) {
  asm volatile("st.relaxed.gpu.global.u32 [%0], %1;" ::"l"(p), "r"(v) : "memory");
}
__device__ __forceinline__ uint32_t pack2(float lo, float hi) {
  uint32_t r;
  asm("cvt.rn.bf16x2.f32 %0, %1, %2;" : "=r"(r) : "f"(hi), "f"(lo));
  return r;
}
__device__ __forceinline__ uint32_t mul2(uint32_t a, uint32_t b) {
  uint32_t r;
  asm("mul.rn.bf16x2 %0, %1, %2;" : "=r"(r) : "r"(a), "r"(b));
  return r;
}
__device__ __forceinline__ uint32_t fma2(uint32_t a, uint32_t b, uint32_t c) {
  uint32_t r;
  asm("fma.rn.bf16x2 %0, %1, %2, %3;" : "=r"(r) : "r"(a), "r"(b), "r"(c));
  return r;
}
__device__ __forceinline__ uint32_t add2(uint32_t a, uint32_t b) {
  uint32_t r;
  asm("add.rn.bf16x2 %0, %1, %2;" : "=r"(r) : "r"(a), "r"(b));
  return r;
}
__device__ __forceinline__ uint32_t sub2(uint32_t a, uint32_t b) {
  uint32_t r;
  asm("sub.rn.bf16x2 %0, %1, %2;" : "=r"(r) : "r"(a), "r"(b));
  return r;
}
__device__ __forceinline__ uint32_t fms2(uint32_t a, uint32_t b, uint32_t c) {
  uint32_t r;
  asm("{\n.reg .b32 n;\nneg.bf16x2 n, %3;\nfma.rn.bf16x2 %0, %1, %2, n;\n}" : "=r"(r) : "r"(a), "r"(b), "r"(c));
  return r;
}
__device__ __forceinline__ float bf_lo(uint32_t v) { return __uint_as_float(v << 16); }
__device__ __forceinline__ float bf_hi(uint32_t v) { return __uint_as_float(v & 0xffff0000u); }
__device__ __forceinline__ float bf_round(float v) { return bf_lo(pack2(v, 0.f)); }
__device__ __forceinline__ float tanh_fast(float v) {
  float r;
  asm("tanh.approx.f32 %0, %1;" : "=f"(r) : "f"(v));
  return r;
}
__device__ __forceinline__ uint64_t mk_desc(uint32_t addr, uint32_t lbo, uint32_t sbo, uint32_t mode) {
  return (uint64_t)((addr & 0x3FFFF) >> 4) | ((uint64_t)(lbo >> 4) << 16) | ((uint64_t)(sbo >> 4) << 32) | ((uint64_t)mode << 62);
}
__device__ __forceinline__ void stmatrix_x4(uint32_t addr, uint32_t r0, uint32_t r1, uint32_t r2, uint32_t r3) {
  asm volatile("stmatrix.sync.aligned.m8n8.x4.shared.b16 [%0], {%1, %2, %3, %4};" ::"r"(addr), "r"(r0), "r"(r1), "r"(r2), "r"(r3) : "memory");
}

template <int TA, int TB>
__device__ __forceinline__ void wgmma_ss_n256(float (&d)[128], uint64_t da, uint64_t db, int sd) {
  asm volatile("{\n.reg .pred p;\nsetp.ne.b32 p, %130, 0;\n"
      "wgmma.mma_async.sync.aligned.m64n256k16.f32.bf16.bf16 {"
      "%0, %1, %2, %3, %4, %5, %6, %7, %8, %9, %10, %11, %12, %13, %14, %15, %16, %17, %18, %19, %20, %21, %22, %23, "
      "%24, %25, %26, %27, %28, %29, %30, %31, %32, %33, %34, %35, %36, %37, %38, %39, %40, %41, %42, %43, %44, %45, "
      "%46, %47, %48, %49, %50, %51, %52, %53, %54, %55, %56, %57, %58, %59, %60, %61, %62, %63, %64, %65, %66, %67, "
      "%68, %69, %70, %71, %72, %73, %74, %75, %76, %77, %78, %79, %80, %81, %82, %83, %84, %85, %86, %87, %88, %89, "
      "%90, %91, %92, %93, %94, %95, %96, %97, %98, %99, %100, %101, %102, %103, %104, %105, %106, %107, %108, %109, "
      "%110, %111, %112, %113, %114, %115, %116, %117, %118, %119, %120, %121, %122, %123, %124, %125, %126, %127"
      "}, %128, %129, p, 1, 1, %131, %132;\n}\n"
      : "+f"(d[0]), "+f"(d[1]), "+f"(d[2]), "+f"(d[3]), "+f"(d[4]), "+f"(d[5]), "+f"(d[6]), "+f"(d[7]), "+f"(d[8]),
        "+f"(d[9]), "+f"(d[10]), "+f"(d[11]), "+f"(d[12]), "+f"(d[13]), "+f"(d[14]), "+f"(d[15]), "+f"(d[16]),
        "+f"(d[17]), "+f"(d[18]), "+f"(d[19]), "+f"(d[20]), "+f"(d[21]), "+f"(d[22]), "+f"(d[23]), "+f"(d[24]),
        "+f"(d[25]), "+f"(d[26]), "+f"(d[27]), "+f"(d[28]), "+f"(d[29]), "+f"(d[30]), "+f"(d[31]), "+f"(d[32]),
        "+f"(d[33]), "+f"(d[34]), "+f"(d[35]), "+f"(d[36]), "+f"(d[37]), "+f"(d[38]), "+f"(d[39]), "+f"(d[40]),
        "+f"(d[41]), "+f"(d[42]), "+f"(d[43]), "+f"(d[44]), "+f"(d[45]), "+f"(d[46]), "+f"(d[47]), "+f"(d[48]),
        "+f"(d[49]), "+f"(d[50]), "+f"(d[51]), "+f"(d[52]), "+f"(d[53]), "+f"(d[54]), "+f"(d[55]), "+f"(d[56]),
        "+f"(d[57]), "+f"(d[58]), "+f"(d[59]), "+f"(d[60]), "+f"(d[61]), "+f"(d[62]), "+f"(d[63]), "+f"(d[64]),
        "+f"(d[65]), "+f"(d[66]), "+f"(d[67]), "+f"(d[68]), "+f"(d[69]), "+f"(d[70]), "+f"(d[71]), "+f"(d[72]),
        "+f"(d[73]), "+f"(d[74]), "+f"(d[75]), "+f"(d[76]), "+f"(d[77]), "+f"(d[78]), "+f"(d[79]), "+f"(d[80]),
        "+f"(d[81]), "+f"(d[82]), "+f"(d[83]), "+f"(d[84]), "+f"(d[85]), "+f"(d[86]), "+f"(d[87]), "+f"(d[88]),
        "+f"(d[89]), "+f"(d[90]), "+f"(d[91]), "+f"(d[92]), "+f"(d[93]), "+f"(d[94]), "+f"(d[95]), "+f"(d[96]),
        "+f"(d[97]), "+f"(d[98]), "+f"(d[99]), "+f"(d[100]), "+f"(d[101]), "+f"(d[102]), "+f"(d[103]), "+f"(d[104]),
        "+f"(d[105]), "+f"(d[106]), "+f"(d[107]), "+f"(d[108]), "+f"(d[109]), "+f"(d[110]), "+f"(d[111]),
        "+f"(d[112]), "+f"(d[113]), "+f"(d[114]), "+f"(d[115]), "+f"(d[116]), "+f"(d[117]), "+f"(d[118]),
        "+f"(d[119]), "+f"(d[120]), "+f"(d[121]), "+f"(d[122]), "+f"(d[123]), "+f"(d[124]), "+f"(d[125]),
        "+f"(d[126]), "+f"(d[127])
      : "l"(da), "l"(db), "r"(sd), "n"(TA), "n"(TB));
}
template <int TA, int TB>
__device__ __forceinline__ void wgmma_ss_n128(float (&d)[64], uint64_t da, uint64_t db, int sd) {
  asm volatile("{\n.reg .pred p;\nsetp.ne.b32 p, %66, 0;\n"
      "wgmma.mma_async.sync.aligned.m64n128k16.f32.bf16.bf16 {"
      "%0, %1, %2, %3, %4, %5, %6, %7, %8, %9, %10, %11, %12, %13, %14, %15, %16, %17, %18, %19, %20, %21, %22, %23, "
      "%24, %25, %26, %27, %28, %29, %30, %31, %32, %33, %34, %35, %36, %37, %38, %39, %40, %41, %42, %43, %44, %45, "
      "%46, %47, %48, %49, %50, %51, %52, %53, %54, %55, %56, %57, %58, %59, %60, %61, %62, %63"
      "}, %64, %65, p, 1, 1, %67, %68;\n}\n"
      : "+f"(d[0]), "+f"(d[1]), "+f"(d[2]), "+f"(d[3]), "+f"(d[4]), "+f"(d[5]), "+f"(d[6]), "+f"(d[7]), "+f"(d[8]),
        "+f"(d[9]), "+f"(d[10]), "+f"(d[11]), "+f"(d[12]), "+f"(d[13]), "+f"(d[14]), "+f"(d[15]), "+f"(d[16]),
        "+f"(d[17]), "+f"(d[18]), "+f"(d[19]), "+f"(d[20]), "+f"(d[21]), "+f"(d[22]), "+f"(d[23]), "+f"(d[24]),
        "+f"(d[25]), "+f"(d[26]), "+f"(d[27]), "+f"(d[28]), "+f"(d[29]), "+f"(d[30]), "+f"(d[31]), "+f"(d[32]),
        "+f"(d[33]), "+f"(d[34]), "+f"(d[35]), "+f"(d[36]), "+f"(d[37]), "+f"(d[38]), "+f"(d[39]), "+f"(d[40]),
        "+f"(d[41]), "+f"(d[42]), "+f"(d[43]), "+f"(d[44]), "+f"(d[45]), "+f"(d[46]), "+f"(d[47]), "+f"(d[48]),
        "+f"(d[49]), "+f"(d[50]), "+f"(d[51]), "+f"(d[52]), "+f"(d[53]), "+f"(d[54]), "+f"(d[55]), "+f"(d[56]),
        "+f"(d[57]), "+f"(d[58]), "+f"(d[59]), "+f"(d[60]), "+f"(d[61]), "+f"(d[62]), "+f"(d[63])
      : "l"(da), "l"(db), "r"(sd), "n"(TA), "n"(TB));
}
template <int TA, int TB>
__device__ __forceinline__ void wgmma_ss_n64(float (&d)[32], uint64_t da, uint64_t db, int sd) {
  asm volatile("{\n.reg .pred p;\nsetp.ne.b32 p, %34, 0;\n"
      "wgmma.mma_async.sync.aligned.m64n64k16.f32.bf16.bf16 {"
      "%0, %1, %2, %3, %4, %5, %6, %7, %8, %9, %10, %11, %12, %13, %14, %15, %16, %17, %18, %19, %20, %21, %22, %23, "
      "%24, %25, %26, %27, %28, %29, %30, %31"
      "}, %32, %33, p, 1, 1, %35, %36;\n}\n"
      : "+f"(d[0]), "+f"(d[1]), "+f"(d[2]), "+f"(d[3]), "+f"(d[4]), "+f"(d[5]), "+f"(d[6]), "+f"(d[7]), "+f"(d[8]),
        "+f"(d[9]), "+f"(d[10]), "+f"(d[11]), "+f"(d[12]), "+f"(d[13]), "+f"(d[14]), "+f"(d[15]), "+f"(d[16]),
        "+f"(d[17]), "+f"(d[18]), "+f"(d[19]), "+f"(d[20]), "+f"(d[21]), "+f"(d[22]), "+f"(d[23]), "+f"(d[24]),
        "+f"(d[25]), "+f"(d[26]), "+f"(d[27]), "+f"(d[28]), "+f"(d[29]), "+f"(d[30]), "+f"(d[31])
      : "l"(da), "l"(db), "r"(sd), "n"(TA), "n"(TB));
}
template <int SA, int TB>
__device__ __forceinline__ void wgmma_rs_n64(float (&d)[32], uint32_t a0, uint32_t a1, uint32_t a2, uint32_t a3, uint64_t db, int sd) {
  asm volatile("{\n.reg .pred p;\nsetp.ne.b32 p, %37, 0;\n"
      "wgmma.mma_async.sync.aligned.m64n64k16.f32.bf16.bf16 {"
      "%0, %1, %2, %3, %4, %5, %6, %7, %8, %9, %10, %11, %12, %13, %14, %15, %16, %17, %18, %19, %20, %21, %22, %23, "
      "%24, %25, %26, %27, %28, %29, %30, %31"
      "}, {%32, %33, %34, %35}, %36, p, %38, 1, %39;\n}\n"
      : "+f"(d[0]), "+f"(d[1]), "+f"(d[2]), "+f"(d[3]), "+f"(d[4]), "+f"(d[5]), "+f"(d[6]), "+f"(d[7]), "+f"(d[8]),
        "+f"(d[9]), "+f"(d[10]), "+f"(d[11]), "+f"(d[12]), "+f"(d[13]), "+f"(d[14]), "+f"(d[15]), "+f"(d[16]),
        "+f"(d[17]), "+f"(d[18]), "+f"(d[19]), "+f"(d[20]), "+f"(d[21]), "+f"(d[22]), "+f"(d[23]), "+f"(d[24]),
        "+f"(d[25]), "+f"(d[26]), "+f"(d[27]), "+f"(d[28]), "+f"(d[29]), "+f"(d[30]), "+f"(d[31])
      : "r"(a0), "r"(a1), "r"(a2), "r"(a3), "l"(db), "r"(sd), "n"(SA), "n"(TB));
}

__device__ __forceinline__ uint32_t BAR_FULL(uint32_t sb, int i) { return sb + SM_BAR + 8 * i; }
__device__ __forceinline__ uint32_t BAR_EMPTY(uint32_t sb, int i) { return sb + SM_BAR + 64 + 8 * i; }
__device__ __forceinline__ uint32_t BAR_X(uint32_t sb, int i) { return sb + SM_BAR + 128 + 8 * i; }
__device__ __forceinline__ uint32_t BAR_Y(uint32_t sb, int i) { return sb + SM_BAR + 192 + 8 * i; }
__device__ __forceinline__ uint32_t BAR_XFREE(uint32_t sb) { return sb + SM_BAR + 256; }

#define CMASK 0x194u
#define XORDER 0, 1, 11, 2, 3, 12, 13, 4, 5, 14, 6, 15, 16
#define XSPREAD 2
#define PFAT 3
#define SKEW 3
#define GL1 0
#define GS0 2
#define GL2 4
#define GS1 5
constexpr int Q_G1B = 18, Q_G2 = 32, Q_P3 = 46, Q_END = 50;

struct Ring {
  uint32_t slot, phase;
  __device__ __forceinline__ void next() { if (++slot == NSTAGE) { slot = 0; phase ^= 1; } }
};

__device__ __forceinline__ void release_slot(uint32_t sb, uint32_t slot, int tid, int times) {
  if (tid < 2 * times) mbar_arrive_cluster(BAR_EMPTY(sb, slot), tid & 1);
}

__device__ __forceinline__ void ffn_consumer(uint32_t sb, const uint8_t* smem, const Params& p, int bid, int wg, int tid, int mt, int jj) {
  const int lane = tid & 31, warp = tid >> 5, q = lane & 3, r0 = 16 * warp + (lane >> 2);
  uint32_t* const my_epoch = &p.s->epoch[blockIdx.x * 12 + (threadIdx.x >> 5)];
  const uint32_t epoch = ld_relaxed(my_epoch) + 1;
  Ring rg{0, 0};
  uint32_t u[64];
  float acc[128];
  uint32_t prev = 0, cmask = CMASK;
  int st = 0;
  auto g1_stage = [&](uint32_t slot, int s) {
    const uint64_t da = mk_desc(sb + SM_X + (s >> 1) * 16384 + wg * 8192 + (s & 1) * 64, 16, 1024, 1);
    const uint64_t db = mk_desc(sb + SM_RING + slot * STAGE_BYTES, 4096, 1024, 1);
    wg_fence();
    wgmma_ss_n256<0, 1>(acc, da, db, s != 0);
    wgmma_ss_n256<0, 1>(acc, da + 2, db + 128, 1);
    wg_commit();
  };
  if (wg == 1) {
    float ap[64];
    constexpr int QX = 32 - __builtin_clz(CMASK);
    constexpr int NPRE = QX + XSPREAD;
    uint4* const x1dst = p.s->x1t + ((64 * jj + r0 + 8) >> 2) * 1024 + (r0 & 3) * 128 + 8 * mt + (q ^ (mt & 3));
    const int x1lo = 64 * jj + r0 == 1 ? 110 * 1024 - 128 : -2048;
#pragma unroll
    for (int qi = 0; qi < NPRE; qi++) {
      const int slot = qi % NSTAGE, nc = __builtin_popcount(CMASK & ((1u << qi) - 1));
      if (qi == 0) TL(60);
      mbar_wait(BAR_FULL(sb, slot), (qi / NSTAGE) & 1);
      if (qi == 0) TL(61);
      if ((CMASK >> qi) & 1) {
#pragma unroll
        for (int kb = 2 * nc; kb < 2 * nc + 2 && kb < 7; kb++) {
          const uint64_t da = mk_desc(sb + SM_RING + slot * STAGE_BYTES + (kb & 1) * 8192, 8192, 1024, 1);
          const uint64_t db = mk_desc(sb + SM_X + kb * 16384, 16, 1024, 1);
          mbar_wait(BAR_X(sb, kb), 0);
          TL(16 + kb);
          wg_fence();
#pragma unroll
          for (int kk = 0; kk < 4; kk++) wgmma_ss_n128<1, 0>(ap, da + kk * 128, db + kk * 2, (kb | kk) != 0);
          wg_commit();
        }
      } else {
        if (((qi - nc) & 1) == 0 && qi - nc >= 4 * nc) mbar_wait(BAR_X(sb, (qi - nc) >> 1), 0);
        TL(32 + qi - nc);
        g1_stage(slot, qi - nc);
      }
      if (qi > 0) {
        wg_wait<1>();
        release_slot(sb, (qi - 1) % NSTAGE, tid, ((CMASK >> (qi - 1)) & 1) ? 2 : 1);
      }
      if (qi >= QX) {
        if (qi == QX) { fence_regs(ap); TL(2); }
#pragma unroll
        for (int t = (qi - QX) * (4 / XSPREAD); t < (qi - QX + 1) * (4 / XSPREAD); t++)
#pragma unroll
        for (int h = 0; h < 2; h++)
          x1dst[(h ? 0 : x1lo) + 512 * (t & 1) + 4 * (t >> 1)] = make_uint4(pack2(ap[16 * t + 2 * h], ap[16 * t + 2 * h + 1]), pack2(ap[16 * t + 4 + 2 * h], ap[16 * t + 5 + 2 * h]),
                                             pack2(ap[16 * t + 8 + 2 * h], ap[16 * t + 9 + 2 * h]), pack2(ap[16 * t + 12 + 2 * h], ap[16 * t + 13 + 2 * h]));
      }
    }
    bar_arrive(7, 160);
    st = NPRE - 4; cmask = 0; prev = (NPRE - 1) % NSTAGE;
    rg.slot = NPRE % NSTAGE; rg.phase = (NPRE / NSTAGE) & 1;
  }
#pragma unroll 1
  for (int pass = 0; pass < 2; pass++) {
#pragma unroll 1
    for (; st < 14; st++) {
      while (cmask & 1) { cmask >>= 1; rg.next(); }
      cmask >>= 1;
      if (pass == 0 && (st & 1) == 0) mbar_wait(BAR_X(sb, st >> 1), 0);
      if (st == 14 - SKEW && wg == 1) bar_sync(9 + pass, 256);
      mbar_wait(BAR_FULL(sb, rg.slot), rg.phase);
      TL(32 + 14 * pass + st);
      g1_stage(rg.slot, st);
      wg_wait<1>();
      if (st > 0) release_slot(sb, prev, tid, 1);
      prev = rg.slot;
      rg.next();
    }
    st = 0;
    if (wg == 0) bar_arrive(9 + pass, 256);
    wg_wait<0>();
    fence_regs(acc);
    release_slot(sb, prev, tid, 1);
    if (pass == 1 && tid == 0) mbar_arrive(BAR_XFREE(sb));
    TL(3 + 2 * pass);
#pragma unroll
    for (int i = 0; i < 32; i++) {
      const float g0 = 0.5f * acc[2 * i], g1 = 0.5f * acc[2 * i + 1];
      const float s0 = fmaf(g0, tanh_fast(g0), g0), s1 = fmaf(g1, tanh_fast(g1), g1);
      u[32 + i] = pack2(s0 * acc[64 + 2 * i], s1 * acc[64 + 2 * i + 1]);
    }
    if (pass == 0) {
#pragma unroll
      for (int i = 0; i < 32; i++) u[i] = u[32 + i];
    }
    TL(4 + 2 * pass);
  }
  fence_regs(u);
  float accA[32], accB[32];
  rg.slot = Q_G2 % NSTAGE; rg.phase = (Q_G2 / NSTAGE) & 1;
  auto stage = [&](float (&acc)[32], int st) {
    mbar_wait(BAR_FULL(sb, rg.slot), rg.phase);
    const uint64_t db = mk_desc(sb + SM_RING + rg.slot * STAGE_BYTES, 8192, 1024, 1);
    wg_fence();
#pragma unroll
    for (int kk = 0; kk < 8; kk++) {
      const uint32_t* a = u + 32 * st + 4 * kk;
      wgmma_rs_n64<1, 1>(acc, a[0], a[1], a[2], a[3], db + kk * 128, (st | kk) != 0);
    }
    wg_commit();
  };
  auto retire = [&](bool rel) {
    wg_wait<1>();
    if (rel) release_slot(sb, prev, tid, 1);
    prev = rg.slot;
    rg.next();
  };
  const uint32_t par = epoch & 1;
  auto put = [&](float (&acc)[32], int c) {
    fence_regs(acc);
    int o = jj + 1 + c;
    if (o >= 7) o -= 7;
    uint4* dst = p.s->part + ((((mt * 7 + o) * 6 + c) * 2 + wg) * 4) * 128 + tid;
#pragma unroll
    for (int v = 0; v < 4; v++) {
      const float* a = acc + 8 * v;
      st_relaxed(dst + v * 128, make_uint4((pack2(a[0], a[1]) & ~1u) | par, pack2(a[2], a[3]), pack2(a[4], a[5]), pack2(a[6], a[7])));
    }
  };
  const uint4* const src = p.s->part + (((mt * 7 + jj) * 6 * 2 + wg) * 4) * 128 + tid;
  auto gload = [&](uint4 (&pv)[8], int c) {
#pragma unroll
    for (int i = 0; i < 8; i++) pv[i] = ld_relaxed(src + ((2 * c + (i >> 2)) * 8 + (i & 3)) * 128);
  };
  auto gsum = [&](uint4 (&pv)[8], int c) {
#pragma unroll 1
    for (uint32_t n = 0; n < SPIN_LIMIT; n++) {
      uint32_t bad = 0;
#pragma unroll
      for (int i = 0; i < 8; i++) bad |= pv[i].x ^ par;
      if (!__any_sync(0xffffffffu, bad & 1)) break;
      gload(pv, c);
    }
    TL(24 + c);
#pragma unroll
    for (int i = 0; i < 8; i++) {
      const float t[8] = {bf_lo(pv[i].x), bf_hi(pv[i].x), bf_lo(pv[i].y), bf_hi(pv[i].y), bf_lo(pv[i].z), bf_hi(pv[i].z), bf_lo(pv[i].w), bf_hi(pv[i].w)};
#pragma unroll
      for (int k = 0; k < 8; k++) accA[8 * (i & 3) + k] += t[k];
    }
  };
  uint4 pv0[8], pv1[8], pv2[8];
  const int row = 128 * mt + 64 * wg + r0;
  uint32_t gt0, gt1;
#pragma unroll
  for (int c2 = 0; c2 < 4; c2++) {
    stage(accA, 0);
    retire(c2 == 1 || c2 == 2);
    stage(accA, 1);
    if (c2 == 3) TL(27);
    if (c2 > 0) put(accB, 2 * c2 - 1);
    TL(7 + c2);
    if (c2 == 3) break;
    retire(true);
    stage(accB, 0);
    retire(true);
    stage(accB, 1);
    put(accA, 2 * c2);
    if (c2 == 2) { gload(pv0, 0); gt0 = ld_relaxed(&p.s->gate[row]); gt1 = ld_relaxed(&p.s->gate[row + 8]); }
    retire(true);
  }
#pragma unroll
  for (int kb = 0; kb < 7; kb++) {
    constexpr int slot0 = Q_P3 % NSTAGE;
    const int slot = (slot0 + (kb >> 1)) % NSTAGE;
    if ((kb & 1) == 0) mbar_wait(BAR_FULL(sb, slot), ((Q_P3 + (kb >> 1)) / NSTAGE) & 1);
    mbar_wait(BAR_Y(sb, kb), 0);
    const uint64_t da = mk_desc(sb + SM_X + kb * 16384 + wg * 8192, 8192, 1024, 1);
    const uint64_t db = mk_desc(sb + SM_RING + slot * STAGE_BYTES + (kb & 1) * 8192, 16, 1024, 1);
    wg_fence();
#pragma unroll
    for (int kk = 0; kk < 4; kk++) wgmma_ss_n64<1, 0>(accB, da + kk * 128, db + kk * 2, (kb | kk) != 0);
    wg_commit();
    if (kb == GL1) gload(pv1, 1);
    if (kb == 1) { wg_wait<2>(); fence_regs(accA); TL(15); }
    if (kb == GS0) gsum(pv0, 0);
    if (kb == GL2) gload(pv2, 2);
    if (kb == GS1) gsum(pv1, 1);
  }
  TL(11);
  for (uint32_t n = 0; (((gt0 ^ epoch) | (gt1 ^ epoch)) & 0xffffu) && n < SPIN_LIMIT; n++) {
    gt0 = ld_relaxed(&p.s->gate[row]); gt1 = ld_relaxed(&p.s->gate[row + 8]);
  }
  gsum(pv2, 2);
  const float ga0 = bf_hi(gt0), ga1 = bf_hi(gt1);
  TL(12);
  wg_wait<0>();
  fence_regs(accB);
  TL(13);
  const float gb0 = bf_round(1.f - ga0), gb1 = bf_round(1.f - ga1);
  const float gs0 = ga0 * (2.f / (float)(S_ * D_)), gs1 = ga1 * (2.f / (float)(S_ * D_));
  uint4* const o = reinterpret_cast<uint4*>(p.out + (size_t)row * D_ + 64 * jj + 8 * q);
#pragma unroll
  for (int h = 0; h < 2; h++) {
    const float gs = h ? gs1 : gs0, gb = h ? gb1 : gb0;
#pragma unroll
    for (int k = 0; k < 2; k++) {
      uint32_t w[4];
#pragma unroll
      for (int j = 0; j < 4; j++) {
        const int i = 16 * k + 4 * j + 2 * h;
        w[j] = pack2(fmaf(gs, accB[i], gb * accA[i]), fmaf(gs, accB[i + 1], gb * accA[i + 1]));
      }
      const bool o1 = q & 1, o2 = q & 2;
      uint32_t a = __shfl_xor_sync(0xffffffffu, o1 ? w[0] : w[1], 1), b = __shfl_xor_sync(0xffffffffu, o1 ? w[2] : w[3], 1);
      if (o1) { w[0] = a; w[2] = b; } else { w[1] = a; w[3] = b; }
      a = __shfl_xor_sync(0xffffffffu, o2 ? w[0] : w[2], 2); b = __shfl_xor_sync(0xffffffffu, o2 ? w[1] : w[3], 2);
      if (o2) { w[0] = a; w[1] = b; } else { w[2] = a; w[3] = b; }
      o[h * D_ + 4 * k] = make_uint4(w[0], w[1], w[2], w[3]);
    }
  }
  if (lane == 0) *my_epoch = epoch;
  TL(14);
}

__device__ __forceinline__ void ring_issue(uint32_t sb, const Params& p, int qi, uint32_t slot, bool wait, uint32_t phase, int jj, uint32_t rank) {
  const CUtensorMap* m;
  int c0, c1, c2 = 0;
  bool half = false, is3d = false;
  if (qi < Q_G2) {
    const int nc = __popc(CMASK & ((1u << qi) - 1));
    if ((CMASK >> qi) & 1) {
      m = &p.ct; c0 = 64 * jj; c1 = 128 * nc + 64 * rank; half = nc == 3;
    } else {
      const int pass = qi >= Q_G1B;
      m = rank ? &p.wu : &p.wg; c0 = 0; c1 = 32 * (qi - nc - 14 * pass); c2 = 4 * jj + 2 * pass; is3d = true;
    }
  } else if (qi < Q_P3) {
    int o = jj + 1 + ((qi - Q_G2) >> 1);
    if (o >= 7) o -= 7;
    m = &p.wd; c0 = 64 * o; c1 = 256 * jj + 128 * (qi & 1) + 64 * rank;
  } else {
    m = &p.ct; c0 = 128 * (qi - Q_P3) + 64 * rank; c1 = 64 * jj; half = qi == Q_END - 1;
  }
  const uint32_t bar = BAR_FULL(sb, slot);
  const uint32_t dst = sb + SM_RING + slot * STAGE_BYTES + rank * 8192;
  if (wait) mbar_wait_cluster(BAR_EMPTY(sb, slot), phase);
  mbar_expect_tx(bar, half ? 8192 : 16384);
  if (is3d) tma3d_mc(dst, m, c0, c1, c2, bar);
  else if (!(half && rank)) tma2d_mc(dst, m, c0, c1, bar);
}

__device__ __forceinline__ void ffn_producer(uint32_t sb, const uint8_t* smem, int bid, const Params& p, int warp, int lane, int mt, int jj, uint32_t rank) {
  if (warp < 2) {
    if (lane == 0) {
      uint32_t slot = warp, phase = 0;
#pragma unroll 1
      for (int qi = NSTAGE + warp; qi < Q_END; qi += 2) {
        ring_issue(sb, p, qi, slot, true, phase, jj, rank);
        TL(10 + qi);
        slot += 2;
        if (slot >= NSTAGE) { slot -= NSTAGE; phase ^= 1; }
      }
    }
  } else {
    const int wg = warp - 2;
    if (wg == 0) {
      if (lane == 0) { prefetch_tmap(&p.wd); prefetch_tmap(&p.yt); }
      uint32_t* const my_epoch = &p.s->epoch[blockIdx.x * 12 + 10];
      const uint32_t epoch = ld_relaxed(my_epoch) + 1;
      {
        const uint4* gw4 = reinterpret_cast<const uint4*>(p.gate_w);
        const uint4 ga = __ldg(gw4 + lane), gb = lane < 24 ? __ldg(gw4 + 32 + lane) : make_uint4(0, 0, 0, 0);
        if (lane < 7) mbar_wait(BAR_X(sb, lane), 0);
        __syncwarp();
        float mine = 0.f;
#pragma unroll 1
        for (int u = 0; u < 19; u++) {
          const int r = min(19 * jj + u, 127);
          const uint8_t* xr = smem + SM_X + (lane >> 3) * 16384 + r * 128 + (((lane ^ r) & 7) << 4);
          const uint4 xa = *reinterpret_cast<const uint4*>(xr);
          const uint4 xb = lane < 24 ? *reinterpret_cast<const uint4*>(xr + 65536) : make_uint4(0, 0, 0, 0);
          float s = 0.f;
          auto dot2 = [&](uint32_t a, uint32_t b) {
            const uint32_t pr = mul2(a, b);
            s += bf_lo(pr) + bf_hi(pr);
          };
          dot2(xa.x, ga.x); dot2(xa.y, ga.y); dot2(xa.z, ga.z); dot2(xa.w, ga.w);
          dot2(xb.x, gb.x); dot2(xb.y, gb.y); dot2(xb.z, gb.z); dot2(xb.w, gb.w);
#pragma unroll
          for (int o = 16; o > 0; o >>= 1) s += __shfl_xor_sync(0xffffffffu, s, o);
          if (lane == u) mine = s;
        }
        if (lane < 19 && 19 * jj + lane < 128)
          st_relaxed(&p.s->gate[128 * mt + 19 * jj + lane], pack2(0.f, 1.f / (1.f + __expf(-bf_round(mine)))) | (epoch & 0xffffu));
      }
      TL(9);
      mbar_wait(BAR_XFREE(sb), 0);
      TL(3);
      bool todo = lane < 7;
      uint32_t n = 0;
      while (__any_sync(0xffffffffu, todo)) {
        if (todo) {
          uint32_t v;
          asm volatile("ld.acquire.gpu.global.u32 %0, [%1];" : "=r"(v) : "l"(&p.s->cnt_y[lane * 32]) : "memory");
          if ((int32_t)(v - epoch * (lane ? 16 : 17)) >= 0 || ++n > SPIN_LIMIT) {
            mbar_expect_tx(BAR_Y(sb, lane), 16384);
            tma3d(sb + SM_X + lane * 16384, &p.yt, 0, 64 * lane, 2 * mt, BAR_Y(sb, lane));
            todo = false;
          }
        }
      }
      TL(4);
      if (lane == 0) *my_epoch = epoch;
    } else {
      mbar_wait(BAR_X(sb, PFAT), 0);
      if (lane < 6) {
        int row = 176 + 3 * bid + (lane >> 1);
        if (row >= D_) row -= D_;
        l2_prefetch(((lane & 1) ? p.pwu : p.pwg) + row * F_, F_ * 2);
      }
      TL(2);
      bar_sync(7, 160);
      if (lane == 0) { fence_gpu(); red_add(&p.s->cnt_x1[jj * 32], 1); l2_prefetch(p.pwd + bid * 16 * D_, 32 * D_); }
      TL(3);
    }
  }
}

__device__ __forceinline__ void spectral_cta(uint32_t sb, uint8_t* smem, const Params& p, int sc, int wg) {
  const int t384 = threadIdx.x, lane = t384 & 31, warp12 = t384 >> 5, tid = t384 & 127;
  const int warp = tid >> 5, q = lane & 3;
  const int sl0 = 6 * sc + min(sc, 8), nsl = sc < 8 ? 7 : 6;
  if (t384 == 320) {
#pragma unroll 1
    for (int i = 0; i < nsl; i++) {
      mbar_expect_tx(BAR_X(sb, i), 2 * SLAB_BYTES);
      const int row = 128 * ((sl0 + i) >> 3) + 8 * ((sl0 + i) & 7);
      const uint32_t dst = sb + SP_Z + 2 * i * SLAB_BYTES;
      bulk_g2s(dst, p.w_r + row * DF_, SLAB_BYTES / 2, BAR_X(sb, i));
      bulk_g2s(dst + SLAB_BYTES / 2, p.w_r + (row + 64) * DF_, SLAB_BYTES / 2, BAR_X(sb, i));
      bulk_g2s(dst + SLAB_BYTES, p.w_i + row * DF_, SLAB_BYTES / 2, BAR_X(sb, i));
      bulk_g2s(dst + 3 * SLAB_BYTES / 2, p.w_i + (row + 64) * DF_, SLAB_BYTES / 2, BAR_X(sb, i));
    }
    if (sc < 19) {
      mbar_expect_tx(BAR_Y(sb, 6), 24576);
      bulk_g2s(sb + SP_TW, p.spec, 24576, BAR_Y(sb, 6));
    }
  }
  uint32_t* const my_epoch = &p.s->epoch[blockIdx.x * 12 + warp12];
  const uint32_t epoch = ld_relaxed(my_epoch) + 1;
  uint32_t fe[16], tw[16];
#pragma unroll
  for (int i = 0; i < 4; i++) {
    const uint4 a = __ldg(reinterpret_cast<const uint4*>(p.spec->fe) + i * 128 + tid);
    const uint4 b = __ldg(reinterpret_cast<const uint4*>(p.spec->tw) + i * 128 + tid);
    fe[4 * i] = a.x; fe[4 * i + 1] = a.y; fe[4 * i + 2] = a.z; fe[4 * i + 3] = a.w;
    tw[4 * i] = b.x; tw[4 * i + 1] = b.y; tw[4 * i + 2] = b.z; tw[4 * i + 3] = b.w;
  }
  __syncwarp();
  asm volatile("barrier.cluster.wait.acquire.aligned;" ::: "memory");
#pragma unroll 2
  for (int un = wg; un < 8 * nsl; un += 3) {
    const int i = un >> 3, sl = sl0 + i, pr = 16 * (un & 7) + 4 * (lane >> 3) + warp, r = lane & 7;
    mbar_wait(BAR_X(sb, i), 0);
    if (pr < 113) {
      const uint16_t* w = reinterpret_cast<const uint16_t*>(smem + SP_Z + 2 * i * SLAB_BYTES) + r * DF_ + 2 * pr;
      const uint32_t m = pr < 112 ? 0xffffffffu : 0u;
      p.s->wt[pr * 1024 + sl * 8 + (r ^ ((sl >> 2) & 6))] =
          make_uint4(w[0] | ((uint32_t)w[8 * DF_] << 16), w[16 * DF_] | ((uint32_t)w[24 * DF_] << 16),
                     (w[1] | ((uint32_t)w[8 * DF_ + 1] << 16)) & m, (w[16 * DF_ + 1] | ((uint32_t)w[24 * DF_ + 1] << 16)) & m);
    }
  }
  __syncthreads();
  if (t384 == 352) { fence_gpu(); red_add(&p.s->cnt_w[0], 1); }
  TL(1);
  if (sc == 19) return;
  const int nrnd = (sc == 18 && wg == 2) ? 1 : 2;
  if (tid == 32) {
    wait_counter(&p.s->cnt_w[0], epoch * NSPEC);
    fence_async();
    for (int rnd = 0; rnd < nrnd; rnd++) {
      const int item = wg + 3 * rnd;
      mbar_expect_tx(BAR_Y(sb, item), 16384);
      bulk_g2s(sb + SP_W + item * 16384, p.s->wt + (6 * sc + item) * 1024, 16384, BAR_Y(sb, item));
    }
  } else if (tid == 0) {
#pragma unroll 1
    for (int rnd = 0; rnd < nrnd; rnd++) {
      const int item = wg + 3 * rnd, pr = 6 * sc + item;
      wait_counter(&p.s->cnt_x1[(pr < 112 ? pr >> 4 : 0) * 32], epoch * 16);
      fence_async();
      const uint32_t bar = BAR_FULL(sb, item), z = sb + SP_Z + item * 16384;
      mbar_expect_tx(bar, 16384);
      bulk_g2s(z, p.s->x1t + pr * 1024, 16384, bar);
    }
  }
  __syncwarp();
  fence_regs(fe); fence_regs(tw);
  mbar_wait(BAR_Y(sb, 6), 0);
  TL(3);
  const uint64_t dT_n = mk_desc(sb + SP_T, 8192, 1024, 1);
#pragma unroll 1
  for (int rnd = 0; rnd < nrnd; rnd++) {
    const int item = wg + 3 * rnd, pr = 6 * sc + item;
    const uint32_t z = sb + SP_Z + item * 16384;
    uint32_t fa[16], fb[16];
    auto load_frag = [&](int off) {
#pragma unroll
      for (int i = 0; i < 4; i++) {
        const uint4 a = *reinterpret_cast<const uint4*>(smem + SP_TW + off + i * 2048 + tid * 16);
        fa[4 * i] = a.x; fa[4 * i + 1] = a.y; fa[4 * i + 2] = a.z; fa[4 * i + 3] = a.w;
      }
      fence_regs(fa);
    };
    load_frag(0);
    mbar_wait(BAR_FULL(sb, item), 0);
    TL(4 + 8 * rnd);
    if (rnd == 0 && wg > 0) bar_sync(3 + wg, 256);
    float aR[32], aI[32];
    {
      const uint64_t de = mk_desc(z, 4096, 512, 2);
      wg_fence();
#pragma unroll
      for (int kk = 0; kk < 4; kk++) {
        wgmma_rs_n64<1, 1>(aR, fe[4 * kk], fe[4 * kk + 1], fe[4 * kk + 2], fe[4 * kk + 3], de + kk * 64, kk != 0);
        wgmma_rs_n64<1, 1>(aI, fa[4 * kk], fa[4 * kk + 1], fa[4 * kk + 2], fa[4 * kk + 3], de + 512 + kk * 64, kk != 0);
      }
      wg_commit();
      if (rnd == 0 && wg < 2) bar_arrive(4 + wg, 256);
      wg_wait<0>();
      fence_regs(aR); fence_regs(aI);
    }
    TL(5 + 8 * rnd);
#pragma unroll
    for (int v = 0; v < 8; v++) {
      uint32_t* f = (v < 4 ? fa : fb) + 2 * (v & 3);
      const uint32_t* t = tw + 2 * (v & 3);
      const float *e = aR + 4 * v, *o = aI + 4 * v;
      const uint32_t er = pack2(e[0], e[1]), ei = pack2(e[2], e[3]), qr = pack2(o[0], o[1]), qi = pack2(o[2], o[3]);
      const uint32_t u0r = add2(er, qr), u0i = add2(ei, qi), u1r = sub2(er, qr), u1i = sub2(ei, qi);
      f[0] = fma2(u0r, t[0], mul2(u0i, t[8]));
      f[8] = fms2(u0i, t[0], mul2(u0r, t[8]));
      f[1] = fma2(u1r, t[1], mul2(u1i, t[9]));
      f[9] = fms2(u1i, t[1], mul2(u1r, t[9]));
    }
    fence_regs(fa); fence_regs(fb);
    wg_fence();
#pragma unroll
    for (int kk = 0; kk < 4; kk++) {
      wgmma_rs_n64<1, 1>(aR, fa[4 * kk], fa[4 * kk + 1], fa[4 * kk + 2], fa[4 * kk + 3], dT_n + kk * 128, kk != 0);
      wgmma_rs_n64<1, 1>(aI, fb[4 * kk], fb[4 * kk + 1], fb[4 * kk + 2], fb[4 * kk + 3], dT_n + kk * 128, kk != 0);
    }
    wg_commit();
    mbar_wait(BAR_Y(sb, item), 0);
    wg_wait<0>();
    fence_regs(aR); fence_regs(aI);
    TL(6 + 8 * rnd);
    {
      const uint8_t* wp = smem + SP_W + item * 16384 + q * 1024 + warp * 128 + (((lane >> 2) ^ (2 * q)) << 4);
#pragma unroll
      for (int jb = 0; jb < 4; jb++) {
#pragma unroll
        for (int h = 0; h < 2; h++) {
          const uint4 w = *reinterpret_cast<const uint4*>(wp + jb * 4096 + h * 512);
          const int i = 4 * jb + 2 * h;
          const uint32_t ar = pack2(aR[i], aR[i + 1]), ai = pack2(aR[16 + i], aR[17 + i]);
          const uint32_t br = pack2(aI[i], aI[i + 1]), bi = pack2(aI[16 + i], aI[17 + i]);
          fa[2 * jb + h] = fms2(ar, w.x, mul2(ai, w.y));
          fa[8 + 2 * jb + h] = fma2(ar, w.y, mul2(ai, w.x));
          fb[2 * jb + h] = fms2(br, w.z, mul2(bi, w.w));
          fb[8 + 2 * jb + h] = fma2(br, w.w, mul2(bi, w.z));
        }
      }
    }
    fence_regs(fa); fence_regs(fb);
    wg_fence();
#pragma unroll
    for (int kk = 0; kk < 4; kk++) {
      wgmma_rs_n64<1, 0>(aR, fa[4 * kk], fa[4 * kk + 1], fa[4 * kk + 2], fa[4 * kk + 3], dT_n + kk * 2, kk != 0);
      wgmma_rs_n64<1, 0>(aI, fb[4 * kk], fb[4 * kk + 1], fb[4 * kk + 2], fb[4 * kk + 3], dT_n + kk * 2, kk != 0);
    }
    wg_commit();
    wg_wait<0>();
    fence_regs(aR); fence_regs(aI);
    TL(7 + 8 * rnd);
#pragma unroll
    for (int v = 0; v < 8; v++) {
      const float* a = (v < 4 ? aR : aI) + 4 * (v & 3);
      const uint32_t* t = tw + 2 * (v & 3);
      const uint32_t u0r = pack2(a[0], a[1]), u1r = pack2(a[2], a[3]), u0i = pack2(a[16], a[17]), u1i = pack2(a[18], a[19]);
      const uint32_t t0r = fms2(u0r, t[0], mul2(u0i, t[8])), t0i = fma2(u0i, t[0], mul2(u0r, t[8]));
      const uint32_t t1r = fms2(u1r, t[1], mul2(u1i, t[9])), t1i = fma2(u1i, t[1], mul2(u1r, t[9]));
      fa[v] = add2(t0i, t1i); fa[8 + v] = add2(t0r, t1r);
      fb[v] = sub2(t0i, t1i); fb[8 + v] = sub2(t0r, t1r);
    }
    bar_sync(1 + wg, 128);
#pragma unroll
    for (int u = 0; u < 4; u++) {
      const uint32_t a = z + (32 * (u >> 1) + 8 * warp + (lane & 7)) * 128 + (((4 * (u & 1) + (lane >> 3)) ^ (lane & 7)) << 4);
      stmatrix_x4(a, fa[4 * u], fa[4 * u + 1], fa[4 * u + 2], fa[4 * u + 3]);
      stmatrix_x4(a + 8192, fb[4 * u], fb[4 * u + 1], fb[4 * u + 2], fb[4 * u + 3]);
    }
    load_frag(8192);
    fence_async_smem();
    bar_sync(1 + wg, 128);
    TL(8 + 8 * rnd);
    {
      const uint64_t de = mk_desc(z, 8192, 1024, 1);
      wg_fence();
#pragma unroll
      for (int kk = 0; kk < 4; kk++) {
        wgmma_rs_n64<1, 1>(aR, fe[4 * kk], fe[4 * kk + 1], fe[4 * kk + 2], fe[4 * kk + 3], de + kk * 128, kk != 0);
        wgmma_rs_n64<1, 1>(aI, fa[4 * kk], fa[4 * kk + 1], fa[4 * kk + 2], fa[4 * kk + 3], de + 512 + kk * 128, kk != 0);
      }
      wg_commit();
      wg_wait<0>();
      fence_regs(aR); fence_regs(aI);
    }
    TL(9 + 8 * rnd);
    const bool edge = pr == 0 || pr == 112;
    if (edge) {
#pragma unroll
      for (int i = 0; i < 16; i++) { aR[i] *= 0.5f; aI[i] *= 0.5f; }
    }
#pragma unroll
    for (int i = 0; i < 8; i++) {
      const float* a = ((i & 1) ? aI : aR) + 16 * (i >> 2) + 2 - (i & 2);
      *reinterpret_cast<uint4*>(smem + SP_W + item * 16384 + (i >> 1) * 4096 + (i & 1) * 64 + (tid >> 2) * 128 + q * 16) =
          make_uint4(pack2(a[0], a[1]), pack2(a[4], a[5]), pack2(a[8], a[9]), pack2(a[12], a[13]));
    }
    fence_async_smem();
    bar_sync(1 + wg, 128);
    if (tid == 0) {
      const uint32_t src = sb + SP_W + item * 16384;
      __nv_bfloat16* dst = p.s->yt + (size_t)(pr < 112 ? 4 * pr : 1) * S_;
      bulk_s2g(dst, src, edge ? 4096 : 16384);
      if (pr == 0) bulk_s2g(dst + 2 * S_, src + 8192, 8192);
      asm volatile("cp.async.bulk.commit_group;" ::: "memory");
      if (rnd == nrnd - 1) {
        asm volatile("cp.async.bulk.wait_group 0;" ::: "memory");
        TL(11);
        fence_async();
        fence_gpu();
        red_add(&p.s->cnt_y[(pr < 112 ? pr >> 4 : 0) * 32], 1);
        if (rnd) red_add(&p.s->cnt_y[((pr - 3) >> 4) * 32], 1);
      }
    }
    __syncwarp();
    TL(10 + 8 * rnd);
  }
  if (lane == 0) *my_epoch = epoch;
}

__global__ void __cluster_dims__(2, 1, 1) __launch_bounds__(384, 1)
fused_kernel(const __grid_constant__ Params p) {
  extern __shared__ __align__(1024) uint8_t smem[];
  const uint32_t sb = smem_u32(smem);
  TL(0);
  const uint32_t rank = blockIdx.x & 1;
  const int hc = blockIdx.x >> 1;
  int grp, jj;
  if (hc < 4) { grp = 8; jj = hc; }
  else if (hc < 36) { grp = (hc - 4) & 7; jj = (hc - 4) >> 3; }
  else if (hc < 57) { jj = (hc - 36) / 7; grp = 1 + (hc - 36) - 7 * jj; jj += 4; }
  else if (hc < 60) { grp = 0; jj = hc - 53; }
  else { grp = 8; jj = hc - 56; }
  const int mt = 2 * grp + rank, bid = 2 * (7 * grp + jj) + rank;
  if (threadIdx.x == 256) {
#pragma unroll
    for (int i = 0; i < NSTAGE; i++) { mbar_init(BAR_FULL(sb, i), 1); mbar_init(BAR_EMPTY(sb, i), 4); }
    asm volatile("fence.mbarrier_init.release.cluster;" ::: "memory");
  } else if (threadIdx.x == 320) {
#pragma unroll
    for (int i = 0; i < NSTAGE; i++) { mbar_init(BAR_X(sb, i), 1); mbar_init(BAR_Y(sb, i), 1); }
    mbar_init(BAR_XFREE(sb), 2);
    asm volatile("fence.mbarrier_init.release.cluster;" ::: "memory");
  } else if (threadIdx.x == 288) {
    prefetch_tmap(rank ? &p.wu : &p.wg); prefetch_tmap(&p.ct);
  }
  __syncwarp();
  asm volatile("barrier.cluster.arrive.relaxed.aligned;" ::: "memory");
  const int wg = __shfl_sync(0xffffffffu, threadIdx.x >> 7, 0);
  if (bid >= NFFN) {
    spectral_cta(sb, smem, p, bid - NFFN, wg);
  } else if (wg < 2) {
    asm volatile("setmaxnreg.inc.sync.aligned.u32 232;");
    asm volatile("barrier.cluster.wait.acquire.aligned;" ::: "memory");
    TL(1);
    ffn_consumer(sb, smem, p, bid, wg, threadIdx.x & 127, mt, jj);
  } else {
    asm volatile("setmaxnreg.dec.sync.aligned.u32 40;");
    if (threadIdx.x == 320) {
      mbar_expect_tx(BAR_X(sb, 0), 16384);
      tma2d(sb + SM_X, &p.x, 0, 128 * mt, BAR_X(sb, 0));
    }
    __syncwarp();
    asm volatile("barrier.cluster.wait.acquire.aligned;" ::: "memory");
    TL(1);
    if (threadIdx.x == 320) {
      constexpr int order[13] = {XORDER};
#pragma unroll
      for (int i = 0; i < 13; i++) {
        if (order[i] < 8) {
          ring_issue(sb, p, order[i], order[i], false, 0, jj, rank);
        } else {
          const int kb = order[i] - 10;
          mbar_expect_tx(BAR_X(sb, kb), 16384);
          tma2d(sb + SM_X + kb * 16384, &p.x, 64 * kb, 128 * mt, BAR_X(sb, kb));
        }
      }
      TL(2);
    } else if (threadIdx.x == 352) {
    }
    __syncwarp();
    ffn_producer(sb, smem, bid, p, (threadIdx.x >> 5) & 3, threadIdx.x & 31, mt, jj, rank);
  }
}

typedef CUresult (*EncodeFn)(CUtensorMap*, CUtensorMapDataType, cuuint32_t, void*, const cuuint64_t*, const cuuint64_t*,
                             const cuuint32_t*, const cuuint32_t*, CUtensorMapInterleave, CUtensorMapSwizzle,
                             CUtensorMapL2promotion, CUtensorMapFloatOOBfill);

void make_map(EncodeFn fn, CUtensorMap* m, const void* base, int rank, const cuuint64_t* dims, const cuuint64_t* strides,
              const cuuint32_t* box, CUtensorMapSwizzle sw) {
  const cuuint32_t es[4] = {1, 1, 1, 1};
  fn(m, CU_TENSOR_MAP_DATA_TYPE_BFLOAT16, rank, const_cast<void*>(base), dims, strides, box, es,
     CU_TENSOR_MAP_INTERLEAVE_NONE, sw, CU_TENSOR_MAP_L2_PROMOTION_L2_256B, CU_TENSOR_MAP_FLOAT_OOB_FILL_NONE);
}

}

extern "C" void kernel_launch(void* const* d_in, const int* in_sizes, int n_in, void* d_out, int out_size) {
  const __nv_bfloat16* x = (const __nv_bfloat16*)d_in[0];
  const __nv_bfloat16* w_r = (const __nv_bfloat16*)d_in[1];
  const __nv_bfloat16* w_i = (const __nv_bfloat16*)d_in[2];
  const __nv_bfloat16* wg = (const __nv_bfloat16*)d_in[4];
  const __nv_bfloat16* wu = (const __nv_bfloat16*)d_in[5];
  const __nv_bfloat16* wd = (const __nv_bfloat16*)d_in[6];
  const __nv_bfloat16* gate_w = (const __nv_bfloat16*)d_in[7];

  void* fnp = nullptr;
  cudaDriverEntryPointQueryResult qr;
  cudaGetDriverEntryPoint("cuTensorMapEncodeTiled", &fnp, cudaEnableDefault, &qr);
  EncodeFn fn = (EncodeFn)fnp;
  void *ctab, *spec, *scr;
  cudaGetSymbolAddress(&ctab, g_ctab);
  cudaGetSymbolAddress(&spec, g_spec);
  cudaGetSymbolAddress(&scr, g_scratch);
  const void* yt = (const char*)scr + offsetof(Scratch, yt);
  Params p;
  p.s = (Scratch*)scr; p.out = (__nv_bfloat16*)d_out;
  p.px = x; p.w_r = w_r; p.w_i = w_i; p.gate_w = gate_w; p.pwg = wg; p.pwu = wu; p.pwd = wd;
  p.ctab = (const tab::Table*)ctab; p.spec = (const tab::Spec*)spec;
  {
    const cuuint64_t d[2] = {D_, S_}, s[1] = {D_ * 2};
    const cuuint32_t b[2] = {64, 128};
    make_map(fn, &p.x, x, 2, d, s, b, CU_TENSOR_MAP_SWIZZLE_128B);
  }
  {
    const cuuint64_t d[3] = {64, D_, F_ / 64}, s[2] = {F_ * 2, 128};
    const cuuint32_t b[3] = {64, 32, 2};
    make_map(fn, &p.wg, wg, 3, d, s, b, CU_TENSOR_MAP_SWIZZLE_128B);
    make_map(fn, &p.wu, wu, 3, d, s, b, CU_TENSOR_MAP_SWIZZLE_128B);
  }
  {
    const cuuint64_t d[2] = {D_, F_}, s[1] = {D_ * 2};
    const cuuint32_t b[2] = {64, 64};
    make_map(fn, &p.wd, wd, 2, d, s, b, CU_TENSOR_MAP_SWIZZLE_128B);
  }
  {
    const cuuint64_t d[2] = {D_, D_}, s[1] = {D_ * 2};
    const cuuint32_t b[2] = {64, 64};
    make_map(fn, &p.ct, ctab, 2, d, s, b, CU_TENSOR_MAP_SWIZZLE_128B);
  }
  {
    const cuuint64_t d[3] = {64, D_, S_ / 64}, s[2] = {S_ * 2, 128};
    const cuuint32_t b[3] = {64, 64, 2};
    make_map(fn, &p.yt, yt, 3, d, s, b, CU_TENSOR_MAP_SWIZZLE_128B);
  }
  cudaFuncSetAttribute(fused_kernel, cudaFuncAttributeMaxDynamicSharedMemorySize, SM_TOTAL);
  fused_kernel<<<NCTA, 384, SM_TOTAL, cudaStreamPerThread>>>(p, x, w_r, w_i, gate_w, wd, (__nv_bfloat16*)d_out);
}
```

```cpp
#include <cuda_runtime.h>
#include <cuda_bf16.h>
#include <cuda.h>
#include <stdint.h>
#include <stddef.h>

namespace {

constexpr int S_ = 2048, D_ = 448, F_ = 1792, DF_ = 225;
constexpr int NFFN = 112, NSPEC = 20, NCTA = NFFN + NSPEC;
constexpr int NSTAGE = 7, STAGE_BYTES = 16384;
constexpr int SM_X = 0, SM_RING = 114688, SM_BAR = 229376, SM_TOTAL = SM_BAR + 512;
constexpr int SP_Z = 0, SP_W = 98304, SP_TW = 198656, SP_T = 215040, SLAB_BYTES = 16 * DF_ * 2;
constexpr uint32_t SPIN_LIMIT = 1u << 20;

namespace tab {
constexpr double PI = 3.14159265358979323846264338327950288;
constexpr double csin(double x) {
  double t = x, s = x;
  for (int i = 1; i < 20; i++) { t = -t * x * x / ((2 * i) * (2 * i + 1)); s += t; }
  return s;
}
constexpr double ccos(double x) {
  double t = 1, s = 1;
  for (int i = 1; i < 20; i++) { t = -t * x * x / ((2 * i - 1) * (2 * i)); s += t; }
  return s;
}
constexpr uint32_t to_bf16(double v) {
  uint32_t sign = v < 0 ? 0x8000u : 0u;
  double a = v < 0 ? -v : v;
  if (a < 1e-12) return 0;
  int e = 0;
  while (a >= 2.0) { a /= 2; e++; }
  while (a < 1.0) { a *= 2; e--; }
  double m = a * 128.0;
  int mi = (int)m;
  double fr = m - mi;
  if (fr > 0.5 || (fr == 0.5 && (mi & 1))) mi++;
  if (mi == 256) { mi = 128; e++; }
  return sign | (uint32_t)((e + 127) << 7) | (uint32_t)(mi - 128);
}
struct Base { uint32_t v[448]; };
constexpr Base make_base() {
  Base b{};
  for (int m = 0; m < 448; m++) {
    int mm = m > 224 ? m - 448 : m;
    double ang = 2 * PI * mm / 448.0;
    b.v[m] = to_bf16(ccos(ang)) | (to_bf16(-csin(ang)) << 16);
  }
  return b;
}
constexpr Base base = make_base();
struct Row { uint32_t v[224]; };
constexpr Row make_row(int d) {
  Row r{};
  r.v[0] = 0x3f80u | ((d & 1) ? 0xbf800000u : 0x3f800000u);
  int m = 0;
  for (int c = 1; c < 224; c++) { m += d; if (m >= 448) m -= 448; r.v[c] = base.v[m]; }
  return r;
}
struct Table { Row r[448]; };
constexpr Table make_table() {
  Table t{};
  for (int d = 0; d < 448; d++) t.r[d] = make_row(d);
  return t;
}
struct Cs { double c[2048], s[2048]; };
constexpr Cs make_cs() {
  Cs t{};
  for (int m = 0; m <= 256; m++) {
    const double a = 2 * PI * m / 2048.0, c = ccos(a), s = csin(a);
    t.c[m] = c; t.s[m] = s;
    t.c[512 - m] = s; t.s[512 - m] = c;
  }
  for (int m = 513; m < 2048; m++) { t.c[m] = -t.s[m - 512]; t.s[m] = t.c[m - 512]; }
  return t;
}
constexpr Cs cs = make_cs();
struct Spec {
  uint32_t fo[2048], fot[2048];
  uint16_t t32[4096];
  uint32_t fe[2048];
  uint32_t tw[2048];
};
constexpr uint32_t blk(int h, int c, int a) { return to_bf16(h == c ? cs.c[a & 2047] : (h ? -cs.s[a & 2047] : cs.s[a & 2047])); }
constexpr Spec make_spec() {
  Spec t{};
  for (int row = 0; row < 64; row++)
    for (int col = 0; col < 64; col++) {
      const int c = row & 31, k2 = col & 31, n2 = 8 * ((c >> 1) & 3) + 2 * (c >> 3) + (c & 1), m = 64 * ((n2 * k2) & 31);
      const double v = (row >> 5) == (col >> 5) ? cs.c[m] : (row < 32 ? -cs.s[m] : cs.s[m]);
      t.t32[row * 64 + (((col >> 3) ^ (row & 7)) << 3) + (col & 7)] = (uint16_t)to_bf16(v);
    }
  for (int th = 0; th < 128; th++)
    for (int i = 0; i < 16; i++) {
      const int r = 8 * (th >> 5) + ((th & 31) >> 2), h = i & 1, c = i >> 3, m = 8 * ((i >> 1) & 3) + 2 * (th & 3);
      const int o = ((i >> 2) * 128 + th) * 4 + (i & 3);
      t.fe[o] = blk(h, c, 64 * m * r) | (blk(h, c, 64 * (m + 1) * r) << 16);
      t.fo[o] = blk(h, c, 32 * (2 * m + 1) * r) | (blk(h, c, 32 * (2 * m + 3) * r) << 16);
      t.fot[o] = blk(h, c, 32 * (2 * r + 1) * m) | (blk(h, c, 32 * (2 * r + 1) * (m + 1)) << 16);
      const int k1 = r + 32 * h, n2 = 8 * (th & 3) + 2 * ((i >> 1) & 3);
      t.tw[o] = blk(0, c, n2 * k1) | (blk(0, c, (n2 + 1) * k1) << 16);
    }
  return t;
}
}
}

__device__ __align__(1024) const tab::Table g_ctab = tab::make_table();
__device__ __align__(1024) const tab::Spec g_spec = tab::make_spec();

struct Scratch {
  uint32_t cnt_w[32];
  uint32_t cnt_x1[7 * 32];
  uint32_t cnt_y[7 * 32];
  uint32_t epoch[NCTA * 12 + 240 + 256];
  uint32_t gate[S_];
  uint4 x1t[113 * 1024];
  __nv_bfloat16 yt[D_ * S_];
  uint4 wt[114 * 1024];
  uint4 part[16 * 7 * 6 * 2 * 4 * 128];
};
static_assert(offsetof(Scratch, x1t) % 1024 == 0, "alignment");
__device__ __align__(1024) Scratch g_scratch;
#define TL(i)

namespace {

struct Params {
  Scratch* s;
  __nv_bfloat16* out;
  const __nv_bfloat16 *px, *w_r, *w_i, *gate_w, *pwg, *pwu, *pwd;
  const tab::Table* ctab;
  const tab::Spec* spec;
  CUtensorMap x, wg, wu, wd, ct, yt;
};

__device__ __forceinline__ uint32_t smem_u32(const void* p) { return (uint32_t)__cvta_generic_to_shared(p); }
__device__ __forceinline__ void mbar_init(uint32_t bar, uint32_t cnt) {
  asm volatile("mbarrier.init.shared::cta.b64 [%0], %1;" ::"r"(bar), "r"(cnt) : "memory");
}
__device__ __forceinline__ void mbar_expect_tx(uint32_t bar, uint32_t bytes) {
  asm volatile("mbarrier.arrive.expect_tx.shared::cta.b64 _, [%0], %1;" ::"r"(bar), "r"(bytes) : "memory");
}
__device__ __forceinline__ void mbar_arrive(uint32_t bar) {
  asm volatile("mbarrier.arrive.shared::cta.b64 _, [%0];" ::"r"(bar) : "memory");
}
__device__ __forceinline__ void mbar_arrive_cluster(uint32_t bar, uint32_t cta) {
  asm volatile("{\n.reg .b32 ra;\nmapa.shared::cluster.u32 ra, %0, %1;\n"
               "mbarrier.arrive.shared::cluster.b64 _, [ra];\n}" ::"r"(bar), "r"(cta) : "memory");
}
__device__ __forceinline__ void mbar_wait(uint32_t bar, uint32_t parity) {
  uint32_t ok, n = 0;
  do {
    asm volatile("{\n.reg .pred p;\nmbarrier.try_wait.parity.shared::cta.b64 p, [%1], %2;\nselp.u32 %0, 1, 0, p;\n}"
                 : "=r"(ok) : "r"(bar), "r"(parity) : "memory");
  } while (!ok && ++n < SPIN_LIMIT);
}
__device__ __forceinline__ void mbar_wait_cluster(uint32_t bar, uint32_t parity) {
  uint32_t ok, n = 0;
  do {
    asm volatile("{\n.reg .pred p;\nmbarrier.try_wait.parity.acquire.cluster.shared::cta.b64 p, [%1], %2;\nselp.u32 %0, 1, 0, p;\n}"
                 : "=r"(ok) : "r"(bar), "r"(parity) : "memory");
  } while (!ok && ++n < SPIN_LIMIT);
}
__device__ __forceinline__ void tma2d(uint32_t dst, const CUtensorMap* m, int c0, int c1, uint32_t bar) {
  asm volatile("cp.async.bulk.tensor.2d.shared::cluster.global.mbarrier::complete_tx::bytes [%0], [%1, {%3, %4}], [%2];"
               ::"r"(dst), "l"(m), "r"(bar), "r"(c0), "r"(c1) : "memory");
}
__device__ __forceinline__ void tma3d(uint32_t dst, const CUtensorMap* m, int c0, int c1, int c2, uint32_t bar) {
  asm volatile("cp.async.bulk.tensor.3d.shared::cluster.global.mbarrier::complete_tx::bytes [%0], [%1, {%3, %4, %5}], [%2];"
               ::"r"(dst), "l"(m), "r"(bar), "r"(c0), "r"(c1), "r"(c2) : "memory");
}
__device__ __forceinline__ void tma2d_mc(uint32_t dst, const CUtensorMap* m, int c0, int c1, uint32_t bar) {
  asm volatile("cp.async.bulk.tensor.2d.shared::cluster.global.mbarrier::complete_tx::bytes.multicast::cluster [%0], [%1, {%3, %4}], [%2], %5;"
               ::"r"(dst), "l"(m), "r"(bar), "r"(c0), "r"(c1), "h"((uint16_t)3) : "memory");
}
__device__ __forceinline__ void tma3d_mc(uint32_t dst, const CUtensorMap* m, int c0, int c1, int c2, uint32_t bar) {
  asm volatile("cp.async.bulk.tensor.3d.shared::cluster.global.mbarrier::complete_tx::bytes.multicast::cluster [%0], [%1, {%3, %4, %5}], [%2], %6;"
               ::"r"(dst), "l"(m), "r"(bar), "r"(c0), "r"(c1), "r"(c2), "h"((uint16_t)3) : "memory");
}
__device__ __forceinline__ void bulk_g2s(uint32_t dst, const void* src, uint32_t bytes, uint32_t bar) {
  asm volatile("cp.async.bulk.shared::cluster.global.mbarrier::complete_tx::bytes [%0], [%1], %2, [%3];"
               ::"r"(dst), "l"(src), "r"(bytes), "r"(bar) : "memory");
}
__device__ __forceinline__ void bulk_s2g(void* dst, uint32_t src, uint32_t bytes) {
  asm volatile("cp.async.bulk.global.shared::cta.bulk_group [%0], [%1], %2;" ::"l"(dst), "r"(src), "r"(bytes) : "memory");
}
__device__ __forceinline__ void prefetch_tmap(const CUtensorMap* m) {
  asm volatile("prefetch.tensormap [%0];" ::"l"(m) : "memory");
}
__device__ __forceinline__ void l2_prefetch(const void* p, uint32_t bytes) {
  asm volatile("cp.async.bulk.prefetch.L2.global [%0], %1;" ::"l"(p), "r"(bytes) : "memory");
}
__device__ __forceinline__ void wg_fence() { asm volatile("wgmma.fence.sync.aligned;" ::: "memory"); }
__device__ __forceinline__ void wg_commit() { asm volatile("wgmma.commit_group.sync.aligned;" ::: "memory"); }
template <int N> __device__ __forceinline__ void wg_wait() { asm volatile("wgmma.wait_group.sync.aligned %0;" ::"n"(N) : "memory"); }
template <int N> __device__ __forceinline__ void fence_regs(float (&d)[N]) {
#pragma unroll
  for (int i = 0; i < N; i++) asm volatile("" : "+f"(d[i])::"memory");
}
template <int N> __device__ __forceinline__ void fence_regs(uint32_t (&d)[N]) {
#pragma unroll
  for (int i = 0; i < N; i++) asm volatile("" : "+r"(d[i])::"memory");
}
__device__ __forceinline__ void bar_sync(int id, int n) { asm volatile("bar.sync %0, %1;" ::"r"(id), "r"(n) : "memory"); }
__device__ __forceinline__ void bar_arrive(int id, int n) { asm volatile("bar.arrive %0, %1;" ::"r"(id), "r"(n) : "memory"); }
__device__ __forceinline__ void fence_gpu() { asm volatile("fence.acq_rel.gpu;" ::: "memory"); }
__device__ __forceinline__ void fence_async() { asm volatile("fence.proxy.async;" ::: "memory"); }
__device__ __forceinline__ void fence_async_smem() { asm volatile("fence.proxy.async.shared::cta;" ::: "memory"); }
__device__ __forceinline__ void red_add(uint32_t* p, uint32_t v) {
  asm volatile("red.relaxed.gpu.global.add.u32 [%0], %1;" ::"l"(p), "r"(v) : "memory");
}
__device__ __forceinline__ uint32_t ld_relaxed(const uint32_t* p) {
  uint32_t v;
  asm volatile("ld.relaxed.gpu.global.u32 %0, [%1];" : "=r"(v) : "l"(p) : "memory");
  return v;
}
__device__ __forceinline__ void wait_counter(const uint32_t* p, uint32_t target) {
  uint32_t v, n = 0;
  while (true) {
    asm volatile("ld.acquire.gpu.global.u32 %0, [%1];" : "=r"(v) : "l"(p) : "memory");
    if ((int32_t)(v - target) >= 0 || ++n > SPIN_LIMIT) break;
  }
}
__device__ __forceinline__ uint4 ld_relaxed(const uint4* p) {
  uint4 v;
  asm volatile("ld.relaxed.gpu.global.v4.u32 {%0, %1, %2, %3}, [%4];" : "=r"(v.x), "=r"(v.y), "=r"(v.z), "=r"(v.w) : "l"(p) : "memory");
  return v;
}
__device__ __forceinline__ void st_relaxed(uint4* p, uint4 v) {
  asm volatile("st.relaxed.gpu.global.v4.u32 [%0], {%1, %2, %3, %4};" ::"l"(p), "r"(v.x), "r"(v.y), "r"(v.z), "r"(v.w) : "memory");
}
__device__ __forceinline__ void st_relaxed(uint32_t* p, uint32_t v) {
  asm volatile("st.relaxed.gpu.global.u32 [%0], %1;" ::"l"(p), "r"(v) : "memory");
}
__device__ __forceinline__ uint32_t pack2(float lo, float hi) {
  uint32_t r;
  asm("cvt.rn.bf16x2.f32 %0, %1, %2;" : "=r"(r) : "f"(hi), "f"(lo));
  return r;
}
__device__ __forceinline__ uint32_t mul2(uint32_t a, uint32_t b) {
  uint32_t r;
  asm("mul.rn.bf16x2 %0, %1, %2;" : "=r"(r) : "r"(a), "r"(b));
  return r;
}
__device__ __forceinline__ uint32_t fma2(uint32_t a, uint32_t b, uint32_t c) {
  uint32_t r;
  asm("fma.rn.bf16x2 %0, %1, %2, %3;" : "=r"(r) : "r"(a), "r"(b), "r"(c));
  return r;
}
__device__ __forceinline__ uint32_t add2(uint32_t a, uint32_t b) {
  uint32_t r;
  asm("add.rn.bf16x2 %0, %1, %2;" : "=r"(r) : "r"(a), "r"(b));
  return r;
}
__device__ __forceinline__ uint32_t sub2(uint32_t a, uint32_t b) {
  uint32_t r;
  asm("sub.rn.bf16x2 %0, %1, %2;" : "=r"(r) : "r"(a), "r"(b));
  return r;
}
__device__ __forceinline__ uint32_t fms2(uint32_t a, uint32_t b, uint32_t c) {
  uint32_t r;
  asm("{\n.reg .b32 n;\nneg.bf16x2 n, %3;\nfma.rn.bf16x2 %0, %1, %2, n;\n}" : "=r"(r) : "r"(a), "r"(b), "r"(c));
  return r;
}
__device__ __forceinline__ float bf_lo(uint32_t v) { return __uint_as_float(v << 16); }
__device__ __forceinline__ float bf_hi(uint32_t v) { return __uint_as_float(v & 0xffff0000u); }
__device__ __forceinline__ float bf_round(float v) { return bf_lo(pack2(v, 0.f)); }
__device__ __forceinline__ float tanh_fast(float v) {
  float r;
  asm("tanh.approx.f32 %0, %1;" : "=f"(r) : "f"(v));
  return r;
}
__device__ __forceinline__ uint64_t mk_desc(uint32_t addr, uint32_t lbo, uint32_t sbo, uint32_t mode) {
  return (uint64_t)((addr & 0x3FFFF) >> 4) | ((uint64_t)(lbo >> 4) << 16) | ((uint64_t)(sbo >> 4) << 32) | ((uint64_t)mode << 62);
}
__device__ __forceinline__ void stmatrix_x4(uint32_t addr, uint32_t r0, uint32_t r1, uint32_t r2, uint32_t r3) {
  asm volatile("stmatrix.sync.aligned.m8n8.x4.shared.b16 [%0], {%1, %2, %3, %4};" ::"r"(addr), "r"(r0), "r"(r1), "r"(r2), "r"(r3) : "memory");
}

template <int TA, int TB>
__device__ __forceinline__ void wgmma_ss_n256(float (&d)[128], uint64_t da, uint64_t db, int sd) {
  asm volatile("{\n.reg .pred p;\nsetp.ne.b32 p, %130, 0;\n"
      "wgmma.mma_async.sync.aligned.m64n256k16.f32.bf16.bf16 {"
      "%0, %1, %2, %3, %4, %5, %6, %7, %8, %9, %10, %11, %12, %13, %14, %15, %16, %17, %18, %19, %20, %21, %22, %23, "
      "%24, %25, %26, %27, %28, %29, %30, %31, %32, %33, %34, %35, %36, %37, %38, %39, %40, %41, %42, %43, %44, %45, "
      "%46, %47, %48, %49, %50, %51, %52, %53, %54, %55, %56, %57, %58, %59, %60, %61, %62, %63, %64, %65, %66, %67, "
      "%68, %69, %70, %71, %72, %73, %74, %75, %76, %77, %78, %79, %80, %81, %82, %83, %84, %85, %86, %87, %88, %89, "
      "%90, %91, %92, %93, %94, %95, %96, %97, %98, %99, %100, %101, %102, %103, %104, %105, %106, %107, %108, %109, "
      "%110, %111, %112, %113, %114, %115, %116, %117, %118, %119, %120, %121, %122, %123, %124, %125, %126, %127"
      "}, %128, %129, p, 1, 1, %131, %132;\n}\n"
      : "+f"(d[0]), "+f"(d[1]), "+f"(d[2]), "+f"(d[3]), "+f"(d[4]), "+f"(d[5]), "+f"(d[6]), "+f"(d[7]), "+f"(d[8]),
        "+f"(d[9]), "+f"(d[10]), "+f"(d[11]), "+f"(d[12]), "+f"(d[13]), "+f"(d[14]), "+f"(d[15]), "+f"(d[16]),
        "+f"(d[17]), "+f"(d[18]), "+f"(d[19]), "+f"(d[20]), "+f"(d[21]), "+f"(d[22]), "+f"(d[23]), "+f"(d[24]),
        "+f"(d[25]), "+f"(d[26]), "+f"(d[27]), "+f"(d[28]), "+f"(d[29]), "+f"(d[30]), "+f"(d[31]), "+f"(d[32]),
        "+f"(d[33]), "+f"(d[34]), "+f"(d[35]), "+f"(d[36]), "+f"(d[37]), "+f"(d[38]), "+f"(d[39]), "+f"(d[40]),
        "+f"(d[41]), "+f"(d[42]), "+f"(d[43]), "+f"(d[44]), "+f"(d[45]), "+f"(d[46]), "+f"(d[47]), "+f"(d[48]),
        "+f"(d[49]), "+f"(d[50]), "+f"(d[51]), "+f"(d[52]), "+f"(d[53]), "+f"(d[54]), "+f"(d[55]), "+f"(d[56]),
        "+f"(d[57]), "+f"(d[58]), "+f"(d[59]), "+f"(d[60]), "+f"(d[61]), "+f"(d[62]), "+f"(d[63]), "+f"(d[64]),
        "+f"(d[65]), "+f"(d[66]), "+f"(d[67]), "+f"(d[68]), "+f"(d[69]), "+f"(d[70]), "+f"(d[71]), "+f"(d[72]),
        "+f"(d[73]), "+f"(d[74]), "+f"(d[75]), "+f"(d[76]), "+f"(d[77]), "+f"(d[78]), "+f"(d[79]), "+f"(d[80]),
        "+f"(d[81]), "+f"(d[82]), "+f"(d[83]), "+f"(d[84]), "+f"(d[85]), "+f"(d[86]), "+f"(d[87]), "+f"(d[88]),
        "+f"(d[89]), "+f"(d[90]), "+f"(d[91]), "+f"(d[92]), "+f"(d[93]), "+f"(d[94]), "+f"(d[95]), "+f"(d[96]),
        "+f"(d[97]), "+f"(d[98]), "+f"(d[99]), "+f"(d[100]), "+f"(d[101]), "+f"(d[102]), "+f"(d[103]), "+f"(d[104]),
        "+f"(d[105]), "+f"(d[106]), "+f"(d[107]), "+f"(d[108]), "+f"(d[109]), "+f"(d[110]), "+f"(d[111]),
        "+f"(d[112]), "+f"(d[113]), "+f"(d[114]), "+f"(d[115]), "+f"(d[116]), "+f"(d[117]), "+f"(d[118]),
        "+f"(d[119]), "+f"(d[120]), "+f"(d[121]), "+f"(d[122]), "+f"(d[123]), "+f"(d[124]), "+f"(d[125]),
        "+f"(d[126]), "+f"(d[127])
      : "l"(da), "l"(db), "r"(sd), "n"(TA), "n"(TB));
}
template <int TA, int TB>
__device__ __forceinline__ void wgmma_ss_n128(float (&d)[64], uint64_t da, uint64_t db, int sd) {
  asm volatile("{\n.reg .pred p;\nsetp.ne.b32 p, %66, 0;\n"
      "wgmma.mma_async.sync.aligned.m64n128k16.f32.bf16.bf16 {"
      "%0, %1, %2, %3, %4, %5, %6, %7, %8, %9, %10, %11, %12, %13, %14, %15, %16, %17, %18, %19, %20, %21, %22, %23, "
      "%24, %25, %26, %27, %28, %29, %30, %31, %32, %33, %34, %35, %36, %37, %38, %39, %40, %41, %42, %43, %44, %45, "
      "%46, %47, %48, %49, %50, %51, %52, %53, %54, %55, %56, %57, %58, %59, %60, %61, %62, %63"
      "}, %64, %65, p, 1, 1, %67, %68;\n}\n"
      : "+f"(d[0]), "+f"(d[1]), "+f"(d[2]), "+f"(d[3]), "+f"(d[4]), "+f"(d[5]), "+f"(d[6]), "+f"(d[7]), "+f"(d[8]),
        "+f"(d[9]), "+f"(d[10]), "+f"(d[11]), "+f"(d[12]), "+f"(d[13]), "+f"(d[14]), "+f"(d[15]), "+f"(d[16]),
        "+f"(d[17]), "+f"(d[18]), "+f"(d[19]), "+f"(d[20]), "+f"(d[21]), "+f"(d[22]), "+f"(d[23]), "+f"(d[24]),
        "+f"(d[25]), "+f"(d[26]), "+f"(d[27]), "+f"(d[28]), "+f"(d[29]), "+f"(d[30]), "+f"(d[31]), "+f"(d[32]),
        "+f"(d[33]), "+f"(d[34]), "+f"(d[35]), "+f"(d[36]), "+f"(d[37]), "+f"(d[38]), "+f"(d[39]), "+f"(d[40]),
        "+f"(d[41]), "+f"(d[42]), "+f"(d[43]), "+f"(d[44]), "+f"(d[45]), "+f"(d[46]), "+f"(d[47]), "+f"(d[48]),
        "+f"(d[49]), "+f"(d[50]), "+f"(d[51]), "+f"(d[52]), "+f"(d[53]), "+f"(d[54]), "+f"(d[55]), "+f"(d[56]),
        "+f"(d[57]), "+f"(d[58]), "+f"(d[59]), "+f"(d[60]), "+f"(d[61]), "+f"(d[62]), "+f"(d[63])
      : "l"(da), "l"(db), "r"(sd), "n"(TA), "n"(TB));
}
template <int TA, int TB>
__device__ __forceinline__ void wgmma_ss_n64(float (&d)[32], uint64_t da, uint64_t db, int sd) {
  asm volatile("{\n.reg .pred p;\nsetp.ne.b32 p, %34, 0;\n"
      "wgmma.mma_async.sync.aligned.m64n64k16.f32.bf16.bf16 {"
      "%0, %1, %2, %3, %4, %5, %6, %7, %8, %9, %10, %11, %12, %13, %14, %15, %16, %17, %18, %19, %20, %21, %22, %23, "
      "%24, %25, %26, %27, %28, %29, %30, %31"
      "}, %32, %33, p, 1, 1, %35, %36;\n}\n"
      : "+f"(d[0]), "+f"(d[1]), "+f"(d[2]), "+f"(d[3]), "+f"(d[4]), "+f"(d[5]), "+f"(d[6]), "+f"(d[7]), "+f"(d[8]),
        "+f"(d[9]), "+f"(d[10]), "+f"(d[11]), "+f"(d[12]), "+f"(d[13]), "+f"(d[14]), "+f"(d[15]), "+f"(d[16]),
        "+f"(d[17]), "+f"(d[18]), "+f"(d[19]), "+f"(d[20]), "+f"(d[21]), "+f"(d[22]), "+f"(d[23]), "+f"(d[24]),
        "+f"(d[25]), "+f"(d[26]), "+f"(d[27]), "+f"(d[28]), "+f"(d[29]), "+f"(d[30]), "+f"(d[31])
      : "l"(da), "l"(db), "r"(sd), "n"(TA), "n"(TB));
}
template <int SA, int TB>
__device__ __forceinline__ void wgmma_rs_n64(float (&d)[32], uint32_t a0, uint32_t a1, uint32_t a2, uint32_t a3, uint64_t db, int sd) {
  asm volatile("{\n.reg .pred p;\nsetp.ne.b32 p, %37, 0;\n"
      "wgmma.mma_async.sync.aligned.m64n64k16.f32.bf16.bf16 {"
      "%0, %1, %2, %3, %4, %5, %6, %7, %8, %9, %10, %11, %12, %13, %14, %15, %16, %17, %18, %19, %20, %21, %22, %23, "
      "%24, %25, %26, %27, %28, %29, %30, %31"
      "}, {%32, %33, %34, %35}, %36, p, %38, 1, %39;\n}\n"
      : "+f"(d[0]), "+f"(d[1]), "+f"(d[2]), "+f"(d[3]), "+f"(d[4]), "+f"(d[5]), "+f"(d[6]), "+f"(d[7]), "+f"(d[8]),
        "+f"(d[9]), "+f"(d[10]), "+f"(d[11]), "+f"(d[12]), "+f"(d[13]), "+f"(d[14]), "+f"(d[15]), "+f"(d[16]),
        "+f"(d[17]), "+f"(d[18]), "+f"(d[19]), "+f"(d[20]), "+f"(d[21]), "+f"(d[22]), "+f"(d[23]), "+f"(d[24]),
        "+f"(d[25]), "+f"(d[26]), "+f"(d[27]), "+f"(d[28]), "+f"(d[29]), "+f"(d[30]), "+f"(d[31])
      : "r"(a0), "r"(a1), "r"(a2), "r"(a3), "l"(db), "r"(sd), "n"(SA), "n"(TB));
}

__device__ __forceinline__ uint32_t BAR_FULL(uint32_t sb, int i) { return sb + SM_BAR + 8 * i; }
__device__ __forceinline__ uint32_t BAR_EMPTY(uint32_t sb, int i) { return sb + SM_BAR + 64 + 8 * i; }
__device__ __forceinline__ uint32_t BAR_X(uint32_t sb, int i) { return sb + SM_BAR + 128 + 8 * i; }
__device__ __forceinline__ uint32_t BAR_Y(uint32_t sb, int i) { return sb + SM_BAR + 192 + 8 * i; }
__device__ __forceinline__ uint32_t BAR_XFREE(uint32_t sb) { return sb + SM_BAR + 256; }

__device__ __forceinline__ uint32_t BAR_E2(uint32_t sb, int i) { return sb + SM_BAR + 264 + 8 * i; }
#define CMASK 0x194u
#define XORDER 0, 1, 11, 2, 3, 12, 13, 4, 5, 14, 6, 15, 16
#define XSPREAD 2
#define PFAT 3
#define SKEW 3
#define GL1 0
#define GS0 2
#define GL2 4
#define GS1 5
constexpr int Q_G1B = 18, Q_G2 = 32, Q_XR = 39, Q_P3 = 46, Q_END = 50;

struct Ring {
  uint32_t slot, phase;
  __device__ __forceinline__ void next() { if (++slot == NSTAGE) { slot = 0; phase ^= 1; } }
};

__device__ __forceinline__ void release_slot(uint32_t sb, uint32_t slot, int tid, int times) {
  if (tid < 2 * times) mbar_arrive_cluster(BAR_EMPTY(sb, slot), tid & 1);
}

__device__ __forceinline__ void ffn_consumer(uint32_t sb, const uint8_t* smem, const Params& p, int bid, int wg, int tid, int mt, int jj) {
  const int lane = tid & 31, warp = tid >> 5, q = lane & 3, r0 = 16 * warp + (lane >> 2);
  uint32_t* const my_epoch = &p.s->epoch[blockIdx.x * 12 + (threadIdx.x >> 5)];
  const uint32_t epoch = ld_relaxed(my_epoch) + 1;
  Ring rg{0, 0};
  uint32_t u[64];
  float acc[128];
  uint32_t prev = 0, cmask = CMASK;
  int st = 0;
  auto g1_stage = [&](uint32_t slot, int s) {
    const uint64_t da = mk_desc(sb + SM_X + (s >> 1) * 16384 + wg * 8192 + (s & 1) * 64, 16, 1024, 1);
    const uint64_t db = mk_desc(sb + SM_RING + slot * STAGE_BYTES, 4096, 1024, 1);
    wg_fence();
    wgmma_ss_n256<0, 1>(acc, da, db, s != 0);
    wgmma_ss_n256<0, 1>(acc, da + 2, db + 128, 1);
    wg_commit();
  };
  if (wg == 1) {
    float ap[64];
    constexpr int QX = 32 - __builtin_clz(CMASK);
    constexpr int NPRE = QX + XSPREAD;
    uint4* const x1dst = p.s->x1t + ((64 * jj + r0 + 8) >> 2) * 1024 + (r0 & 3) * 128 + 8 * mt + (q ^ (mt & 3));
    const int x1lo = 64 * jj + r0 == 1 ? 110 * 1024 - 128 : -2048;
#pragma unroll
    for (int qi = 0; qi < NPRE; qi++) {
      const int slot = qi % NSTAGE, nc = __builtin_popcount(CMASK & ((1u << qi) - 1));
      if (qi == 0) TL(60);
      mbar_wait(BAR_FULL(sb, slot), (qi / NSTAGE) & 1);
      if (qi == 0) TL(61);
      if ((CMASK >> qi) & 1) {
#pragma unroll
        for (int kb = 2 * nc; kb < 2 * nc + 2 && kb < 7; kb++) {
          const uint64_t da = mk_desc(sb + SM_RING + slot * STAGE_BYTES + (kb & 1) * 8192, 8192, 1024, 1);
          const uint64_t db = mk_desc(sb + SM_X + kb * 16384, 16, 1024, 1);
          mbar_wait(BAR_X(sb, kb), 0);
          TL(16 + kb);
          wg_fence();
#pragma unroll
          for (int kk = 0; kk < 4; kk++) wgmma_ss_n128<1, 0>(ap, da + kk * 128, db + kk * 2, (kb | kk) != 0);
          wg_commit();
        }
      } else {
        if (((qi - nc) & 1) == 0 && qi - nc >= 4 * nc) mbar_wait(BAR_X(sb, (qi - nc) >> 1), 0);
        TL(32 + qi - nc);
        g1_stage(slot, qi - nc);
      }
      if (qi > 0) {
        wg_wait<1>();
        release_slot(sb, (qi - 1) % NSTAGE, tid, ((CMASK >> (qi - 1)) & 1) ? 2 : 1);
      }
      if (qi >= QX) {
        if (qi == QX) { fence_regs(ap); TL(2); }
#pragma unroll
        for (int t = (qi - QX) * (4 / XSPREAD); t < (qi - QX + 1) * (4 / XSPREAD); t++)
#pragma unroll
        for (int h = 0; h < 2; h++)
          x1dst[(h ? 0 : x1lo) + 512 * (t & 1) + 4 * (t >> 1)] = make_uint4(pack2(ap[16 * t + 2 * h], ap[16 * t + 2 * h + 1]), pack2(ap[16 * t + 4 + 2 * h], ap[16 * t + 5 + 2 * h]),
                                             pack2(ap[16 * t + 8 + 2 * h], ap[16 * t + 9 + 2 * h]), pack2(ap[16 * t + 12 + 2 * h], ap[16 * t + 13 + 2 * h]));
      }
    }
    bar_arrive(7, 160);
    st = NPRE - 4; cmask = 0; prev = (NPRE - 1) % NSTAGE;
    rg.slot = NPRE % NSTAGE; rg.phase = (NPRE / NSTAGE) & 1;
  }
#pragma unroll 1
  for (int pass = 0; pass < 2; pass++) {
#pragma unroll 1
    for (; st < 14; st++) {
      while (cmask & 1) { cmask >>= 1; rg.next(); }
      cmask >>= 1;
      if (pass == 0 && (st & 1) == 0) mbar_wait(BAR_X(sb, st >> 1), 0);
      if (st == 14 - SKEW && wg == 1) bar_sync(9 + pass, 256);
      mbar_wait(BAR_FULL(sb, rg.slot), rg.phase);
      TL(32 + 14 * pass + st);
      g1_stage(rg.slot, st);
      wg_wait<1>();
      if (st > 0) release_slot(sb, prev, tid, 1);
      prev = rg.slot;
      rg.next();
    }
    st = 0;
    if (wg == 0) bar_arrive(9 + pass, 256);
    wg_wait<0>();
    fence_regs(acc);
    release_slot(sb, prev, tid, 1);
    if (pass == 1 && tid < 2) mbar_arrive_cluster(BAR_XFREE(sb), tid);
    TL(3 + 2 * pass);
#pragma unroll
    for (int i = 0; i < 32; i++) {
      const float g0 = 0.5f * acc[2 * i], g1 = 0.5f * acc[2 * i + 1];
      const float s0 = fmaf(g0, tanh_fast(g0), g0), s1 = fmaf(g1, tanh_fast(g1), g1);
      u[32 + i] = pack2(s0 * acc[64 + 2 * i], s1 * acc[64 + 2 * i + 1]);
    }
    if (pass == 0) {
#pragma unroll
      for (int i = 0; i < 32; i++) u[i] = u[32 + i];
    }
    TL(4 + 2 * pass);
  }
  fence_regs(u);
  float accA[32], accB[32];
  auto stage = [&](float (&acc)[32], int qi) {
    const int st = qi & 1;
    if (qi < Q_XR) mbar_wait(BAR_FULL(sb, qi % NSTAGE), (qi / NSTAGE) & 1);
    else mbar_wait(BAR_X(sb, qi - Q_XR), 1);
    const uint64_t db = mk_desc(sb + (qi < Q_XR ? SM_RING + (qi % NSTAGE) * STAGE_BYTES : SM_X + (qi - Q_XR) * 16384), 8192, 1024, 1);
    wg_fence();
#pragma unroll
    for (int kk = 0; kk < 8; kk++) {
      const uint32_t* a = u + 32 * st + 4 * kk;
      wgmma_rs_n64<1, 1>(acc, a[0], a[1], a[2], a[3], db + kk * 128, (st | kk) != 0);
    }
    wg_commit();
  };
  auto retire = [&](int qi) {
    wg_wait<1>();
    if (qi >= Q_G2 && qi < Q_XR + 4 && tid < 2) mbar_arrive_cluster(qi < Q_XR ? BAR_EMPTY(sb, qi % NSTAGE) : BAR_E2(sb, qi - Q_XR), tid);
  };
  const uint32_t par = epoch & 1;
  auto put = [&](float (&acc)[32], int c) {
    fence_regs(acc);
    int o = jj + 1 + c;
    if (o >= 7) o -= 7;
    uint4* dst = p.s->part + ((((mt * 7 + o) * 6 + c) * 2 + wg) * 4) * 128 + tid;
#pragma unroll
    for (int v = 0; v < 4; v++) {
      const float* a = acc + 8 * v;
      st_relaxed(dst + v * 128, make_uint4((pack2(a[0], a[1]) & ~1u) | par, pack2(a[2], a[3]), pack2(a[4], a[5]), pack2(a[6], a[7])));
    }
  };
  const uint4* const src = p.s->part + (((mt * 7 + jj) * 6 * 2 + wg) * 4) * 128 + tid;
  auto gload = [&](uint4 (&pv)[8], int c) {
#pragma unroll
    for (int i = 0; i < 8; i++) pv[i] = ld_relaxed(src + ((2 * c + (i >> 2)) * 8 + (i & 3)) * 128);
  };
  auto gsum = [&](uint4 (&pv)[8], int c) {
#pragma unroll 1
    for (uint32_t n = 0; n < SPIN_LIMIT; n++) {
      uint32_t bad = 0;
#pragma unroll
      for (int i = 0; i < 8; i++) bad |= pv[i].x ^ par;
      if (!__any_sync(0xffffffffu, bad & 1)) break;
      gload(pv, c);
    }
    TL(24 + c);
#pragma unroll
    for (int i = 0; i < 8; i++) {
      const float t[8] = {bf_lo(pv[i].x), bf_hi(pv[i].x), bf_lo(pv[i].y), bf_hi(pv[i].y), bf_lo(pv[i].z), bf_hi(pv[i].z), bf_lo(pv[i].w), bf_hi(pv[i].w)};
#pragma unroll
      for (int k = 0; k < 8; k++) accA[8 * (i & 3) + k] += t[k];
    }
  };
  uint4 pv0[8], pv1[8], pv2[8];
  const int row = 128 * mt + 64 * wg + r0;
  uint32_t gt0, gt1;
#pragma unroll
  for (int c2 = 0; c2 < 4; c2++) {
    const int qi = Q_G2 + 4 * c2;
    stage(accA, qi);
    retire(qi - 1);
    stage(accA, qi + 1);
    if (c2 == 3) TL(27);
    if (c2 > 0) put(accB, 2 * c2 - 1);
    TL(7 + c2);
    if (c2 == 3) break;
    retire(qi);
    stage(accB, qi + 2);
    retire(qi + 1);
    stage(accB, qi + 3);
    put(accA, 2 * c2);
    if (c2 == 2) { gload(pv0, 0); gt0 = ld_relaxed(&p.s->gate[row]); gt1 = ld_relaxed(&p.s->gate[row + 8]); }
    retire(qi + 2);
  }
#pragma unroll
  for (int kb = 0; kb < 7; kb++) {
    if ((kb & 1) == 0) mbar_wait(BAR_X(sb, kb >> 1), 0);
    mbar_wait(BAR_Y(sb, kb), 0);
    const uint64_t da = mk_desc(sb + SM_RING + ((Q_XR + kb) % NSTAGE) * STAGE_BYTES + wg * 8192, 8192, 1024, 1);
    const uint64_t db = mk_desc(sb + SM_X + kb * 8192, 16, 1024, 1);
    wg_fence();
#pragma unroll
    for (int kk = 0; kk < 4; kk++) wgmma_ss_n64<1, 0>(accB, da + kk * 128, db + kk * 2, (kb | kk) != 0);
    wg_commit();
    if (kb == GL1) gload(pv1, 1);
    if (kb == 1) { wg_wait<2>(); fence_regs(accA); TL(15); }
    if (kb == GS0) gsum(pv0, 0);
    if (kb == GL2) gload(pv2, 2);
    if (kb == GS1) gsum(pv1, 1);
  }
  TL(11);
  for (uint32_t n = 0; (((gt0 ^ epoch) | (gt1 ^ epoch)) & 0xffffu) && n < SPIN_LIMIT; n++) {
    gt0 = ld_relaxed(&p.s->gate[row]); gt1 = ld_relaxed(&p.s->gate[row + 8]);
  }
  gsum(pv2, 2);
  const float ga0 = bf_hi(gt0), ga1 = bf_hi(gt1);
  TL(12);
  wg_wait<0>();
  fence_regs(accB);
  TL(13);
  const float gb0 = bf_round(1.f - ga0), gb1 = bf_round(1.f - ga1);
  const float gs0 = ga0 * (2.f / (float)(S_ * D_)), gs1 = ga1 * (2.f / (float)(S_ * D_));
  uint4* const o = reinterpret_cast<uint4*>(p.out + (size_t)row * D_ + 64 * jj + 8 * q);
#pragma unroll
  for (int h = 0; h < 2; h++) {
    const float gs = h ? gs1 : gs0, gb = h ? gb1 : gb0;
#pragma unroll
    for (int k = 0; k < 2; k++) {
      uint32_t w[4];
#pragma unroll
      for (int j = 0; j < 4; j++) {
        const int i = 16 * k + 4 * j + 2 * h;
        w[j] = pack2(fmaf(gs, accB[i], gb * accA[i]), fmaf(gs, accB[i + 1], gb * accA[i + 1]));
      }
      const bool o1 = q & 1, o2 = q & 2;
      uint32_t a = __shfl_xor_sync(0xffffffffu, o1 ? w[0] : w[1], 1), b = __shfl_xor_sync(0xffffffffu, o1 ? w[2] : w[3], 1);
      if (o1) { w[0] = a; w[2] = b; } else { w[1] = a; w[3] = b; }
      a = __shfl_xor_sync(0xffffffffu, o2 ? w[0] : w[2], 2); b = __shfl_xor_sync(0xffffffffu, o2 ? w[1] : w[3], 2);
      if (o2) { w[0] = a; w[1] = b; } else { w[2] = a; w[3] = b; }
      o[h * D_ + 4 * k] = make_uint4(w[0], w[1], w[2], w[3]);
    }
  }
  if (lane == 0) *my_epoch = epoch;
  TL(14);
}

__device__ __forceinline__ void ring_issue(uint32_t sb, const Params& p, int qi, uint32_t slot, bool wait, uint32_t phase, int jj, uint32_t rank) {
  const CUtensorMap* m;
  int c0, c1, c2 = 0;
  bool half = false, is3d = false;
  if (qi < Q_G2) {
    const int nc = __popc(CMASK & ((1u << qi) - 1));
    if ((CMASK >> qi) & 1) {
      m = &p.ct; c0 = 64 * jj; c1 = 128 * nc + 64 * rank; half = nc == 3;
    } else {
      const int pass = qi >= Q_G1B;
      m = rank ? &p.wu : &p.wg; c0 = 0; c1 = 32 * (qi - nc - 14 * pass); c2 = 4 * jj + 2 * pass; is3d = true;
    }
  } else if (qi < Q_P3) {
    int o = jj + 1 + ((qi - Q_G2) >> 1);
    if (o >= 7) o -= 7;
    m = &p.wd; c0 = 64 * o; c1 = 256 * jj + 128 * (qi & 1) + 64 * rank;
  } else {
    m = &p.ct; c0 = 128 * (qi - Q_P3) + 64 * rank; c1 = 64 * jj; half = qi == Q_END - 1;
  }
  uint32_t bar = BAR_FULL(sb, slot), dst = sb + SM_RING + slot * STAGE_BYTES + rank * 8192, ebar = BAR_EMPTY(sb, slot);
  if (qi >= Q_XR) {
    const int i = qi - (qi < Q_P3 ? Q_XR : Q_P3);
    bar = BAR_X(sb, i); dst = sb + SM_X + i * 16384 + rank * 8192;
    ebar = qi < Q_P3 ? BAR_XFREE(sb) : BAR_E2(sb, i); phase = 0;
  }
  if (wait) mbar_wait_cluster(ebar, phase);
  mbar_expect_tx(bar, half ? 8192 : 16384);
  if (is3d) tma3d_mc(dst, m, c0, c1, c2, bar);
  else if (!(half && rank)) tma2d_mc(dst, m, c0, c1, bar);
}

__device__ __forceinline__ void ffn_producer(uint32_t sb, const uint8_t* smem, int bid, const Params& p, int warp, int lane, int mt, int jj, uint32_t rank) {
  if (warp < 2) {
    if (lane == 0) {
      uint32_t slot = warp, phase = 0;
#pragma unroll 1
      for (int qi = NSTAGE + warp; qi < Q_END; qi += 2) {
        ring_issue(sb, p, qi, slot, true, phase, jj, rank);
        TL(10 + qi);
        slot += 2;
        if (slot >= NSTAGE) { slot -= NSTAGE; phase ^= 1; }
      }
    }
  } else {
    const int wg = warp - 2;
    if (wg == 0) {
      if (lane == 0) { prefetch_tmap(&p.wd); prefetch_tmap(&p.yt); }
      uint32_t* const my_epoch = &p.s->epoch[blockIdx.x * 12 + 10];
      const uint32_t epoch = ld_relaxed(my_epoch) + 1;
      {
        const uint4* gw4 = reinterpret_cast<const uint4*>(p.gate_w);
        const uint4 ga = __ldg(gw4 + lane), gb = lane < 24 ? __ldg(gw4 + 32 + lane) : make_uint4(0, 0, 0, 0);
        if (lane < 7) mbar_wait(BAR_X(sb, lane), 0);
        __syncwarp();
        float mine = 0.f;
#pragma unroll 1
        for (int u = 0; u < 19; u++) {
          const int r = min(19 * jj + u, 127);
          const uint8_t* xr = smem + SM_X + (lane >> 3) * 16384 + r * 128 + (((lane ^ r) & 7) << 4);
          const uint4 xa = *reinterpret_cast<const uint4*>(xr);
          const uint4 xb = lane < 24 ? *reinterpret_cast<const uint4*>(xr + 65536) : make_uint4(0, 0, 0, 0);
          float s = 0.f;
          auto dot2 = [&](uint32_t a, uint32_t b) {
            const uint32_t pr = mul2(a, b);
            s += bf_lo(pr) + bf_hi(pr);
          };
          dot2(xa.x, ga.x); dot2(xa.y, ga.y); dot2(xa.z, ga.z); dot2(xa.w, ga.w);
          dot2(xb.x, gb.x); dot2(xb.y, gb.y); dot2(xb.z, gb.z); dot2(xb.w, gb.w);
#pragma unroll
          for (int o = 16; o > 0; o >>= 1) s += __shfl_xor_sync(0xffffffffu, s, o);
          if (lane == u) mine = s;
        }
        if (lane < 19 && 19 * jj + lane < 128)
          st_relaxed(&p.s->gate[128 * mt + 19 * jj + lane], pack2(0.f, 1.f / (1.f + __expf(-bf_round(mine)))) | (epoch & 0xffffu));
      }
      TL(9);
      if (lane < 2) mbar_arrive_cluster(BAR_XFREE(sb), lane);
      mbar_wait(BAR_XFREE(sb), 0);
      TL(3);
      const uint32_t yslot = (Q_XR + lane) % NSTAGE;
      bool todo = lane < 7;
      uint32_t n = 0;
      while (__any_sync(0xffffffffu, todo)) {
        if (todo) {
          uint32_t v;
          asm volatile("ld.acquire.gpu.global.u32 %0, [%1];" : "=r"(v) : "l"(&p.s->cnt_y[lane * 32]) : "memory");
          if ((int32_t)(v - epoch * (lane ? 16 : 17)) >= 0 || ++n > SPIN_LIMIT) {
            mbar_wait(BAR_EMPTY(sb, yslot), ((Q_XR + lane) / NSTAGE - 1) & 1);
            mbar_expect_tx(BAR_Y(sb, lane), 16384);
            tma3d(sb + SM_RING + yslot * STAGE_BYTES, &p.yt, 0, 64 * lane, 2 * mt, BAR_Y(sb, lane));
            todo = false;
          }
        }
      }
      TL(4);
      if (lane == 0) *my_epoch = epoch;
    } else {
      mbar_wait(BAR_X(sb, PFAT), 0);
      if (lane < 6) {
        int row = 176 + 3 * bid + (lane >> 1);
        if (row >= D_) row -= D_;
        l2_prefetch(((lane & 1) ? p.pwu : p.pwg) + row * F_, F_ * 2);
      }
      TL(2);
      bar_sync(7, 160);
      if (lane == 0) { fence_gpu(); red_add(&p.s->cnt_x1[jj * 32], 1); l2_prefetch(p.pwd + bid * 16 * D_, 32 * D_); }
      TL(3);
    }
  }
}

__device__ __forceinline__ void spectral_cta(uint32_t sb, uint8_t* smem, const Params& p, int sc, int wg) {
  const int t384 = threadIdx.x, lane = t384 & 31, warp12 = t384 >> 5, tid = t384 & 127;
  const int warp = tid >> 5, q = lane & 3;
  const int sl0 = 6 * sc + min(sc, 8), nsl = sc < 8 ? 7 : 6;
  if (t384 == 320) {
#pragma unroll 1
    for (int i = 0; i < nsl; i++) {
      mbar_expect_tx(BAR_X(sb, i), 2 * SLAB_BYTES);
      const int row = 128 * ((sl0 + i) >> 3) + 8 * ((sl0 + i) & 7);
      const uint32_t dst = sb + SP_Z + 2 * i * SLAB_BYTES;
      bulk_g2s(dst, p.w_r + row * DF_, SLAB_BYTES / 2, BAR_X(sb, i));
      bulk_g2s(dst + SLAB_BYTES / 2, p.w_r + (row + 64) * DF_, SLAB_BYTES / 2, BAR_X(sb, i));
      bulk_g2s(dst + SLAB_BYTES, p.w_i + row * DF_, SLAB_BYTES / 2, BAR_X(sb, i));
      bulk_g2s(dst + 3 * SLAB_BYTES / 2, p.w_i + (row + 64) * DF_, SLAB_BYTES / 2, BAR_X(sb, i));
    }
    if (sc < 19) {
      mbar_expect_tx(BAR_Y(sb, 6), 24576);
      bulk_g2s(sb + SP_TW, p.spec, 24576, BAR_Y(sb, 6));
    }
  }
  uint32_t* const my_epoch = &p.s->epoch[blockIdx.x * 12 + warp12];
  const uint32_t epoch = ld_relaxed(my_epoch) + 1;
  uint32_t fe[16], tw[16];
#pragma unroll
  for (int i = 0; i < 4; i++) {
    const uint4 a = __ldg(reinterpret_cast<const uint4*>(p.spec->fe) + i * 128 + tid);
    const uint4 b = __ldg(reinterpret_cast<const uint4*>(p.spec->tw) + i * 128 + tid);
    fe[4 * i] = a.x; fe[4 * i + 1] = a.y; fe[4 * i + 2] = a.z; fe[4 * i + 3] = a.w;
    tw[4 * i] = b.x; tw[4 * i + 1] = b.y; tw[4 * i + 2] = b.z; tw[4 * i + 3] = b.w;
  }
  __syncwarp();
  asm volatile("barrier.cluster.wait.acquire.aligned;" ::: "memory");
#pragma unroll 2
  for (int un = wg; un < 8 * nsl; un += 3) {
    const int i = un >> 3, sl = sl0 + i, pr = 16 * (un & 7) + 4 * (lane >> 3) + warp, r = lane & 7;
    mbar_wait(BAR_X(sb, i), 0);
    if (pr < 113) {
      const uint16_t* w = reinterpret_cast<const uint16_t*>(smem + SP_Z + 2 * i * SLAB_BYTES) + r * DF_ + 2 * pr;
      const uint32_t m = pr < 112 ? 0xffffffffu : 0u;
      p.s->wt[pr * 1024 + sl * 8 + (r ^ ((sl >> 2) & 6))] =
          make_uint4(w[0] | ((uint32_t)w[8 * DF_] << 16), w[16 * DF_] | ((uint32_t)w[24 * DF_] << 16),
                     (w[1] | ((uint32_t)w[8 * DF_ + 1] << 16)) & m, (w[16 * DF_ + 1] | ((uint32_t)w[24 * DF_ + 1] << 16)) & m);
    }
  }
  __syncthreads();
  if (t384 == 352) { fence_gpu(); red_add(&p.s->cnt_w[0], 1); }
  TL(1);
  if (sc == 19) return;
  const int nrnd = (sc == 18 && wg == 2) ? 1 : 2;
  if (tid == 32) {
    wait_counter(&p.s->cnt_w[0], epoch * NSPEC);
    fence_async();
    for (int rnd = 0; rnd < nrnd; rnd++) {
      const int item = wg + 3 * rnd;
      mbar_expect_tx(BAR_Y(sb, item), 16384);
      bulk_g2s(sb + SP_W + item * 16384, p.s->wt + (6 * sc + item) * 1024, 16384, BAR_Y(sb, item));
    }
  } else if (tid == 0) {
#pragma unroll 1
    for (int rnd = 0; rnd < nrnd; rnd++) {
      const int item = wg + 3 * rnd, pr = 6 * sc + item;
      wait_counter(&p.s->cnt_x1[(pr < 112 ? pr >> 4 : 0) * 32], epoch * 16);
      fence_async();
      const uint32_t bar = BAR_FULL(sb, item), z = sb + SP_Z + item * 16384;
      mbar_expect_tx(bar, 16384);
      bulk_g2s(z, p.s->x1t + pr * 1024, 16384, bar);
    }
  }
  __syncwarp();
  fence_regs(fe); fence_regs(tw);
  mbar_wait(BAR_Y(sb, 6), 0);
  TL(3);
  const uint64_t dT_n = mk_desc(sb + SP_T, 8192, 1024, 1);
#pragma unroll 1
  for (int rnd = 0; rnd < nrnd; rnd++) {
    const int item = wg + 3 * rnd, pr = 6 * sc + item;
    const uint32_t z = sb + SP_Z + item * 16384;
    uint32_t fa[16], fb[16];
    auto load_frag = [&](int off) {
#pragma unroll
      for (int i = 0; i < 4; i++) {
        const uint4 a = *reinterpret_cast<const uint4*>(smem + SP_TW + off + i * 2048 + tid * 16);
        fa[4 * i] = a.x; fa[4 * i + 1] = a.y; fa[4 * i + 2] = a.z; fa[4 * i + 3] = a.w;
      }
      fence_regs(fa);
    };
    load_frag(0);
    mbar_wait(BAR_FULL(sb, item), 0);
    TL(4 + 8 * rnd);
    if (rnd == 0 && wg > 0) bar_sync(3 + wg, 256);
    float aR[32], aI[32];
    {
      const uint64_t de = mk_desc(z, 4096, 512, 2);
      wg_fence();
#pragma unroll
      for (int kk = 0; kk < 4; kk++) {
        wgmma_rs_n64<1, 1>(aR, fe[4 * kk], fe[4 * kk + 1], fe[4 * kk + 2], fe[4 * kk + 3], de + kk * 64, kk != 0);
        wgmma_rs_n64<1, 1>(aI, fa[4 * kk], fa[4 * kk + 1], fa[4 * kk + 2], fa[4 * kk + 3], de + 512 + kk * 64, kk != 0);
      }
      wg_commit();
      if (rnd == 0 && wg < 2) bar_arrive(4 + wg, 256);
      wg_wait<0>();
      fence_regs(aR); fence_regs(aI);
    }
    TL(5 + 8 * rnd);
#pragma unroll
    for (int v = 0; v < 8; v++) {
      uint32_t* f = (v < 4 ? fa : fb) + 2 * (v & 3);
      const uint32_t* t = tw + 2 * (v & 3);
      const float *e = aR + 4 * v, *o = aI + 4 * v;
      const uint32_t er = pack2(e[0], e[1]), ei = pack2(e[2], e[3]), qr = pack2(o[0], o[1]), qi = pack2(o[2], o[3]);
      const uint32_t u0r = add2(er, qr), u0i = add2(ei, qi), u1r = sub2(er, qr), u1i = sub2(ei, qi);
      f[0] = fma2(u0r, t[0], mul2(u0i, t[8]));
      f[8] = fms2(u0i, t[0], mul2(u0r, t[8]));
      f[1] = fma2(u1r, t[1], mul2(u1i, t[9]));
      f[9] = fms2(u1i, t[1], mul2(u1r, t[9]));
    }
    fence_regs(fa); fence_regs(fb);
    wg_fence();
#pragma unroll
    for (int kk = 0; kk < 4; kk++) {
      wgmma_rs_n64<1, 1>(aR, fa[4 * kk], fa[4 * kk + 1], fa[4 * kk + 2], fa[4 * kk + 3], dT_n + kk * 128, kk != 0);
      wgmma_rs_n64<1, 1>(aI, fb[4 * kk], fb[4 * kk + 1], fb[4 * kk + 2], fb[4 * kk + 3], dT_n + kk * 128, kk != 0);
    }
    wg_commit();
    mbar_wait(BAR_Y(sb, item), 0);
    wg_wait<0>();
    fence_regs(aR); fence_regs(aI);
    TL(6 + 8 * rnd);
    {
      const uint8_t* wp = smem + SP_W + item * 16384 + q * 1024 + warp * 128 + (((lane >> 2) ^ (2 * q)) << 4);
#pragma unroll
      for (int jb = 0; jb < 4; jb++) {
#pragma unroll
        for (int h = 0; h < 2; h++) {
          const uint4 w = *reinterpret_cast<const uint4*>(wp + jb * 4096 + h * 512);
          const int i = 4 * jb + 2 * h;
          const uint32_t ar = pack2(aR[i], aR[i + 1]), ai = pack2(aR[16 + i], aR[17 + i]);
          const uint32_t br = pack2(aI[i], aI[i + 1]), bi = pack2(aI[16 + i], aI[17 + i]);
          fa[2 * jb + h] = fms2(ar, w.x, mul2(ai, w.y));
          fa[8 + 2 * jb + h] = fma2(ar, w.y, mul2(ai, w.x));
          fb[2 * jb + h] = fms2(br, w.z, mul2(bi, w.w));
          fb[8 + 2 * jb + h] = fma2(br, w.w, mul2(bi, w.z));
        }
      }
    }
    fence_regs(fa); fence_regs(fb);
    wg_fence();
#pragma unroll
    for (int kk = 0; kk < 4; kk++) {
      wgmma_rs_n64<1, 0>(aR, fa[4 * kk], fa[4 * kk + 1], fa[4 * kk + 2], fa[4 * kk + 3], dT_n + kk * 2, kk != 0);
      wgmma_rs_n64<1, 0>(aI, fb[4 * kk], fb[4 * kk + 1], fb[4 * kk + 2], fb[4 * kk + 3], dT_n + kk * 2, kk != 0);
    }
    wg_commit();
    wg_wait<0>();
    fence_regs(aR); fence_regs(aI);
    TL(7 + 8 * rnd);
#pragma unroll
    for (int v = 0; v < 8; v++) {
      const float* a = (v < 4 ? aR : aI) + 4 * (v & 3);
      const uint32_t* t = tw + 2 * (v & 3);
      const uint32_t u0r = pack2(a[0], a[1]), u1r = pack2(a[2], a[3]), u0i = pack2(a[16], a[17]), u1i = pack2(a[18], a[19]);
      const uint32_t t0r = fms2(u0r, t[0], mul2(u0i, t[8])), t0i = fma2(u0i, t[0], mul2(u0r, t[8]));
      const uint32_t t1r = fms2(u1r, t[1], mul2(u1i, t[9])), t1i = fma2(u1i, t[1], mul2(u1r, t[9]));
      fa[v] = add2(t0i, t1i); fa[8 + v] = add2(t0r, t1r);
      fb[v] = sub2(t0i, t1i); fb[8 + v] = sub2(t0r, t1r);
    }
    bar_sync(1 + wg, 128);
#pragma unroll
    for (int u = 0; u < 4; u++) {
      const uint32_t a = z + (32 * (u >> 1) + 8 * warp + (lane & 7)) * 128 + (((4 * (u & 1) + (lane >> 3)) ^ (lane & 7)) << 4);
      stmatrix_x4(a, fa[4 * u], fa[4 * u + 1], fa[4 * u + 2], fa[4 * u + 3]);
      stmatrix_x4(a + 8192, fb[4 * u], fb[4 * u + 1], fb[4 * u + 2], fb[4 * u + 3]);
    }
    load_frag(8192);
    fence_async_smem();
    bar_sync(1 + wg, 128);
    TL(8 + 8 * rnd);
    {
      const uint64_t de = mk_desc(z, 8192, 1024, 1);
      wg_fence();
#pragma unroll
      for (int kk = 0; kk < 4; kk++) {
        wgmma_rs_n64<1, 1>(aR, fe[4 * kk], fe[4 * kk + 1], fe[4 * kk + 2], fe[4 * kk + 3], de + kk * 128, kk != 0);
        wgmma_rs_n64<1, 1>(aI, fa[4 * kk], fa[4 * kk + 1], fa[4 * kk + 2], fa[4 * kk + 3], de + 512 + kk * 128, kk != 0);
      }
      wg_commit();
      wg_wait<0>();
      fence_regs(aR); fence_regs(aI);
    }
    TL(9 + 8 * rnd);
    const bool edge = pr == 0 || pr == 112;
    if (edge) {
#pragma unroll
      for (int i = 0; i < 16; i++) { aR[i] *= 0.5f; aI[i] *= 0.5f; }
    }
#pragma unroll
    for (int i = 0; i < 8; i++) {
      const float* a = ((i & 1) ? aI : aR) + 16 * (i >> 2) + 2 - (i & 2);
      *reinterpret_cast<uint4*>(smem + SP_W + item * 16384 + (i >> 1) * 4096 + (i & 1) * 64 + (tid >> 2) * 128 + q * 16) =
          make_uint4(pack2(a[0], a[1]), pack2(a[4], a[5]), pack2(a[8], a[9]), pack2(a[12], a[13]));
    }
    fence_async_smem();
    bar_sync(1 + wg, 128);
    if (tid == 0) {
      const uint32_t src = sb + SP_W + item * 16384;
      __nv_bfloat16* dst = p.s->yt + (size_t)(pr < 112 ? 4 * pr : 1) * S_;
      bulk_s2g(dst, src, edge ? 4096 : 16384);
      if (pr == 0) bulk_s2g(dst + 2 * S_, src + 8192, 8192);
      asm volatile("cp.async.bulk.commit_group;" ::: "memory");
      if (rnd == nrnd - 1) {
        asm volatile("cp.async.bulk.wait_group 0;" ::: "memory");
        TL(11);
        fence_async();
        fence_gpu();
        red_add(&p.s->cnt_y[(pr < 112 ? pr >> 4 : 0) * 32], 1);
        if (rnd) red_add(&p.s->cnt_y[((pr - 3) >> 4) * 32], 1);
      }
    }
    __syncwarp();
    TL(10 + 8 * rnd);
  }
  if (lane == 0) *my_epoch = epoch;
}

__global__ void __cluster_dims__(2, 1, 1) __launch_bounds__(384, 1)
fused_kernel(const __grid_constant__ Params p) {
  extern __shared__ __align__(1024) uint8_t smem[];
  const uint32_t sb = smem_u32(smem);
  TL(0);
  const uint32_t rank = blockIdx.x & 1;
  const int hc = blockIdx.x >> 1;
  int grp, jj;
  if (hc < 4) { grp = 8; jj = hc; }
  else if (hc < 36) { grp = (hc - 4) & 7; jj = (hc - 4) >> 3; }
  else if (hc < 57) { jj = (hc - 36) / 7; grp = 1 + (hc - 36) - 7 * jj; jj += 4; }
  else if (hc < 60) { grp = 0; jj = hc - 53; }
  else { grp = 8; jj = hc - 56; }
  const int mt = 2 * grp + rank, bid = 2 * (7 * grp + jj) + rank;
  if (threadIdx.x == 256) {
#pragma unroll
    for (int i = 0; i < NSTAGE; i++) { mbar_init(BAR_FULL(sb, i), 1); mbar_init(BAR_EMPTY(sb, i), 4); }
    asm volatile("fence.mbarrier_init.release.cluster;" ::: "memory");
  } else if (threadIdx.x == 320) {
#pragma unroll
    for (int i = 0; i < NSTAGE; i++) { mbar_init(BAR_X(sb, i), 1); mbar_init(BAR_Y(sb, i), 1); }
    mbar_init(BAR_XFREE(sb), 6);
#pragma unroll
    for (int i = 0; i < 4; i++) mbar_init(BAR_E2(sb, i), 4);
    asm volatile("fence.mbarrier_init.release.cluster;" ::: "memory");
  } else if (threadIdx.x == 288) {
    prefetch_tmap(rank ? &p.wu : &p.wg); prefetch_tmap(&p.ct);
  }
  __syncwarp();
  asm volatile("barrier.cluster.arrive.relaxed.aligned;" ::: "memory");
  const int wg = __shfl_sync(0xffffffffu, threadIdx.x >> 7, 0);
  if (bid >= NFFN) {
    spectral_cta(sb, smem, p, bid - NFFN, wg);
  } else if (wg < 2) {
    asm volatile("setmaxnreg.inc.sync.aligned.u32 232;");
    asm volatile("barrier.cluster.wait.acquire.aligned;" ::: "memory");
    TL(1);
    ffn_consumer(sb, smem, p, bid, wg, threadIdx.x & 127, mt, jj);
  } else {
    asm volatile("setmaxnreg.dec.sync.aligned.u32 40;");
    if (threadIdx.x == 320) {
      mbar_expect_tx(BAR_X(sb, 0), 16384);
      tma2d(sb + SM_X, &p.x, 0, 128 * mt, BAR_X(sb, 0));
    }
    __syncwarp();
    asm volatile("barrier.cluster.wait.acquire.aligned;" ::: "memory");
    TL(1);
    if (threadIdx.x == 320) {
      constexpr int order[13] = {XORDER};
#pragma unroll
      for (int i = 0; i < 13; i++) {
        if (order[i] < 8) {
          ring_issue(sb, p, order[i], order[i], false, 0, jj, rank);
        } else {
          const int kb = order[i] - 10;
          mbar_expect_tx(BAR_X(sb, kb), 16384);
          tma2d(sb + SM_X + kb * 16384, &p.x, 64 * kb, 128 * mt, BAR_X(sb, kb));
        }
      }
      TL(2);
    } else if (threadIdx.x == 352) {
    }
    __syncwarp();
    ffn_producer(sb, smem, bid, p, (threadIdx.x >> 5) & 3, threadIdx.x & 31, mt, jj, rank);
  }
}

typedef CUresult (*EncodeFn)(CUtensorMap*, CUtensorMapDataType, cuuint32_t, void*, const cuuint64_t*, const cuuint64_t*,
                             const cuuint32_t*, const cuuint32_t*, CUtensorMapInterleave, CUtensorMapSwizzle,
                             CUtensorMapL2promotion, CUtensorMapFloatOOBfill);

void make_map(EncodeFn fn, CUtensorMap* m, const void* base, int rank, const cuuint64_t* dims, const cuuint64_t* strides,
              const cuuint32_t* box, CUtensorMapSwizzle sw) {
  const cuuint32_t es[4] = {1, 1, 1, 1};
  fn(m, CU_TENSOR_MAP_DATA_TYPE_BFLOAT16, rank, const_cast<void*>(base), dims, strides, box, es,
     CU_TENSOR_MAP_INTERLEAVE_NONE, sw, CU_TENSOR_MAP_L2_PROMOTION_L2_256B, CU_TENSOR_MAP_FLOAT_OOB_FILL_NONE);
}

}

extern "C" void kernel_launch(void* const* d_in, const int* in_sizes, int n_in, void* d_out, int out_size) {
  const __nv_bfloat16* x = (const __nv_bfloat16*)d_in[0];
  const __nv_bfloat16* w_r = (const __nv_bfloat16*)d_in[1];
  const __nv_bfloat16* w_i = (const __nv_bfloat16*)d_in[2];
  const __nv_bfloat16* wg = (const __nv_bfloat16*)d_in[4];
  const __nv_bfloat16* wu = (const __nv_bfloat16*)d_in[5];
  const __nv_bfloat16* wd = (const __nv_bfloat16*)d_in[6];
  const __nv_bfloat16* gate_w = (const __nv_bfloat16*)d_in[7];

  void* fnp = nullptr;
  cudaDriverEntryPointQueryResult qr;
  cudaGetDriverEntryPoint("cuTensorMapEncodeTiled", &fnp, cudaEnableDefault, &qr);
  EncodeFn fn = (EncodeFn)fnp;
  void *ctab, *spec, *scr;
  cudaGetSymbolAddress(&ctab, g_ctab);
  cudaGetSymbolAddress(&spec, g_spec);
  cudaGetSymbolAddress(&scr, g_scratch);
  const void* yt = (const char*)scr + offsetof(Scratch, yt);
  Params p;
  p.s = (Scratch*)scr; p.out = (__nv_bfloat16*)d_out;
  p.px = x; p.w_r = w_r; p.w_i = w_i; p.gate_w = gate_w; p.pwg = wg; p.pwu = wu; p.pwd = wd;
  p.ctab = (const tab::Table*)ctab; p.spec = (const tab::Spec*)spec;
  {
    const cuuint64_t d[2] = {D_, S_}, s[1] = {D_ * 2};
    const cuuint32_t b[2] = {64, 128};
    make_map(fn, &p.x, x, 2, d, s, b, CU_TENSOR_MAP_SWIZZLE_128B);
  }
  {
    const cuuint64_t d[3] = {64, D_, F_ / 64}, s[2] = {F_ * 2, 128};
    const cuuint32_t b[3] = {64, 32, 2};
    make_map(fn, &p.wg, wg, 3, d, s, b, CU_TENSOR_MAP_SWIZZLE_128B);
    make_map(fn, &p.wu, wu, 3, d, s, b, CU_TENSOR_MAP_SWIZZLE_128B);
  }
  {
    const cuuint64_t d[2] = {D_, F_}, s[1] = {D_ * 2};
    const cuuint32_t b[2] = {64, 64};
    make_map(fn, &p.wd, wd, 2, d, s, b, CU_TENSOR_MAP_SWIZZLE_128B);
  }
  {
    const cuuint64_t d[2] = {D_, D_}, s[1] = {D_ * 2};
    const cuuint32_t b[2] = {64, 64};
    make_map(fn, &p.ct, ctab, 2, d, s, b, CU_TENSOR_MAP_SWIZZLE_128B);
  }
  {
    const cuuint64_t d[3] = {64, D_, S_ / 64}, s[2] = {S_ * 2, 128};
    const cuuint32_t b[3] = {64, 64, 2};
    make_map(fn, &p.yt, yt, 3, d, s, b, CU_TENSOR_MAP_SWIZZLE_128B);
  }
  cudaFuncSetAttribute(fused_kernel, cudaFuncAttributeMaxDynamicSharedMemorySize, SM_TOTAL);
  fused_kernel<<<NCTA, 384, SM_TOTAL, cudaStreamPerThread>>>(p, x, w_r, w_i, gate_w, wd, (__nv_bfloat16*)d_out);
}
```

```cpp
#include <cuda_runtime.h>
#include <cuda_bf16.h>
#include <cuda.h>
#include <stdint.h>
#include <stddef.h>

namespace {

constexpr int S_ = 2048, D_ = 448, F_ = 1792, DF_ = 225;
constexpr int NFFN = 112, NSPEC = 20, NCTA = NFFN + NSPEC;
constexpr int NSTAGE = 7, STAGE_BYTES = 16384;
constexpr int SM_X = 0, SM_RING = 114688, SM_BAR = 229376, SM_TOTAL = SM_BAR + 512;
constexpr int SP_Z = 0, SP_W = 98304, SP_TW = 198656, SP_T = 215040, SLAB_BYTES = 16 * DF_ * 2;
constexpr uint32_t SPIN_LIMIT = 1u << 20;

namespace tab {
constexpr double PI = 3.14159265358979323846264338327950288;
constexpr double csin(double x) {
  double t = x, s = x;
  for (int i = 1; i < 20; i++) { t = -t * x * x / ((2 * i) * (2 * i + 1)); s += t; }
  return s;
}
constexpr double ccos(double x) {
  double t = 1, s = 1;
  for (int i = 1; i < 20; i++) { t = -t * x * x / ((2 * i - 1) * (2 * i)); s += t; }
  return s;
}
constexpr uint32_t to_bf16(double v) {
  uint32_t sign = v < 0 ? 0x8000u : 0u;
  double a = v < 0 ? -v : v;
  if (a < 1e-12) return 0;
  int e = 0;
  while (a >= 2.0) { a /= 2; e++; }
  while (a < 1.0) { a *= 2; e--; }
  double m = a * 128.0;
  int mi = (int)m;
  double fr = m - mi;
  if (fr > 0.5 || (fr == 0.5 && (mi & 1))) mi++;
  if (mi == 256) { mi = 128; e++; }
  return sign | (uint32_t)((e + 127) << 7) | (uint32_t)(mi - 128);
}
struct Base { uint32_t v[448]; };
constexpr Base make_base() {
  Base b{};
  for (int m = 0; m < 448; m++) {
    int mm = m > 224 ? m - 448 : m;
    double ang = 2 * PI * mm / 448.0;
    b.v[m] = to_bf16(ccos(ang)) | (to_bf16(-csin(ang)) << 16);
  }
  return b;
}
constexpr Base base = make_base();
struct Row { uint32_t v[224]; };
constexpr Row make_row(int d) {
  Row r{};
  r.v[0] = 0x3f80u | ((d & 1) ? 0xbf800000u : 0x3f800000u);
  int m = 0;
  for (int c = 1; c < 224; c++) { m += d; if (m >= 448) m -= 448; r.v[c] = base.v[m]; }
  return r;
}
struct Table { Row r[448]; };
constexpr Table make_table() {
  Table t{};
  for (int d = 0; d < 448; d++) t.r[d] = make_row(d);
  return t;
}
struct Cs { double c[2048], s[2048]; };
constexpr Cs make_cs() {
  Cs t{};
  for (int m = 0; m <= 256; m++) {
    const double a = 2 * PI * m / 2048.0, c = ccos(a), s = csin(a);
    t.c[m] = c; t.s[m] = s;
    t.c[512 - m] = s; t.s[512 - m] = c;
  }
  for (int m = 513; m < 2048; m++) { t.c[m] = -t.s[m - 512]; t.s[m] = t.c[m - 512]; }
  return t;
}
constexpr Cs cs = make_cs();
struct Spec {
  uint32_t fo[2048], fot[2048];
  uint16_t t32[4096];
  uint32_t fe[2048];
  uint32_t tw[2048];
};
constexpr uint32_t blk(int h, int c, int a) { return to_bf16(h == c ? cs.c[a & 2047] : (h ? -cs.s[a & 2047] : cs.s[a & 2047])); }
constexpr Spec make_spec() {
  Spec t{};
  for (int row = 0; row < 64; row++)
    for (int col = 0; col < 64; col++) {
      const int c = row & 31, k2 = col & 31, n2 = 8 * ((c >> 1) & 3) + 2 * (c >> 3) + (c & 1), m = 64 * ((n2 * k2) & 31);
      const double v = (row >> 5) == (col >> 5) ? cs.c[m] : (row < 32 ? -cs.s[m] : cs.s[m]);
      t.t32[row * 64 + (((col >> 3) ^ (row & 7)) << 3) + (col & 7)] = (uint16_t)to_bf16(v);
    }
  for (int th = 0; th < 128; th++)
    for (int i = 0; i < 16; i++) {
      const int r = 8 * (th >> 5) + ((th & 31) >> 2), h = i & 1, c = i >> 3, m = 8 * ((i >> 1) & 3) + 2 * (th & 3);
      const int o = ((i >> 2) * 128 + th) * 4 + (i & 3);
      t.fe[o] = blk(h, c, 64 * m * r) | (blk(h, c, 64 * (m + 1) * r) << 16);
      t.fo[o] = blk(h, c, 32 * (2 * m + 1) * r) | (blk(h, c, 32 * (2 * m + 3) * r) << 16);
      t.fot[o] = blk(h, c, 32 * (2 * r + 1) * m) | (blk(h, c, 32 * (2 * r + 1) * (m + 1)) << 16);
      const int k1 = r + 32 * h, n2 = 8 * (th & 3) + 2 * ((i >> 1) & 3);
      t.tw[o] = blk(0, c, n2 * k1) | (blk(0, c, (n2 + 1) * k1) << 16);
    }
  return t;
}
}
}

__device__ __align__(1024) const tab::Table g_ctab = tab::make_table();
__device__ __align__(1024) const tab::Spec g_spec = tab::make_spec();

struct Scratch {
  uint32_t cnt_w[32];
  uint32_t cnt_x1[7 * 32];
  uint32_t cnt_y[7 * 32];
  uint32_t epoch[NCTA * 12 + 240 + 256];
  uint32_t gate[S_];
  uint4 x1t[113 * 1024];
  __nv_bfloat16 yt[D_ * S_];
  uint4 wt[114 * 1024];
  uint4 part[16 * 7 * 6 * 2 * 4 * 128];
};
static_assert(offsetof(Scratch, x1t) % 1024 == 0, "alignment");
__device__ __align__(1024) Scratch g_scratch;
#define TL(i)

namespace {

struct Params {
  Scratch* s;
  __nv_bfloat16* out;
  const __nv_bfloat16 *px, *w_r, *w_i, *gate_w, *pwg, *pwu, *pwd;
  const tab::Table* ctab;
  const tab::Spec* spec;
  CUtensorMap x, wg, wu, wd, ct, yt;
};

__device__ __forceinline__ uint32_t smem_u32(const void* p) { return (uint32_t)__cvta_generic_to_shared(p); }
__device__ __forceinline__ void mbar_init(uint32_t bar, uint32_t cnt) {
  asm volatile("mbarrier.init.shared::cta.b64 [%0], %1;" ::"r"(bar), "r"(cnt) : "memory");
}
__device__ __forceinline__ void mbar_expect_tx(uint32_t bar, uint32_t bytes) {
  asm volatile("mbarrier.arrive.expect_tx.shared::cta.b64 _, [%0], %1;" ::"r"(bar), "r"(bytes) : "memory");
}
__device__ __forceinline__ void mbar_arrive(uint32_t bar) {
  asm volatile("mbarrier.arrive.shared::cta.b64 _, [%0];" ::"r"(bar) : "memory");
}
__device__ __forceinline__ void mbar_arrive_cluster(uint32_t bar, uint32_t cta) {
  asm volatile("{\n.reg .b32 ra;\nmapa.shared::cluster.u32 ra, %0, %1;\n"
               "mbarrier.arrive.shared::cluster.b64 _, [ra];\n}" ::"r"(bar), "r"(cta) : "memory");
}
__device__ __forceinline__ void mbar_wait(uint32_t bar, uint32_t parity) {
  uint32_t ok, n = 0;
  do {
    asm volatile("{\n.reg .pred p;\nmbarrier.try_wait.parity.shared::cta.b64 p, [%1], %2;\nselp.u32 %0, 1, 0, p;\n}"
                 : "=r"(ok) : "r"(bar), "r"(parity) : "memory");
  } while (!ok && ++n < SPIN_LIMIT);
}
__device__ __forceinline__ void mbar_wait_cluster(uint32_t bar, uint32_t parity) {
  uint32_t ok, n = 0;
  do {
    asm volatile("{\n.reg .pred p;\nmbarrier.try_wait.parity.acquire.cluster.shared::cta.b64 p, [%1], %2;\nselp.u32 %0, 1, 0, p;\n}"
                 : "=r"(ok) : "r"(bar), "r"(parity) : "memory");
  } while (!ok && ++n < SPIN_LIMIT);
}
__device__ __forceinline__ void tma2d(uint32_t dst, const CUtensorMap* m, int c0, int c1, uint32_t bar) {
  asm volatile("cp.async.bulk.tensor.2d.shared::cluster.global.mbarrier::complete_tx::bytes [%0], [%1, {%3, %4}], [%2];"
               ::"r"(dst), "l"(m), "r"(bar), "r"(c0), "r"(c1) : "memory");
}
__device__ __forceinline__ void tma3d(uint32_t dst, const CUtensorMap* m, int c0, int c1, int c2, uint32_t bar) {
  asm volatile("cp.async.bulk.tensor.3d.shared::cluster.global.mbarrier::complete_tx::bytes [%0], [%1, {%3, %4, %5}], [%2];"
               ::"r"(dst), "l"(m), "r"(bar), "r"(c0), "r"(c1), "r"(c2) : "memory");
}
__device__ __forceinline__ void tma2d_mc(uint32_t dst, const CUtensorMap* m, int c0, int c1, uint32_t bar) {
  asm volatile("cp.async.bulk.tensor.2d.shared::cluster.global.mbarrier::complete_tx::bytes.multicast::cluster [%0], [%1, {%3, %4}], [%2], %5;"
               ::"r"(dst), "l"(m), "r"(bar), "r"(c0), "r"(c1), "h"((uint16_t)3) : "memory");
}
__device__ __forceinline__ void tma3d_mc(uint32_t dst, const CUtensorMap* m, int c0, int c1, int c2, uint32_t bar) {
  asm volatile("cp.async.bulk.tensor.3d.shared::cluster.global.mbarrier::complete_tx::bytes.multicast::cluster [%0], [%1, {%3, %4, %5}], [%2], %6;"
               ::"r"(dst), "l"(m), "r"(bar), "r"(c0), "r"(c1), "r"(c2), "h"((uint16_t)3) : "memory");
}
__device__ __forceinline__ void bulk_g2s(uint32_t dst, const void* src, uint32_t bytes, uint32_t bar) {
  asm volatile("cp.async.bulk.shared::cluster.global.mbarrier::complete_tx::bytes [%0], [%1], %2, [%3];"
               ::"r"(dst), "l"(src), "r"(bytes), "r"(bar) : "memory");
}
__device__ __forceinline__ void bulk_s2g(void* dst, uint32_t src, uint32_t bytes) {
  asm volatile("cp.async.bulk.global.shared::cta.bulk_group [%0], [%1], %2;" ::"l"(dst), "r"(src), "r"(bytes) : "memory");
}
__device__ __forceinline__ void prefetch_tmap(const CUtensorMap* m) {
  asm volatile("prefetch.tensormap [%0];" ::"l"(m) : "memory");
}
__device__ __forceinline__ void l2_prefetch(const void* p, uint32_t bytes) {
  asm volatile("cp.async.bulk.prefetch.L2.global [%0], %1;" ::"l"(p), "r"(bytes) : "memory");
}
__device__ __forceinline__ void wg_fence() { asm volatile("wgmma.fence.sync.aligned;" ::: "memory"); }
__device__ __forceinline__ void wg_commit() { asm volatile("wgmma.commit_group.sync.aligned;" ::: "memory"); }
template <int N> __device__ __forceinline__ void wg_wait() { asm volatile("wgmma.wait_group.sync.aligned %0;" ::"n"(N) : "memory"); }
template <int N> __device__ __forceinline__ void fence_regs(float (&d)[N]) {
#pragma unroll
  for (int i = 0; i < N; i++) asm volatile("" : "+f"(d[i])::"memory");
}
template <int N> __device__ __forceinline__ void fence_regs(uint32_t (&d)[N]) {
#pragma unroll
  for (int i = 0; i < N; i++) asm volatile("" : "+r"(d[i])::"memory");
}
__device__ __forceinline__ void bar_sync(int id, int n) { asm volatile("bar.sync %0, %1;" ::"r"(id), "r"(n) : "memory"); }
__device__ __forceinline__ void bar_arrive(int id, int n) { asm volatile("bar.arrive %0, %1;" ::"r"(id), "r"(n) : "memory"); }
__device__ __forceinline__ void fence_gpu() { asm volatile("fence.acq_rel.gpu;" ::: "memory"); }
__device__ __forceinline__ void fence_async() { asm volatile("fence.proxy.async;" ::: "memory"); }
__device__ __forceinline__ void fence_async_smem() { asm volatile("fence.proxy.async.shared::cta;" ::: "memory"); }
__device__ __forceinline__ void red_add(uint32_t* p, uint32_t v) {
  asm volatile("red.relaxed.gpu.global.add.u32 [%0], %1;" ::"l"(p), "r"(v) : "memory");
}
__device__ __forceinline__ uint32_t ld_relaxed(const uint32_t* p) {
  uint32_t v;
  asm volatile("ld.relaxed.gpu.global.u32 %0, [%1];" : "=r"(v) : "l"(p) : "memory");
  return v;
}
__device__ __forceinline__ void wait_counter(const uint32_t* p, uint32_t target) {
  uint32_t v, n = 0;
  while (true) {
    asm volatile("ld.acquire.gpu.global.u32 %0, [%1];" : "=r"(v) : "l"(p) : "memory");
    if ((int32_t)(v - target) >= 0 || ++n > SPIN_LIMIT) break;
  }
}
__device__ __forceinline__ uint4 ld_relaxed(const uint4* p) {
  uint4 v;
  asm volatile("ld.relaxed.gpu.global.v4.u32 {%0, %1, %2, %3}, [%4];" : "=r"(v.x), "=r"(v.y), "=r"(v.z), "=r"(v.w) : "l"(p) : "memory");
  return v;
}
__device__ __forceinline__ void st_relaxed(uint4* p, uint4 v) {
  asm volatile("st.relaxed.gpu.global.v4.u32 [%0], {%1, %2, %3, %4};" ::"l"(p), "r"(v.x), "r"(v.y), "r"(v.z), "r"(v.w) : "memory");
}
__device__ __forceinline__ void st_relaxed(uint32_t* p, uint32_t v) {
  asm volatile("st.relaxed.gpu.global.u32 [%0], %1;" ::"l"(p), "r"(v) : "memory");
}
__device__ __forceinline__ uint32_t pack2(float lo, float hi) {
  uint32_t r;
  asm("cvt.rn.bf16x2.f32 %0, %1, %2;" : "=r"(r) : "f"(hi), "f"(lo));
  return r;
}
__device__ __forceinline__ uint32_t mul2(uint32_t a, uint32_t b) {
  uint32_t r;
  asm("mul.rn.bf16x2 %0, %1, %2;" : "=r"(r) : "r"(a), "r"(b));
  return r;
}
__device__ __forceinline__ uint32_t fma2(uint32_t a, uint32_t b, uint32_t c) {
  uint32_t r;
  asm("fma.rn.bf16x2 %0, %1, %2, %3;" : "=r"(r) : "r"(a), "r"(b), "r"(c));
  return r;
}
__device__ __forceinline__ uint32_t add2(uint32_t a, uint32_t b) {
  uint32_t r;
  asm("add.rn.bf16x2 %0, %1, %2;" : "=r"(r) : "r"(a), "r"(b));
  return r;
}
__device__ __forceinline__ uint32_t sub2(uint32_t a, uint32_t b) {
  uint32_t r;
  asm("sub.rn.bf16x2 %0, %1, %2;" : "=r"(r) : "r"(a), "r"(b));
  return r;
}
__device__ __forceinline__ uint32_t fms2(uint32_t a, uint32_t b, uint32_t c) {
  uint32_t r;
  asm("{\n.reg .b32 n;\nneg.bf16x2 n, %3;\nfma.rn.bf16x2 %0, %1, %2, n;\n}" : "=r"(r) : "r"(a), "r"(b), "r"(c));
  return r;
}
__device__ __forceinline__ float bf_lo(uint32_t v) { return __uint_as_float(v << 16); }
__device__ __forceinline__ float bf_hi(uint32_t v) { return __uint_as_float(v & 0xffff0000u); }
__device__ __forceinline__ float bf_round(float v) { return bf_lo(pack2(v, 0.f)); }
__device__ __forceinline__ float tanh_fast(float v) {
  float r;
  asm("tanh.approx.f32 %0, %1;" : "=f"(r) : "f"(v));
  return r;
}
__device__ __forceinline__ uint64_t mk_desc(uint32_t addr, uint32_t lbo, uint32_t sbo, uint32_t mode) {
  return (uint64_t)((addr & 0x3FFFF) >> 4) | ((uint64_t)(lbo >> 4) << 16) | ((uint64_t)(sbo >> 4) << 32) | ((uint64_t)mode << 62);
}
__device__ __forceinline__ void stmatrix_x4(uint32_t addr, uint32_t r0, uint32_t r1, uint32_t r2, uint32_t r3) {
  asm volatile("stmatrix.sync.aligned.m8n8.x4.shared.b16 [%0], {%1, %2, %3, %4};" ::"r"(addr), "r"(r0), "r"(r1), "r"(r2), "r"(r3) : "memory");
}

template <int TA, int TB>
__device__ __forceinline__ void wgmma_ss_n256(float (&d)[128], uint64_t da, uint64_t db, int sd) {
  asm volatile("{\n.reg .pred p;\nsetp.ne.b32 p, %130, 0;\n"
      "wgmma.mma_async.sync.aligned.m64n256k16.f32.bf16.bf16 {"
      "%0, %1, %2, %3, %4, %5, %6, %7, %8, %9, %10, %11, %12, %13, %14, %15, %16, %17, %18, %19, %20, %21, %22, %23, "
      "%24, %25, %26, %27, %28, %29, %30, %31, %32, %33, %34, %35, %36, %37, %38, %39, %40, %41, %42, %43, %44, %45, "
      "%46, %47, %48, %49, %50, %51, %52, %53, %54, %55, %56, %57, %58, %59, %60, %61, %62, %63, %64, %65, %66, %67, "
      "%68, %69, %70, %71, %72, %73, %74, %75, %76, %77, %78, %79, %80, %81, %82, %83, %84, %85, %86, %87, %88, %89, "
      "%90, %91, %92, %93, %94, %95, %96, %97, %98, %99, %100, %101, %102, %103, %104, %105, %106, %107, %108, %109, "
      "%110, %111, %112, %113, %114, %115, %116, %117, %118, %119, %120, %121, %122, %123, %124, %125, %126, %127"
      "}, %128, %129, p, 1, 1, %131, %132;\n}\n"
      : "+f"(d[0]), "+f"(d[1]), "+f"(d[2]), "+f"(d[3]), "+f"(d[4]), "+f"(d[5]), "+f"(d[6]), "+f"(d[7]), "+f"(d[8]),
        "+f"(d[9]), "+f"(d[10]), "+f"(d[11]), "+f"(d[12]), "+f"(d[13]), "+f"(d[14]), "+f"(d[15]), "+f"(d[16]),
        "+f"(d[17]), "+f"(d[18]), "+f"(d[19]), "+f"(d[20]), "+f"(d[21]), "+f"(d[22]), "+f"(d[23]), "+f"(d[24]),
        "+f"(d[25]), "+f"(d[26]), "+f"(d[27]), "+f"(d[28]), "+f"(d[29]), "+f"(d[30]), "+f"(d[31]), "+f"(d[32]),
        "+f"(d[33]), "+f"(d[34]), "+f"(d[35]), "+f"(d[36]), "+f"(d[37]), "+f"(d[38]), "+f"(d[39]), "+f"(d[40]),
        "+f"(d[41]), "+f"(d[42]), "+f"(d[43]), "+f"(d[44]), "+f"(d[45]), "+f"(d[46]), "+f"(d[47]), "+f"(d[48]),
        "+f"(d[49]), "+f"(d[50]), "+f"(d[51]), "+f"(d[52]), "+f"(d[53]), "+f"(d[54]), "+f"(d[55]), "+f"(d[56]),
        "+f"(d[57]), "+f"(d[58]), "+f"(d[59]), "+f"(d[60]), "+f"(d[61]), "+f"(d[62]), "+f"(d[63]), "+f"(d[64]),
        "+f"(d[65]), "+f"(d[66]), "+f"(d[67]), "+f"(d[68]), "+f"(d[69]), "+f"(d[70]), "+f"(d[71]), "+f"(d[72]),
        "+f"(d[73]), "+f"(d[74]), "+f"(d[75]), "+f"(d[76]), "+f"(d[77]), "+f"(d[78]), "+f"(d[79]), "+f"(d[80]),
        "+f"(d[81]), "+f"(d[82]), "+f"(d[83]), "+f"(d[84]), "+f"(d[85]), "+f"(d[86]), "+f"(d[87]), "+f"(d[88]),
        "+f"(d[89]), "+f"(d[90]), "+f"(d[91]), "+f"(d[92]), "+f"(d[93]), "+f"(d[94]), "+f"(d[95]), "+f"(d[96]),
        "+f"(d[97]), "+f"(d[98]), "+f"(d[99]), "+f"(d[100]), "+f"(d[101]), "+f"(d[102]), "+f"(d[103]), "+f"(d[104]),
        "+f"(d[105]), "+f"(d[106]), "+f"(d[107]), "+f"(d[108]), "+f"(d[109]), "+f"(d[110]), "+f"(d[111]),
        "+f"(d[112]), "+f"(d[113]), "+f"(d[114]), "+f"(d[115]), "+f"(d[116]), "+f"(d[117]), "+f"(d[118]),
        "+f"(d[119]), "+f"(d[120]), "+f"(d[121]), "+f"(d[122]), "+f"(d[123]), "+f"(d[124]), "+f"(d[125]),
        "+f"(d[126]), "+f"(d[127])
      : "l"(da), "l"(db), "r"(sd), "n"(TA), "n"(TB));
}
template <int TA, int TB>
__device__ __forceinline__ void wgmma_ss_n128(float (&d)[64], uint64_t da, uint64_t db, int sd) {
  asm volatile("{\n.reg .pred p;\nsetp.ne.b32 p, %66, 0;\n"
      "wgmma.mma_async.sync.aligned.m64n128k16.f32.bf16.bf16 {"
      "%0, %1, %2, %3, %4, %5, %6, %7, %8, %9, %10, %11, %12, %13, %14, %15, %16, %17, %18, %19, %20, %21, %22, %23, "
      "%24, %25, %26, %27, %28, %29, %30, %31, %32, %33, %34, %35, %36, %37, %38, %39, %40, %41, %42, %43, %44, %45, "
      "%46, %47, %48, %49, %50, %51, %52, %53, %54, %55, %56, %57, %58, %59, %60, %61, %62, %63"
      "}, %64, %65, p, 1, 1, %67, %68;\n}\n"
      : "+f"(d[0]), "+f"(d[1]), "+f"(d[2]), "+f"(d[3]), "+f"(d[4]), "+f"(d[5]), "+f"(d[6]), "+f"(d[7]), "+f"(d[8]),
        "+f"(d[9]), "+f"(d[10]), "+f"(d[11]), "+f"(d[12]), "+f"(d[13]), "+f"(d[14]), "+f"(d[15]), "+f"(d[16]),
        "+f"(d[17]), "+f"(d[18]), "+f"(d[19]), "+f"(d[20]), "+f"(d[21]), "+f"(d[22]), "+f"(d[23]), "+f"(d[24]),
        "+f"(d[25]), "+f"(d[26]), "+f"(d[27]), "+f"(d[28]), "+f"(d[29]), "+f"(d[30]), "+f"(d[31]), "+f"(d[32]),
        "+f"(d[33]), "+f"(d[34]), "+f"(d[35]), "+f"(d[36]), "+f"(d[37]), "+f"(d[38]), "+f"(d[39]), "+f"(d[40]),
        "+f"(d[41]), "+f"(d[42]), "+f"(d[43]), "+f"(d[44]), "+f"(d[45]), "+f"(d[46]), "+f"(d[47]), "+f"(d[48]),
        "+f"(d[49]), "+f"(d[50]), "+f"(d[51]), "+f"(d[52]), "+f"(d[53]), "+f"(d[54]), "+f"(d[55]), "+f"(d[56]),
        "+f"(d[57]), "+f"(d[58]), "+f"(d[59]), "+f"(d[60]), "+f"(d[61]), "+f"(d[62]), "+f"(d[63])
      : "l"(da), "l"(db), "r"(sd), "n"(TA), "n"(TB));
}
template <int TA, int TB>
__device__ __forceinline__ void wgmma_ss_n64(float (&d)[32], uint64_t da, uint64_t db, int sd) {
  asm volatile("{\n.reg .pred p;\nsetp.ne.b32 p, %34, 0;\n"
      "wgmma.mma_async.sync.aligned.m64n64k16.f32.bf16.bf16 {"
      "%0, %1, %2, %3, %4, %5, %6, %7, %8, %9, %10, %11, %12, %13, %14, %15, %16, %17, %18, %19, %20, %21, %22, %23, "
      "%24, %25, %26, %27, %28, %29, %30, %31"
      "}, %32, %33, p, 1, 1, %35, %36;\n}\n"
      : "+f"(d[0]), "+f"(d[1]), "+f"(d[2]), "+f"(d[3]), "+f"(d[4]), "+f"(d[5]), "+f"(d[6]), "+f"(d[7]), "+f"(d[8]),
        "+f"(d[9]), "+f"(d[10]), "+f"(d[11]), "+f"(d[12]), "+f"(d[13]), "+f"(d[14]), "+f"(d[15]), "+f"(d[16]),
        "+f"(d[17]), "+f"(d[18]), "+f"(d[19]), "+f"(d[20]), "+f"(d[21]), "+f"(d[22]), "+f"(d[23]), "+f"(d[24]),
        "+f"(d[25]), "+f"(d[26]), "+f"(d[27]), "+f"(d[28]), "+f"(d[29]), "+f"(d[30]), "+f"(d[31])
      : "l"(da), "l"(db), "r"(sd), "n"(TA), "n"(TB));
}
template <int SA, int TB>
__device__ __forceinline__ void wgmma_rs_n64(float (&d)[32], uint32_t a0, uint32_t a1, uint32_t a2, uint32_t a3, uint64_t db, int sd) {
  asm volatile("{\n.reg .pred p;\nsetp.ne.b32 p, %37, 0;\n"
      "wgmma.mma_async.sync.aligned.m64n64k16.f32.bf16.bf16 {"
      "%0, %1, %2, %3, %4, %5, %6, %7, %8, %9, %10, %11, %12, %13, %14, %15, %16, %17, %18, %19, %20, %21, %22, %23, "
      "%24, %25, %26, %27, %28, %29, %30, %31"
      "}, {%32, %33, %34, %35}, %36, p, %38, 1, %39;\n}\n"
      : "+f"(d[0]), "+f"(d[1]), "+f"(d[2]), "+f"(d[3]), "+f"(d[4]), "+f"(d[5]), "+f"(d[6]), "+f"(d[7]), "+f"(d[8]),
        "+f"(d[9]), "+f"(d[10]), "+f"(d[11]), "+f"(d[12]), "+f"(d[13]), "+f"(d[14]), "+f"(d[15]), "+f"(d[16]),
        "+f"(d[17]), "+f"(d[18]), "+f"(d[19]), "+f"(d[20]), "+f"(d[21]), "+f"(d[22]), "+f"(d[23]), "+f"(d[24]),
        "+f"(d[25]), "+f"(d[26]), "+f"(d[27]), "+f"(d[28]), "+f"(d[29]), "+f"(d[30]), "+f"(d[31])
      : "r"(a0), "r"(a1), "r"(a2), "r"(a3), "l"(db), "r"(sd), "n"(SA), "n"(TB));
}

__device__ __forceinline__ uint32_t BAR_FULL(uint32_t sb, int i) { return sb + SM_BAR + 8 * i; }
__device__ __forceinline__ uint32_t BAR_EMPTY(uint32_t sb, int i) { return sb + SM_BAR + 64 + 8 * i; }
__device__ __forceinline__ uint32_t BAR_X(uint32_t sb, int i) { return sb + SM_BAR + 128 + 8 * i; }
__device__ __forceinline__ uint32_t BAR_Y(uint32_t sb, int i) { return sb + SM_BAR + 192 + 8 * i; }
__device__ __forceinline__ uint32_t BAR_XFREE(uint32_t sb) { return sb + SM_BAR + 256; }

__device__ __forceinline__ uint32_t BAR_E2(uint32_t sb, int i) { return sb + SM_BAR + 264 + 8 * i; }
#define CMASK 0x194u
#define XORDER 0, 1, 11, 2, 3, 12, 13, 4, 5, 14, 6, 15, 16
#define XSPREAD 2
#define PFAT 3
#define SKEW 3
#define GL1 0
#define GS0 2
#define GL2 4
#define GS1 5
constexpr int Q_G1B = 18, Q_G2 = 32, Q_XR = 39, Q_P3 = 46, Q_END = 50;

__device__ __forceinline__ uint32_t y_addr(int kb) { return kb < 3 ? SM_RING + (kb + (Q_G2 + 4) % NSTAGE) * STAGE_BYTES : SM_X + (kb - 3) * 16384; }
static_assert((Q_G2 + 4) % NSTAGE + 2 < NSTAGE, "");

struct Ring {
  uint32_t slot, phase;
  __device__ __forceinline__ void next() { if (++slot == NSTAGE) { slot = 0; phase ^= 1; } }
};

__device__ __forceinline__ void release_slot(uint32_t sb, uint32_t slot, int tid, int times) {
  if (tid < 2 * times) mbar_arrive_cluster(BAR_EMPTY(sb, slot), tid & 1);
}

__device__ __forceinline__ void ffn_consumer(uint32_t sb, const uint8_t* smem, const Params& p, int bid, int wg, int tid, int mt, int jj) {
  const int lane = tid & 31, warp = tid >> 5, q = lane & 3, r0 = 16 * warp + (lane >> 2);
  uint32_t* const my_epoch = &p.s->epoch[blockIdx.x * 12 + (threadIdx.x >> 5)];
  const uint32_t epoch = ld_relaxed(my_epoch) + 1;
  Ring rg{0, 0};
  uint32_t u[64];
  float acc[128];
  uint32_t prev = 0, cmask = CMASK;
  int st = 0;
  auto g1_stage = [&](uint32_t slot, int s) {
    const uint64_t da = mk_desc(sb + SM_X + (s >> 1) * 16384 + wg * 8192 + (s & 1) * 64, 16, 1024, 1);
    const uint64_t db = mk_desc(sb + SM_RING + slot * STAGE_BYTES, 4096, 1024, 1);
    wg_fence();
    wgmma_ss_n256<0, 1>(acc, da, db, s != 0);
    wgmma_ss_n256<0, 1>(acc, da + 2, db + 128, 1);
    wg_commit();
  };
  if (wg == 1) {
    float ap[64];
    constexpr int QX = 32 - __builtin_clz(CMASK);
    constexpr int NPRE = QX + XSPREAD;
    uint4* const x1dst = p.s->x1t + ((64 * jj + r0 + 8) >> 2) * 1024 + (r0 & 3) * 128 + 8 * mt + (q ^ (mt & 3));
    const int x1lo = 64 * jj + r0 == 1 ? 110 * 1024 - 128 : -2048;
#pragma unroll
    for (int qi = 0; qi < NPRE; qi++) {
      const int slot = qi % NSTAGE, nc = __builtin_popcount(CMASK & ((1u << qi) - 1));
      if (qi == 0) TL(60);
      mbar_wait(BAR_FULL(sb, slot), (qi / NSTAGE) & 1);
      if (qi == 0) TL(61);
      if ((CMASK >> qi) & 1) {
#pragma unroll
        for (int kb = 2 * nc; kb < 2 * nc + 2 && kb < 7; kb++) {
          const uint64_t da = mk_desc(sb + SM_RING + slot * STAGE_BYTES + (kb & 1) * 8192, 8192, 1024, 1);
          const uint64_t db = mk_desc(sb + SM_X + kb * 16384, 16, 1024, 1);
          mbar_wait(BAR_X(sb, kb), 0);
          TL(16 + kb);
          wg_fence();
#pragma unroll
          for (int kk = 0; kk < 4; kk++) wgmma_ss_n128<1, 0>(ap, da + kk * 128, db + kk * 2, (kb | kk) != 0);
          wg_commit();
        }
      } else {
        if (((qi - nc) & 1) == 0 && qi - nc >= 4 * nc) mbar_wait(BAR_X(sb, (qi - nc) >> 1), 0);
        TL(32 + qi - nc);
        g1_stage(slot, qi - nc);
      }
      if (qi > 0) {
        wg_wait<1>();
        release_slot(sb, (qi - 1) % NSTAGE, tid, ((CMASK >> (qi - 1)) & 1) ? 2 : 1);
      }
      if (qi >= QX) {
        if (qi == QX) { fence_regs(ap); TL(2); }
#pragma unroll
        for (int t = (qi - QX) * (4 / XSPREAD); t < (qi - QX + 1) * (4 / XSPREAD); t++)
#pragma unroll
        for (int h = 0; h < 2; h++)
          x1dst[(h ? 0 : x1lo) + 512 * (t & 1) + 4 * (t >> 1)] = make_uint4(pack2(ap[16 * t + 2 * h], ap[16 * t + 2 * h + 1]), pack2(ap[16 * t + 4 + 2 * h], ap[16 * t + 5 + 2 * h]),
                                             pack2(ap[16 * t + 8 + 2 * h], ap[16 * t + 9 + 2 * h]), pack2(ap[16 * t + 12 + 2 * h], ap[16 * t + 13 + 2 * h]));
      }
    }
    bar_arrive(7, 160);
    st = NPRE - 4; cmask = 0; prev = (NPRE - 1) % NSTAGE;
    rg.slot = NPRE % NSTAGE; rg.phase = (NPRE / NSTAGE) & 1;
  }
#pragma unroll 1
  for (int pass = 0; pass < 2; pass++) {
#pragma unroll 1
    for (; st < 14; st++) {
      while (cmask & 1) { cmask >>= 1; rg.next(); }
      cmask >>= 1;
      if (pass == 0 && (st & 1) == 0) mbar_wait(BAR_X(sb, st >> 1), 0);
      if (st == 14 - SKEW && wg == 1) bar_sync(9 + pass, 256);
      mbar_wait(BAR_FULL(sb, rg.slot), rg.phase);
      TL(32 + 14 * pass + st);
      g1_stage(rg.slot, st);
      wg_wait<1>();
      if (st > 0) release_slot(sb, prev, tid, 1);
      prev = rg.slot;
      rg.next();
    }
    st = 0;
    if (wg == 0) bar_arrive(9 + pass, 256);
    wg_wait<0>();
    fence_regs(acc);
    release_slot(sb, prev, tid, 1);
    if (pass == 1 && tid < 2) mbar_arrive_cluster(BAR_XFREE(sb), tid);
    TL(3 + 2 * pass);
#pragma unroll
    for (int i = 0; i < 32; i++) {
      const float g0 = 0.5f * acc[2 * i], g1 = 0.5f * acc[2 * i + 1];
      const float s0 = fmaf(g0, tanh_fast(g0), g0), s1 = fmaf(g1, tanh_fast(g1), g1);
      u[32 + i] = pack2(s0 * acc[64 + 2 * i], s1 * acc[64 + 2 * i + 1]);
    }
    if (pass == 0) {
#pragma unroll
      for (int i = 0; i < 32; i++) u[i] = u[32 + i];
    }
    TL(4 + 2 * pass);
  }
  fence_regs(u);
  float accA[32], accB[32];
  auto stage = [&](float (&acc)[32], int qi) {
    const int st = qi & 1;
    if (qi < Q_XR) mbar_wait(BAR_FULL(sb, qi % NSTAGE), (qi / NSTAGE) & 1);
    else mbar_wait(BAR_X(sb, qi - Q_XR), 1);
    const uint64_t db = mk_desc(sb + (qi < Q_XR ? SM_RING + (qi % NSTAGE) * STAGE_BYTES : SM_X + (qi - Q_XR) * 16384), 8192, 1024, 1);
    wg_fence();
#pragma unroll
    for (int kk = 0; kk < 8; kk++) {
      const uint32_t* a = u + 32 * st + 4 * kk;
      wgmma_rs_n64<1, 1>(acc, a[0], a[1], a[2], a[3], db + kk * 128, (st | kk) != 0);
    }
    wg_commit();
  };
  auto retire = [&](int qi) {
    wg_wait<1>();
    if (qi >= Q_G2 && qi < Q_G2 + 4) release_slot(sb, qi % NSTAGE, tid, 1);
    else if (qi >= Q_G2 + 4 && qi < Q_G2 + 11 && tid == 0) mbar_arrive(BAR_E2(sb, qi - Q_G2 - 4));
  };
  const uint32_t par = epoch & 1;
  auto put = [&](float (&acc)[32], int c) {
    fence_regs(acc);
    int o = jj + 1 + c;
    if (o >= 7) o -= 7;
    uint4* dst = p.s->part + ((((mt * 7 + o) * 6 + c) * 2 + wg) * 4) * 128 + tid;
#pragma unroll
    for (int v = 0; v < 4; v++) {
      const float* a = acc + 8 * v;
      st_relaxed(dst + v * 128, make_uint4((pack2(a[0], a[1]) & ~1u) | par, pack2(a[2], a[3]), pack2(a[4], a[5]), pack2(a[6], a[7])));
    }
  };
  const uint4* const src = p.s->part + (((mt * 7 + jj) * 6 * 2 + wg) * 4) * 128 + tid;
  auto gload = [&](uint4 (&pv)[8], int c) {
#pragma unroll
    for (int i = 0; i < 8; i++) pv[i] = ld_relaxed(src + ((2 * c + (i >> 2)) * 8 + (i & 3)) * 128);
  };
  auto gsum = [&](uint4 (&pv)[8], int c) {
#pragma unroll 1
    for (uint32_t n = 0; n < SPIN_LIMIT; n++) {
      uint32_t bad = 0;
#pragma unroll
      for (int i = 0; i < 8; i++) bad |= pv[i].x ^ par;
      if (!__any_sync(0xffffffffu, bad & 1)) break;
      gload(pv, c);
    }
    TL(24 + c);
#pragma unroll
    for (int i = 0; i < 8; i++) {
      const float t[8] = {bf_lo(pv[i].x), bf_hi(pv[i].x), bf_lo(pv[i].y), bf_hi(pv[i].y), bf_lo(pv[i].z), bf_hi(pv[i].z), bf_lo(pv[i].w), bf_hi(pv[i].w)};
#pragma unroll
      for (int k = 0; k < 8; k++) accA[8 * (i & 3) + k] += t[k];
    }
  };
  uint4 pv0[8], pv1[8], pv2[8];
  const int row = 128 * mt + 64 * wg + r0;
  uint32_t gt0, gt1;
#pragma unroll
  for (int c2 = 0; c2 < 4; c2++) {
    const int qi = Q_G2 + 4 * c2;
    stage(accA, qi);
    retire(qi - 1);
    stage(accA, qi + 1);
    if (c2 == 3) TL(27);
    if (c2 > 0) put(accB, 2 * c2 - 1);
    TL(7 + c2);
    if (c2 == 3) break;
    retire(qi);
    stage(accB, qi + 2);
    retire(qi + 1);
    stage(accB, qi + 3);
    put(accA, 2 * c2);
    if (c2 == 2) { gload(pv0, 0); gt0 = ld_relaxed(&p.s->gate[row]); gt1 = ld_relaxed(&p.s->gate[row + 8]); }
    retire(qi + 2);
  }
#pragma unroll
  for (int kb = 0; kb < 7; kb++) {
    const int qt = Q_XR + (kb >> 1);
    if ((kb & 1) == 0) mbar_wait(BAR_FULL(sb, qt % NSTAGE), (qt / NSTAGE) & 1);
    mbar_wait(BAR_Y(sb, kb), 0);
    const uint64_t da = mk_desc(sb + y_addr(kb) + wg * 8192, 8192, 1024, 1);
    const uint64_t db = mk_desc(sb + SM_RING + (qt % NSTAGE) * STAGE_BYTES + (kb & 1) * 8192, 16, 1024, 1);
    wg_fence();
#pragma unroll
    for (int kk = 0; kk < 4; kk++) wgmma_ss_n64<1, 0>(accB, da + kk * 128, db + kk * 2, (kb | kk) != 0);
    wg_commit();
    if (kb == GL1) gload(pv1, 1);
    if (kb == 1) { wg_wait<2>(); fence_regs(accA); TL(15); }
    if (kb == GS0) gsum(pv0, 0);
    if (kb == GL2) gload(pv2, 2);
    if (kb == GS1) gsum(pv1, 1);
  }
  TL(11);
  for (uint32_t n = 0; (((gt0 ^ epoch) | (gt1 ^ epoch)) & 0xffffu) && n < SPIN_LIMIT; n++) {
    gt0 = ld_relaxed(&p.s->gate[row]); gt1 = ld_relaxed(&p.s->gate[row + 8]);
  }
  gsum(pv2, 2);
  const float ga0 = bf_hi(gt0), ga1 = bf_hi(gt1);
  TL(12);
  wg_wait<0>();
  fence_regs(accB);
  TL(13);
  const float gb0 = bf_round(1.f - ga0), gb1 = bf_round(1.f - ga1);
  const float gs0 = ga0 * (2.f / (float)(S_ * D_)), gs1 = ga1 * (2.f / (float)(S_ * D_));
  uint4* const o = reinterpret_cast<uint4*>(p.out + (size_t)row * D_ + 64 * jj + 8 * q);
#pragma unroll
  for (int h = 0; h < 2; h++) {
    const float gs = h ? gs1 : gs0, gb = h ? gb1 : gb0;
#pragma unroll
    for (int k = 0; k < 2; k++) {
      uint32_t w[4];
#pragma unroll
      for (int j = 0; j < 4; j++) {
        const int i = 16 * k + 4 * j + 2 * h;
        w[j] = pack2(fmaf(gs, accB[i], gb * accA[i]), fmaf(gs, accB[i + 1], gb * accA[i + 1]));
      }
      const bool o1 = q & 1, o2 = q & 2;
      uint32_t a = __shfl_xor_sync(0xffffffffu, o1 ? w[0] : w[1], 1), b = __shfl_xor_sync(0xffffffffu, o1 ? w[2] : w[3], 1);
      if (o1) { w[0] = a; w[2] = b; } else { w[1] = a; w[3] = b; }
      a = __shfl_xor_sync(0xffffffffu, o2 ? w[0] : w[2], 2); b = __shfl_xor_sync(0xffffffffu, o2 ? w[1] : w[3], 2);
      if (o2) { w[0] = a; w[1] = b; } else { w[2] = a; w[3] = b; }
      o[h * D_ + 4 * k] = make_uint4(w[0], w[1], w[2], w[3]);
    }
  }
  if (lane == 0) *my_epoch = epoch;
  TL(14);
}

__device__ __forceinline__ void ring_issue(uint32_t sb, const Params& p, int qi, uint32_t slot, bool wait, uint32_t phase, int jj, uint32_t rank) {
  const CUtensorMap* m;
  int c0, c1, c2 = 0;
  bool half = false, is3d = false;
  if (qi < Q_G2) {
    const int nc = __popc(CMASK & ((1u << qi) - 1));
    if ((CMASK >> qi) & 1) {
      m = &p.ct; c0 = 64 * jj; c1 = 128 * nc + 64 * rank; half = nc == 3;
    } else {
      const int pass = qi >= Q_G1B;
      m = rank ? &p.wu : &p.wg; c0 = 0; c1 = 32 * (qi - nc - 14 * pass); c2 = 4 * jj + 2 * pass; is3d = true;
    }
  } else if (qi < Q_P3) {
    int o = jj + 1 + ((qi - Q_G2) >> 1);
    if (o >= 7) o -= 7;
    m = &p.wd; c0 = 64 * o; c1 = 256 * jj + 128 * (qi & 1) + 64 * rank;
  } else {
    m = &p.ct; c0 = 128 * (qi - Q_P3) + 64 * rank; c1 = 64 * jj; half = qi == Q_END - 1;
  }
  uint32_t bar = BAR_FULL(sb, slot), dst = sb + SM_RING + slot * STAGE_BYTES + rank * 8192;
  if (qi >= Q_XR && qi < Q_P3) {
    bar = BAR_X(sb, qi - Q_XR); dst = sb + SM_X + (qi - Q_XR) * 16384 + rank * 8192;
    if (qi < Q_XR + 2) mbar_wait_cluster(BAR_XFREE(sb), 0);
  } else {
    if (wait) mbar_wait_cluster(BAR_EMPTY(sb, slot), phase ^ (qi >= Q_P3));
    mbar_expect_tx(bar, half ? 8192 : 16384);
  }
  if (is3d) tma3d_mc(dst, m, c0, c1, c2, bar);
  else if (!(half && rank)) tma2d_mc(dst, m, c0, c1, bar);
}

__device__ __forceinline__ void ffn_producer(uint32_t sb, const uint8_t* smem, int bid, const Params& p, int warp, int lane, int mt, int jj, uint32_t rank) {
  if (warp < 2) {
    if (lane == 0) {
      uint32_t slot = warp, phase = 0;
#pragma unroll 1
      for (int qi = NSTAGE + warp; qi < Q_END; qi += 2) {
        ring_issue(sb, p, qi, slot, true, phase, jj, rank);
        TL(10 + qi);
        slot += 2;
        if (slot >= NSTAGE) { slot -= NSTAGE; phase ^= 1; }
      }
    }
  } else {
    const int wg = warp - 2;
    uint32_t* const my_epoch = &p.s->epoch[blockIdx.x * 12 + 8 + warp];
    const uint32_t epoch = ld_relaxed(my_epoch) + 1;
    if (wg == 0) {
      if (lane == 0) { prefetch_tmap(&p.wd); prefetch_tmap(&p.yt); }
      {
        const uint4* gw4 = reinterpret_cast<const uint4*>(p.gate_w);
        const uint4 ga = __ldg(gw4 + lane), gb = lane < 24 ? __ldg(gw4 + 32 + lane) : make_uint4(0, 0, 0, 0);
        if (lane < 7) { mbar_wait(BAR_X(sb, lane), 0); mbar_expect_tx(BAR_X(sb, lane), 16384); mbar_expect_tx(BAR_Y(sb, lane), 16384); }
        __syncwarp();
        float mine = 0.f;
#pragma unroll 1
        for (int u = 0; u < 19; u++) {
          const int r = min(19 * jj + u, 127);
          const uint8_t* xr = smem + SM_X + (lane >> 3) * 16384 + r * 128 + (((lane ^ r) & 7) << 4);
          const uint4 xa = *reinterpret_cast<const uint4*>(xr);
          const uint4 xb = lane < 24 ? *reinterpret_cast<const uint4*>(xr + 65536) : make_uint4(0, 0, 0, 0);
          float s = 0.f;
          auto dot2 = [&](uint32_t a, uint32_t b) {
            const uint32_t pr = mul2(a, b);
            s += bf_lo(pr) + bf_hi(pr);
          };
          dot2(xa.x, ga.x); dot2(xa.y, ga.y); dot2(xa.z, ga.z); dot2(xa.w, ga.w);
          dot2(xb.x, gb.x); dot2(xb.y, gb.y); dot2(xb.z, gb.z); dot2(xb.w, gb.w);
#pragma unroll
          for (int o = 16; o > 0; o >>= 1) s += __shfl_xor_sync(0xffffffffu, s, o);
          if (lane == u) mine = s;
        }
        if (lane < 19 && 19 * jj + lane < 128)
          st_relaxed(&p.s->gate[128 * mt + 19 * jj + lane], pack2(0.f, 1.f / (1.f + __expf(-bf_round(mine)))) | (epoch & 0xffffu));
      }
      TL(9);
      if (lane < 2) mbar_arrive_cluster(BAR_XFREE(sb), lane);
    } else {
      mbar_wait(BAR_X(sb, PFAT), 0);
      if (lane < 6) {
        int row = 176 + 3 * bid + (lane >> 1);
        if (row >= D_) row -= D_;
        l2_prefetch(((lane & 1) ? p.pwu : p.pwg) + row * F_, F_ * 2);
      }
      TL(2);
      bar_sync(7, 160);
      if (lane == 0) { fence_gpu(); red_add(&p.s->cnt_x1[jj * 32], 1); l2_prefetch(p.pwd + bid * 16 * D_, 32 * D_); }
      TL(5);
    }
    mbar_wait(BAR_XFREE(sb), 0);
    TL(3);
    const int kb = 2 * lane + wg;
    bool todo = kb < 7;
    uint32_t n = 0;
    while (__any_sync(0xffffffffu, todo)) {
      if (todo) {
        uint32_t v, ok;
        asm volatile("ld.acquire.gpu.global.u32 %0, [%1];" : "=r"(v) : "l"(&p.s->cnt_y[kb * 32]) : "memory");
        asm volatile("{\n.reg .pred p;\nmbarrier.test_wait.parity.shared::cta.b64 p, [%1], 0;\nselp.u32 %0, 1, 0, p;\n}"
                     : "=r"(ok) : "r"(BAR_E2(sb, kb)) : "memory");
        if ((ok && (int32_t)(v - epoch * (kb ? 16 : 17)) >= 0) || ++n > SPIN_LIMIT) {
          tma3d(sb + y_addr(kb), &p.yt, 0, 64 * kb, 2 * mt, BAR_Y(sb, kb));
          todo = false;
        }
      }
    }
    TL(4);
    if (lane == 0) *my_epoch = epoch;
  }
}

__device__ __forceinline__ void spectral_cta(uint32_t sb, uint8_t* smem, const Params& p, int sc, int wg) {
  const int t384 = threadIdx.x, lane = t384 & 31, warp12 = t384 >> 5, tid = t384 & 127;
  const int warp = tid >> 5, q = lane & 3;
  const int sl0 = 6 * sc + min(sc, 8), nsl = sc < 8 ? 7 : 6;
  if (t384 == 320) {
#pragma unroll 1
    for (int i = 0; i < nsl; i++) {
      mbar_expect_tx(BAR_X(sb, i), 2 * SLAB_BYTES);
      const int row = 128 * ((sl0 + i) >> 3) + 8 * ((sl0 + i) & 7);
      const uint32_t dst = sb + SP_Z + 2 * i * SLAB_BYTES;
      bulk_g2s(dst, p.w_r + row * DF_, SLAB_BYTES / 2, BAR_X(sb, i));
      bulk_g2s(dst + SLAB_BYTES / 2, p.w_r + (row + 64) * DF_, SLAB_BYTES / 2, BAR_X(sb, i));
      bulk_g2s(dst + SLAB_BYTES, p.w_i + row * DF_, SLAB_BYTES / 2, BAR_X(sb, i));
      bulk_g2s(dst + 3 * SLAB_BYTES / 2, p.w_i + (row + 64) * DF_, SLAB_BYTES / 2, BAR_X(sb, i));
    }
    if (sc < 19) {
      mbar_expect_tx(BAR_Y(sb, 6), 24576);
      bulk_g2s(sb + SP_TW, p.spec, 24576, BAR_Y(sb, 6));
    }
  }
  uint32_t* const my_epoch = &p.s->epoch[blockIdx.x * 12 + warp12];
  const uint32_t epoch = ld_relaxed(my_epoch) + 1;
  uint32_t fe[16], tw[16];
#pragma unroll
  for (int i = 0; i < 4; i++) {
    const uint4 a = __ldg(reinterpret_cast<const uint4*>(p.spec->fe) + i * 128 + tid);
    const uint4 b = __ldg(reinterpret_cast<const uint4*>(p.spec->tw) + i * 128 + tid);
    fe[4 * i] = a.x; fe[4 * i + 1] = a.y; fe[4 * i + 2] = a.z; fe[4 * i + 3] = a.w;
    tw[4 * i] = b.x; tw[4 * i + 1] = b.y; tw[4 * i + 2] = b.z; tw[4 * i + 3] = b.w;
  }
  __syncwarp();
  asm volatile("barrier.cluster.wait.acquire.aligned;" ::: "memory");
#pragma unroll 2
  for (int un = wg; un < 8 * nsl; un += 3) {
    const int i = un >> 3, sl = sl0 + i, pr = 16 * (un & 7) + 4 * (lane >> 3) + warp, r = lane & 7;
    mbar_wait(BAR_X(sb, i), 0);
    if (pr < 113) {
      const uint16_t* w = reinterpret_cast<const uint16_t*>(smem + SP_Z + 2 * i * SLAB_BYTES) + r * DF_ + 2 * pr;
      const uint32_t m = pr < 112 ? 0xffffffffu : 0u;
      p.s->wt[pr * 1024 + sl * 8 + (r ^ ((sl >> 2) & 6))] =
          make_uint4(w[0] | ((uint32_t)w[8 * DF_] << 16), w[16 * DF_] | ((uint32_t)w[24 * DF_] << 16),
                     (w[1] | ((uint32_t)w[8 * DF_ + 1] << 16)) & m, (w[16 * DF_ + 1] | ((uint32_t)w[24 * DF_ + 1] << 16)) & m);
    }
  }
  __syncthreads();
  if (t384 == 352) { fence_gpu(); red_add(&p.s->cnt_w[0], 1); }
  TL(1);
  if (sc == 19) return;
  const int nrnd = (sc == 18 && wg == 2) ? 1 : 2;
  if (tid == 32) {
    wait_counter(&p.s->cnt_w[0], epoch * NSPEC);
    fence_async();
    for (int rnd = 0; rnd < nrnd; rnd++) {
      const int item = wg + 3 * rnd;
      mbar_expect_tx(BAR_Y(sb, item), 16384);
      bulk_g2s(sb + SP_W + item * 16384, p.s->wt + (6 * sc + item) * 1024, 16384, BAR_Y(sb, item));
    }
  } else if (tid == 0) {
#pragma unroll 1
    for (int rnd = 0; rnd < nrnd; rnd++) {
      const int item = wg + 3 * rnd, pr = 6 * sc + item;
      wait_counter(&p.s->cnt_x1[(pr < 112 ? pr >> 4 : 0) * 32], epoch * 16);
      fence_async();
      const uint32_t bar = BAR_FULL(sb, item), z = sb + SP_Z + item * 16384;
      mbar_expect_tx(bar, 16384);
      bulk_g2s(z, p.s->x1t + pr * 1024, 16384, bar);
    }
  }
  __syncwarp();
  fence_regs(fe); fence_regs(tw);
  mbar_wait(BAR_Y(sb, 6), 0);
  TL(3);
  const uint64_t dT_n = mk_desc(sb + SP_T, 8192, 1024, 1);
#pragma unroll 1
  for (int rnd = 0; rnd < nrnd; rnd++) {
    const int item = wg + 3 * rnd, pr = 6 * sc + item;
    const uint32_t z = sb + SP_Z + item * 16384;
    uint32_t fa[16], fb[16];
    auto load_frag = [&](int off) {
#pragma unroll
      for (int i = 0; i < 4; i++) {
        const uint4 a = *reinterpret_cast<const uint4*>(smem + SP_TW + off + i * 2048 + tid * 16);
        fa[4 * i] = a.x; fa[4 * i + 1] = a.y; fa[4 * i + 2] = a.z; fa[4 * i + 3] = a.w;
      }
      fence_regs(fa);
    };
    load_frag(0);
    mbar_wait(BAR_FULL(sb, item), 0);
    TL(4 + 8 * rnd);
    if (rnd == 0 && wg > 0) bar_sync(3 + wg, 256);
    float aR[32], aI[32];
    {
      const uint64_t de = mk_desc(z, 4096, 512, 2);
      wg_fence();
#pragma unroll
      for (int kk = 0; kk < 4; kk++) {
        wgmma_rs_n64<1, 1>(aR, fe[4 * kk], fe[4 * kk + 1], fe[4 * kk + 2], fe[4 * kk + 3], de + kk * 64, kk != 0);
        wgmma_rs_n64<1, 1>(aI, fa[4 * kk], fa[4 * kk + 1], fa[4 * kk + 2], fa[4 * kk + 3], de + 512 + kk * 64, kk != 0);
      }
      wg_commit();
      if (rnd == 0 && wg < 2) bar_arrive(4 + wg, 256);
      wg_wait<0>();
      fence_regs(aR); fence_regs(aI);
    }
    TL(5 + 8 * rnd);
#pragma unroll
    for (int v = 0; v < 8; v++) {
      uint32_t* f = (v < 4 ? fa : fb) + 2 * (v & 3);
      const uint32_t* t = tw + 2 * (v & 3);
      const float *e = aR + 4 * v, *o = aI + 4 * v;
      const uint32_t er = pack2(e[0], e[1]), ei = pack2(e[2], e[3]), qr = pack2(o[0], o[1]), qi = pack2(o[2], o[3]);
      const uint32_t u0r = add2(er, qr), u0i = add2(ei, qi), u1r = sub2(er, qr), u1i = sub2(ei, qi);
      f[0] = fma2(u0r, t[0], mul2(u0i, t[8]));
      f[8] = fms2(u0i, t[0], mul2(u0r, t[8]));
      f[1] = fma2(u1r, t[1], mul2(u1i, t[9]));
      f[9] = fms2(u1i, t[1], mul2(u1r, t[9]));
    }
    fence_regs(fa); fence_regs(fb);
    wg_fence();
#pragma unroll
    for (int kk = 0; kk < 4; kk++) {
      wgmma_rs_n64<1, 1>(aR, fa[4 * kk], fa[4 * kk + 1], fa[4 * kk + 2], fa[4 * kk + 3], dT_n + kk * 128, kk != 0);
      wgmma_rs_n64<1, 1>(aI, fb[4 * kk], fb[4 * kk + 1], fb[4 * kk + 2], fb[4 * kk + 3], dT_n + kk * 128, kk != 0);
    }
    wg_commit();
    mbar_wait(BAR_Y(sb, item), 0);
    wg_wait<0>();
    fence_regs(aR); fence_regs(aI);
    TL(6 + 8 * rnd);
    {
      const uint8_t* wp = smem + SP_W + item * 16384 + q * 1024 + warp * 128 + (((lane >> 2) ^ (2 * q)) << 4);
#pragma unroll
      for (int jb = 0; jb < 4; jb++) {
#pragma unroll
        for (int h = 0; h < 2; h++) {
          const uint4 w = *reinterpret_cast<const uint4*>(wp + jb * 4096 + h * 512);
          const int i = 4 * jb + 2 * h;
          const uint32_t ar = pack2(aR[i], aR[i + 1]), ai = pack2(aR[16 + i], aR[17 + i]);
          const uint32_t br = pack2(aI[i], aI[i + 1]), bi = pack2(aI[16 + i], aI[17 + i]);
          fa[2 * jb + h] = fms2(ar, w.x, mul2(ai, w.y));
          fa[8 + 2 * jb + h] = fma2(ar, w.y, mul2(ai, w.x));
          fb[2 * jb + h] = fms2(br, w.z, mul2(bi, w.w));
          fb[8 + 2 * jb + h] = fma2(br, w.w, mul2(bi, w.z));
        }
      }
    }
    fence_regs(fa); fence_regs(fb);
    wg_fence();
#pragma unroll
    for (int kk = 0; kk < 4; kk++) {
      wgmma_rs_n64<1, 0>(aR, fa[4 * kk], fa[4 * kk + 1], fa[4 * kk + 2], fa[4 * kk + 3], dT_n + kk * 2, kk != 0);
      wgmma_rs_n64<1, 0>(aI, fb[4 * kk], fb[4 * kk + 1], fb[4 * kk + 2], fb[4 * kk + 3], dT_n + kk * 2, kk != 0);
    }
    wg_commit();
    wg_wait<0>();
    fence_regs(aR); fence_regs(aI);
    TL(7 + 8 * rnd);
#pragma unroll
    for (int v = 0; v < 8; v++) {
      const float* a = (v < 4 ? aR : aI) + 4 * (v & 3);
      const uint32_t* t = tw + 2 * (v & 3);
      const uint32_t u0r = pack2(a[0], a[1]), u1r = pack2(a[2], a[3]), u0i = pack2(a[16], a[17]), u1i = pack2(a[18], a[19]);
      const uint32_t t0r = fms2(u0r, t[0], mul2(u0i, t[8])), t0i = fma2(u0i, t[0], mul2(u0r, t[8]));
      const uint32_t t1r = fms2(u1r, t[1], mul2(u1i, t[9])), t1i = fma2(u1i, t[1], mul2(u1r, t[9]));
      fa[v] = add2(t0i, t1i); fa[8 + v] = add2(t0r, t1r);
      fb[v] = sub2(t0i, t1i); fb[8 + v] = sub2(t0r, t1r);
    }
    bar_sync(1 + wg, 128);
#pragma unroll
    for (int u = 0; u < 4; u++) {
      const uint32_t a = z + (32 * (u >> 1) + 8 * warp + (lane & 7)) * 128 + (((4 * (u & 1) + (lane >> 3)) ^ (lane & 7)) << 4);
      stmatrix_x4(a, fa[4 * u], fa[4 * u + 1], fa[4 * u + 2], fa[4 * u + 3]);
      stmatrix_x4(a + 8192, fb[4 * u], fb[4 * u + 1], fb[4 * u + 2], fb[4 * u + 3]);
    }
    load_frag(8192);
    fence_async_smem();
    bar_sync(1 + wg, 128);
    TL(8 + 8 * rnd);
    {
      const uint64_t de = mk_desc(z, 8192, 1024, 1);
      wg_fence();
#pragma unroll
      for (int kk = 0; kk < 4; kk++) {
        wgmma_rs_n64<1, 1>(aR, fe[4 * kk], fe[4 * kk + 1], fe[4 * kk + 2], fe[4 * kk + 3], de + kk * 128, kk != 0);
        wgmma_rs_n64<1, 1>(aI, fa[4 * kk], fa[4 * kk + 1], fa[4 * kk + 2], fa[4 * kk + 3], de + 512 + kk * 128, kk != 0);
      }
      wg_commit();
      wg_wait<0>();
      fence_regs(aR); fence_regs(aI);
    }
    TL(9 + 8 * rnd);
    const bool edge = pr == 0 || pr == 112;
    if (edge) {
#pragma unroll
      for (int i = 0; i < 16; i++) { aR[i] *= 0.5f; aI[i] *= 0.5f; }
    }
#pragma unroll
    for (int i = 0; i < 8; i++) {
      const float* a = ((i & 1) ? aI : aR) + 16 * (i >> 2) + 2 - (i & 2);
      *reinterpret_cast<uint4*>(smem + SP_W + item * 16384 + (i >> 1) * 4096 + (i & 1) * 64 + (tid >> 2) * 128 + q * 16) =
          make_uint4(pack2(a[0], a[1]), pack2(a[4], a[5]), pack2(a[8], a[9]), pack2(a[12], a[13]));
    }
    fence_async_smem();
    bar_sync(1 + wg, 128);
    if (tid == 0) {
      const uint32_t src = sb + SP_W + item * 16384;
      __nv_bfloat16* dst = p.s->yt + (size_t)(pr < 112 ? 4 * pr : 1) * S_;
      bulk_s2g(dst, src, edge ? 4096 : 16384);
      if (pr == 0) bulk_s2g(dst + 2 * S_, src + 8192, 8192);
      asm volatile("cp.async.bulk.commit_group;" ::: "memory");
      if (rnd == nrnd - 1) {
        asm volatile("cp.async.bulk.wait_group 0;" ::: "memory");
        TL(11);
        fence_async();
        fence_gpu();
        red_add(&p.s->cnt_y[(pr < 112 ? pr >> 4 : 0) * 32], 1);
        if (rnd) red_add(&p.s->cnt_y[((pr - 3) >> 4) * 32], 1);
      }
    }
    __syncwarp();
    TL(10 + 8 * rnd);
  }
  if (lane == 0) *my_epoch = epoch;
}

__global__ void __cluster_dims__(2, 1, 1) __launch_bounds__(384, 1)
fused_kernel(const __grid_constant__ Params p) {
  extern __shared__ __align__(1024) uint8_t smem[];
  const uint32_t sb = smem_u32(smem);
  TL(0);
  const uint32_t rank = blockIdx.x & 1;
  const int hc = blockIdx.x >> 1;
  int grp, jj;
  if (hc < 4) { grp = 8; jj = hc; }
  else if (hc < 36) { grp = (hc - 4) & 7; jj = (hc - 4) >> 3; }
  else if (hc < 57) { jj = (hc - 36) / 7; grp = 1 + (hc - 36) - 7 * jj; jj += 4; }
  else if (hc < 60) { grp = 0; jj = hc - 53; }
  else { grp = 8; jj = hc - 56; }
  const int mt = 2 * grp + rank, bid = 2 * (7 * grp + jj) + rank;
  if (threadIdx.x == 256) {
#pragma unroll
    for (int i = 0; i < NSTAGE; i++) { mbar_init(BAR_FULL(sb, i), 1); mbar_init(BAR_EMPTY(sb, i), 4); }
    asm volatile("fence.mbarrier_init.release.cluster;" ::: "memory");
  } else if (threadIdx.x == 320) {
#pragma unroll
    for (int i = 0; i < NSTAGE; i++) { mbar_init(BAR_X(sb, i), 1); mbar_init(BAR_Y(sb, i), 1); }
    mbar_init(BAR_XFREE(sb), 6);
#pragma unroll
    for (int i = 0; i < 7; i++) mbar_init(BAR_E2(sb, i), 2);
    asm volatile("fence.mbarrier_init.release.cluster;" ::: "memory");
  } else if (threadIdx.x == 288) {
    prefetch_tmap(rank ? &p.wu : &p.wg); prefetch_tmap(&p.ct);
  }
  __syncwarp();
  asm volatile("barrier.cluster.arrive.relaxed.aligned;" ::: "memory");
  const int wg = __shfl_sync(0xffffffffu, threadIdx.x >> 7, 0);
  if (bid >= NFFN) {
    spectral_cta(sb, smem, p, bid - NFFN, wg);
  } else if (wg < 2) {
    asm volatile("setmaxnreg.inc.sync.aligned.u32 232;");
    asm volatile("barrier.cluster.wait.acquire.aligned;" ::: "memory");
    TL(1);
    ffn_consumer(sb, smem, p, bid, wg, threadIdx.x & 127, mt, jj);
  } else {
    asm volatile("setmaxnreg.dec.sync.aligned.u32 40;");
    if (threadIdx.x == 320) {
      mbar_expect_tx(BAR_X(sb, 0), 16384);
      tma2d(sb + SM_X, &p.x, 0, 128 * mt, BAR_X(sb, 0));
    }
    __syncwarp();
    asm volatile("barrier.cluster.wait.acquire.aligned;" ::: "memory");
    TL(1);
    if (threadIdx.x == 320) {
      constexpr int order[13] = {XORDER};
#pragma unroll
      for (int i = 0; i < 13; i++) {
        if (order[i] < 8) {
          ring_issue(sb, p, order[i], order[i], false, 0, jj, rank);
        } else {
          const int kb = order[i] - 10;
          mbar_expect_tx(BAR_X(sb, kb), 16384);
          tma2d(sb + SM_X + kb * 16384, &p.x, 64 * kb, 128 * mt, BAR_X(sb, kb));
        }
      }
      TL(2);
    } else if (threadIdx.x == 352) {
    }
    __syncwarp();
    ffn_producer(sb, smem, bid, p, (threadIdx.x >> 5) & 3, threadIdx.x & 31, mt, jj, rank);
  }
}

typedef CUresult (*EncodeFn)(CUtensorMap*, CUtensorMapDataType, cuuint32_t, void*, const cuuint64_t*, const cuuint64_t*,
                             const cuuint32_t*, const cuuint32_t*, CUtensorMapInterleave, CUtensorMapSwizzle,
                             CUtensorMapL2promotion, CUtensorMapFloatOOBfill);

void make_map(EncodeFn fn, CUtensorMap* m, const void* base, int rank, const cuuint64_t* dims, const cuuint64_t* strides,
              const cuuint32_t* box, CUtensorMapSwizzle sw) {
  const cuuint32_t es[4] = {1, 1, 1, 1};
  fn(m, CU_TENSOR_MAP_DATA_TYPE_BFLOAT16, rank, const_cast<void*>(base), dims, strides, box, es,
     CU_TENSOR_MAP_INTERLEAVE_NONE, sw, CU_TENSOR_MAP_L2_PROMOTION_L2_256B, CU_TENSOR_MAP_FLOAT_OOB_FILL_NONE);
}

}

extern "C" void kernel_launch(void* const* d_in, const int* in_sizes, int n_in, void* d_out, int out_size) {
  const __nv_bfloat16* x = (const __nv_bfloat16*)d_in[0];
  const __nv_bfloat16* w_r = (const __nv_bfloat16*)d_in[1];
  const __nv_bfloat16* w_i = (const __nv_bfloat16*)d_in[2];
  const __nv_bfloat16* wg = (const __nv_bfloat16*)d_in[4];
  const __nv_bfloat16* wu = (const __nv_bfloat16*)d_in[5];
  const __nv_bfloat16* wd = (const __nv_bfloat16*)d_in[6];
  const __nv_bfloat16* gate_w = (const __nv_bfloat16*)d_in[7];

  void* fnp = nullptr;
  cudaDriverEntryPointQueryResult qr;
  cudaGetDriverEntryPoint("cuTensorMapEncodeTiled", &fnp, cudaEnableDefault, &qr);
  EncodeFn fn = (EncodeFn)fnp;
  void *ctab, *spec, *scr;
  cudaGetSymbolAddress(&ctab, g_ctab);
  cudaGetSymbolAddress(&spec, g_spec);
  cudaGetSymbolAddress(&scr, g_scratch);
  const void* yt = (const char*)scr + offsetof(Scratch, yt);
  Params p;
  p.s = (Scratch*)scr; p.out = (__nv_bfloat16*)d_out;
  p.px = x; p.w_r = w_r; p.w_i = w_i; p.gate_w = gate_w; p.pwg = wg; p.pwu = wu; p.pwd = wd;
  p.ctab = (const tab::Table*)ctab; p.spec = (const tab::Spec*)spec;
  {
    const cuuint64_t d[2] = {D_, S_}, s[1] = {D_ * 2};
    const cuuint32_t b[2] = {64, 128};
    make_map(fn, &p.x, x, 2, d, s, b, CU_TENSOR_MAP_SWIZZLE_128B);
  }
  {
    const cuuint64_t d[3] = {64, D_, F_ / 64}, s[2] = {F_ * 2, 128};
    const cuuint32_t b[3] = {64, 32, 2};
    make_map(fn, &p.wg, wg, 3, d, s, b, CU_TENSOR_MAP_SWIZZLE_128B);
    make_map(fn, &p.wu, wu, 3, d, s, b, CU_TENSOR_MAP_SWIZZLE_128B);
  }
  {
    const cuuint64_t d[2] = {D_, F_}, s[1] = {D_ * 2};
    const cuuint32_t b[2] = {64, 64};
    make_map(fn, &p.wd, wd, 2, d, s, b, CU_TENSOR_MAP_SWIZZLE_128B);
  }
  {
    const cuuint64_t d[2] = {D_, D_}, s[1] = {D_ * 2};
    const cuuint32_t b[2] = {64, 64};
    make_map(fn, &p.ct, ctab, 2, d, s, b, CU_TENSOR_MAP_SWIZZLE_128B);
  }
  {
    const cuuint64_t d[3] = {64, D_, S_ / 64}, s[2] = {S_ * 2, 128};
    const cuuint32_t b[3] = {64, 64, 2};
    make_map(fn, &p.yt, yt, 3, d, s, b, CU_TENSOR_MAP_SWIZZLE_128B);
  }
  cudaFuncSetAttribute(fused_kernel, cudaFuncAttributeMaxDynamicSharedMemorySize, SM_TOTAL);
  fused_kernel<<<NCTA, 384, SM_TOTAL, cudaStreamPerThread>>>(p, x, w_r, w_i, gate_w, wd, (__nv_bfloat16*)d_out);
}
```

```cpp
#include <cuda_runtime.h>
#include <cuda_bf16.h>
#include <cuda.h>
#include <stdint.h>
#include <stddef.h>

namespace {

constexpr int S_ = 2048, D_ = 448, F_ = 1792, DF_ = 225;
constexpr int NFFN = 112, NSPEC = 20, NCTA = NFFN + NSPEC;
constexpr int NSTAGE = 7, STAGE_BYTES = 16384;
constexpr int SM_X = 0, SM_RING = 114688, SM_BAR = 229376, SM_ODD = SM_BAR + 512, SM_TOTAL = SM_ODD + 256;
constexpr int SP_Z = 0, SP_W = 98304, SP_TW = 198656, SP_T = 215040, SLAB_BYTES = 16 * DF_ * 2;
constexpr uint32_t SPIN_LIMIT = 1u << 20;

namespace tab {
constexpr double PI = 3.14159265358979323846264338327950288;
constexpr double csin(double x) {
  double t = x, s = x;
  for (int i = 1; i < 20; i++) { t = -t * x * x / ((2 * i) * (2 * i + 1)); s += t; }
  return s;
}
constexpr double ccos(double x) {
  double t = 1, s = 1;
  for (int i = 1; i < 20; i++) { t = -t * x * x / ((2 * i - 1) * (2 * i)); s += t; }
  return s;
}
constexpr uint32_t to_bf16(double v) {
  uint32_t sign = v < 0 ? 0x8000u : 0u;
  double a = v < 0 ? -v : v;
  if (a < 1e-12) return 0;
  int e = 0;
  while (a >= 2.0) { a /= 2; e++; }
  while (a < 1.0) { a *= 2; e--; }
  double m = a * 128.0;
  int mi = (int)m;
  double fr = m - mi;
  if (fr > 0.5 || (fr == 0.5 && (mi & 1))) mi++;
  if (mi == 256) { mi = 128; e++; }
  return sign | (uint32_t)((e + 127) << 7) | (uint32_t)(mi - 128);
}
struct Base { uint32_t v[448]; };
constexpr Base make_base() {
  Base b{};
  for (int m = 0; m < 448; m++) {
    int mm = m > 224 ? m - 448 : m;
    double ang = 2 * PI * mm / 448.0;
    b.v[m] = to_bf16(ccos(ang)) | (to_bf16(-csin(ang)) << 16);
  }
  return b;
}
constexpr Base base = make_base();
struct Row { uint32_t v[224]; };
constexpr Row make_row(int d) {
  Row r{};
  r.v[0] = 0x3f80u | ((d & 1) ? 0xbf800000u : 0x3f800000u);
  int m = 0;
  for (int c = 1; c < 224; c++) { m += d; if (m >= 448) m -= 448; r.v[c] = base.v[m]; }
  return r;
}
struct Table { Row r[448]; };
constexpr Table make_table() {
  Table t{};
  for (int d = 0; d < 448; d++) t.r[d] = make_row(d);
  return t;
}
struct Cs { double c[2048], s[2048]; };
constexpr Cs make_cs() {
  Cs t{};
  for (int m = 0; m <= 256; m++) {
    const double a = 2 * PI * m / 2048.0, c = ccos(a), s = csin(a);
    t.c[m] = c; t.s[m] = s;
    t.c[512 - m] = s; t.s[512 - m] = c;
  }
  for (int m = 513; m < 2048; m++) { t.c[m] = -t.s[m - 512]; t.s[m] = t.c[m - 512]; }
  return t;
}
constexpr Cs cs = make_cs();
struct Spec {
  uint32_t fo[2048], fot[2048];
  uint16_t t32[4096];
  uint32_t fe[2048];
  uint32_t tw[2048];
};
constexpr uint32_t blk(int h, int c, int a) { return to_bf16(h == c ? cs.c[a & 2047] : (h ? -cs.s[a & 2047] : cs.s[a & 2047])); }
constexpr Spec make_spec() {
  Spec t{};
  for (int row = 0; row < 64; row++)
    for (int col = 0; col < 64; col++) {
      const int c = row & 31, k2 = col & 31, n2 = 8 * ((c >> 1) & 3) + 2 * (c >> 3) + (c & 1), m = 64 * ((n2 * k2) & 31);
      const double v = (row >> 5) == (col >> 5) ? cs.c[m] : (row < 32 ? -cs.s[m] : cs.s[m]);
      t.t32[row * 64 + (((col >> 3) ^ (row & 7)) << 3) + (col & 7)] = (uint16_t)to_bf16(v);
    }
  for (int th = 0; th < 128; th++)
    for (int i = 0; i < 16; i++) {
      const int r = 8 * (th >> 5) + ((th & 31) >> 2), h = i & 1, c = i >> 3, m = 8 * ((i >> 1) & 3) + 2 * (th & 3);
      const int o = ((i >> 2) * 128 + th) * 4 + (i & 3);
      t.fe[o] = blk(h, c, 64 * m * r) | (blk(h, c, 64 * (m + 1) * r) << 16);
      t.fo[o] = blk(h, c, 32 * (2 * m + 1) * r) | (blk(h, c, 32 * (2 * m + 3) * r) << 16);
      t.fot[o] = blk(h, c, 32 * (2 * r + 1) * m) | (blk(h, c, 32 * (2 * r + 1) * (m + 1)) << 16);
      const int k1 = r + 32 * h, n2 = 8 * (th & 3) + 2 * ((i >> 1) & 3);
      t.tw[o] = blk(0, c, n2 * k1) | (blk(0, c, (n2 + 1) * k1) << 16);
    }
  return t;
}
}
}

__device__ __align__(1024) const tab::Table g_ctab = tab::make_table();
__device__ __align__(1024) const tab::Spec g_spec = tab::make_spec();

struct Scratch {
  uint32_t cnt_w[32];
  uint32_t cnt_x1[7 * 32];
  uint32_t cnt_y[7 * 32];
  uint32_t epoch[NCTA * 12 + 240 + 256];
  uint32_t gate[S_];
  uint4 x1t[113 * 1024];
  __nv_bfloat16 yt[D_ * S_];
  uint4 wt[114 * 1024];
  uint4 part[16 * 7 * 6 * 2 * 4 * 128];
};
static_assert(offsetof(Scratch, x1t) % 1024 == 0, "alignment");
__device__ __align__(1024) Scratch g_scratch;
#define TL(i)

namespace {

struct Params {
  Scratch* s;
  __nv_bfloat16* out;
  const __nv_bfloat16 *px, *w_r, *w_i, *gate_w, *pwg, *pwu, *pwd;
  const tab::Table* ctab;
  const tab::Spec* spec;
  CUtensorMap x, wg, wu, wd, ct, yt, x1;
};

__device__ __forceinline__ uint32_t smem_u32(const void* p) { return (uint32_t)__cvta_generic_to_shared(p); }
__device__ __forceinline__ void mbar_init(uint32_t bar, uint32_t cnt) {
  asm volatile("mbarrier.init.shared::cta.b64 [%0], %1;" ::"r"(bar), "r"(cnt) : "memory");
}
__device__ __forceinline__ void mbar_expect_tx(uint32_t bar, uint32_t bytes) {
  asm volatile("mbarrier.arrive.expect_tx.shared::cta.b64 _, [%0], %1;" ::"r"(bar), "r"(bytes) : "memory");
}
__device__ __forceinline__ void mbar_arrive(uint32_t bar) {
  asm volatile("mbarrier.arrive.shared::cta.b64 _, [%0];" ::"r"(bar) : "memory");
}
__device__ __forceinline__ void mbar_arrive_cluster(uint32_t bar, uint32_t cta) {
  asm volatile("{\n.reg .b32 ra;\nmapa.shared::cluster.u32 ra, %0, %1;\n"
               "mbarrier.arrive.shared::cluster.b64 _, [ra];\n}" ::"r"(bar), "r"(cta) : "memory");
}
__device__ __forceinline__ void mbar_wait(uint32_t bar, uint32_t parity) {
  uint32_t ok, n = 0;
  do {
    asm volatile("{\n.reg .pred p;\nmbarrier.try_wait.parity.shared::cta.b64 p, [%1], %2;\nselp.u32 %0, 1, 0, p;\n}"
                 : "=r"(ok) : "r"(bar), "r"(parity) : "memory");
  } while (!ok && ++n < SPIN_LIMIT);
}
__device__ __forceinline__ void mbar_wait_cluster(uint32_t bar, uint32_t parity) {
  uint32_t ok, n = 0;
  do {
    asm volatile("{\n.reg .pred p;\nmbarrier.try_wait.parity.acquire.cluster.shared::cta.b64 p, [%1], %2;\nselp.u32 %0, 1, 0, p;\n}"
                 : "=r"(ok) : "r"(bar), "r"(parity) : "memory");
  } while (!ok && ++n < SPIN_LIMIT);
}
__device__ __forceinline__ void tma2d(uint32_t dst, const CUtensorMap* m, int c0, int c1, uint32_t bar) {
  asm volatile("cp.async.bulk.tensor.2d.shared::cluster.global.mbarrier::complete_tx::bytes [%0], [%1, {%3, %4}], [%2];"
               ::"r"(dst), "l"(m), "r"(bar), "r"(c0), "r"(c1) : "memory");
}
__device__ __forceinline__ void tma3d(uint32_t dst, const CUtensorMap* m, int c0, int c1, int c2, uint32_t bar) {
  asm volatile("cp.async.bulk.tensor.3d.shared::cluster.global.mbarrier::complete_tx::bytes [%0], [%1, {%3, %4, %5}], [%2];"
               ::"r"(dst), "l"(m), "r"(bar), "r"(c0), "r"(c1), "r"(c2) : "memory");
}
__device__ __forceinline__ void tma2d_mc(uint32_t dst, const CUtensorMap* m, int c0, int c1, uint32_t bar) {
  asm volatile("cp.async.bulk.tensor.2d.shared::cluster.global.mbarrier::complete_tx::bytes.multicast::cluster [%0], [%1, {%3, %4}], [%2], %5;"
               ::"r"(dst), "l"(m), "r"(bar), "r"(c0), "r"(c1), "h"((uint16_t)3) : "memory");
}
__device__ __forceinline__ void tma3d_mc(uint32_t dst, const CUtensorMap* m, int c0, int c1, int c2, uint32_t bar) {
  asm volatile("cp.async.bulk.tensor.3d.shared::cluster.global.mbarrier::complete_tx::bytes.multicast::cluster [%0], [%1, {%3, %4, %5}], [%2], %6;"
               ::"r"(dst), "l"(m), "r"(bar), "r"(c0), "r"(c1), "r"(c2), "h"((uint16_t)3) : "memory");
}
__device__ __forceinline__ void bulk_g2s(uint32_t dst, const void* src, uint32_t bytes, uint32_t bar) {
  asm volatile("cp.async.bulk.shared::cluster.global.mbarrier::complete_tx::bytes [%0], [%1], %2, [%3];"
               ::"r"(dst), "l"(src), "r"(bytes), "r"(bar) : "memory");
}
__device__ __forceinline__ void bulk_s2g(void* dst, uint32_t src, uint32_t bytes) {
  asm volatile("cp.async.bulk.global.shared::cta.bulk_group [%0], [%1], %2;" ::"l"(dst), "r"(src), "r"(bytes) : "memory");
}
__device__ __forceinline__ void prefetch_tmap(const CUtensorMap* m) {
  asm volatile("prefetch.tensormap [%0];" ::"l"(m) : "memory");
}
__device__ __forceinline__ void l2_prefetch(const void* p, uint32_t bytes) {
  asm volatile("cp.async.bulk.prefetch.L2.global [%0], %1;" ::"l"(p), "r"(bytes) : "memory");
}
__device__ __forceinline__ void wg_fence() { asm volatile("wgmma.fence.sync.aligned;" ::: "memory"); }
__device__ __forceinline__ void wg_commit() { asm volatile("wgmma.commit_group.sync.aligned;" ::: "memory"); }
template <int N> __device__ __forceinline__ void wg_wait() { asm volatile("wgmma.wait_group.sync.aligned %0;" ::"n"(N) : "memory"); }
template <int N> __device__ __forceinline__ void fence_regs(float (&d)[N]) {
#pragma unroll
  for (int i = 0; i < N; i++) asm volatile("" : "+f"(d[i])::"memory");
}
template <int N> __device__ __forceinline__ void fence_regs(uint32_t (&d)[N]) {
#pragma unroll
  for (int i = 0; i < N; i++) asm volatile("" : "+r"(d[i])::"memory");
}
__device__ __forceinline__ void bar_sync(int id, int n) { asm volatile("bar.sync %0, %1;" ::"r"(id), "r"(n) : "memory"); }
__device__ __forceinline__ void bar_arrive(int id, int n) { asm volatile("bar.arrive %0, %1;" ::"r"(id), "r"(n) : "memory"); }
__device__ __forceinline__ void fence_gpu() { asm volatile("fence.acq_rel.gpu;" ::: "memory"); }
__device__ __forceinline__ void fence_async() { asm volatile("fence.proxy.async;" ::: "memory"); }
__device__ __forceinline__ void fence_async_smem() { asm volatile("fence.proxy.async.shared::cta;" ::: "memory"); }
__device__ __forceinline__ void red_add(uint32_t* p, uint32_t v) {
  asm volatile("red.relaxed.gpu.global.add.u32 [%0], %1;" ::"l"(p), "r"(v) : "memory");
}
__device__ __forceinline__ uint32_t ld_relaxed(const uint32_t* p) {
  uint32_t v;
  asm volatile("ld.relaxed.gpu.global.u32 %0, [%1];" : "=r"(v) : "l"(p) : "memory");
  return v;
}
__device__ __forceinline__ void wait_counter(const uint32_t* p, uint32_t target) {
  uint32_t v, n = 0;
  while (true) {
    asm volatile("ld.acquire.gpu.global.u32 %0, [%1];" : "=r"(v) : "l"(p) : "memory");
    if ((int32_t)(v - target) >= 0 || ++n > SPIN_LIMIT) break;
  }
}
__device__ __forceinline__ uint4 ld_relaxed(const uint4* p) {
  uint4 v;
  asm volatile("ld.relaxed.gpu.global.v4.u32 {%0, %1, %2, %3}, [%4];" : "=r"(v.x), "=r"(v.y), "=r"(v.z), "=r"(v.w) : "l"(p) : "memory");
  return v;
}
__device__ __forceinline__ void st_relaxed(uint4* p, uint4 v) {
  asm volatile("st.relaxed.gpu.global.v4.u32 [%0], {%1, %2, %3, %4};" ::"l"(p), "r"(v.x), "r"(v.y), "r"(v.z), "r"(v.w) : "memory");
}
__device__ __forceinline__ void st_relaxed(uint32_t* p, uint32_t v) {
  asm volatile("st.relaxed.gpu.global.u32 [%0], %1;" ::"l"(p), "r"(v) : "memory");
}
__device__ __forceinline__ uint32_t pack2(float lo, float hi) {
  uint32_t r;
  asm("cvt.rn.bf16x2.f32 %0, %1, %2;" : "=r"(r) : "f"(hi), "f"(lo));
  return r;
}
__device__ __forceinline__ uint32_t mul2(uint32_t a, uint32_t b) {
  uint32_t r;
  asm("mul.rn.bf16x2 %0, %1, %2;" : "=r"(r) : "r"(a), "r"(b));
  return r;
}
__device__ __forceinline__ uint32_t fma2(uint32_t a, uint32_t b, uint32_t c) {
  uint32_t r;
  asm("fma.rn.bf16x2 %0, %1, %2, %3;" : "=r"(r) : "r"(a), "r"(b), "r"(c));
  return r;
}
__device__ __forceinline__ uint32_t add2(uint32_t a, uint32_t b) {
  uint32_t r;
  asm("add.rn.bf16x2 %0, %1, %2;" : "=r"(r) : "r"(a), "r"(b));
  return r;
}
__device__ __forceinline__ uint32_t sub2(uint32_t a, uint32_t b) {
  uint32_t r;
  asm("sub.rn.bf16x2 %0, %1, %2;" : "=r"(r) : "r"(a), "r"(b));
  return r;
}
__device__ __forceinline__ uint32_t fms2(uint32_t a, uint32_t b, uint32_t c) {
  uint32_t r;
  asm("{\n.reg .b32 n;\nneg.bf16x2 n, %3;\nfma.rn.bf16x2 %0, %1, %2, n;\n}" : "=r"(r) : "r"(a), "r"(b), "r"(c));
  return r;
}
__device__ __forceinline__ float bf_lo(uint32_t v) { return __uint_as_float(v << 16); }
__device__ __forceinline__ float bf_hi(uint32_t v) { return __uint_as_float(v & 0xffff0000u); }
__device__ __forceinline__ float bf_round(float v) { return bf_lo(pack2(v, 0.f)); }
__device__ __forceinline__ float tanh_fast(float v) {
  float r;
  asm("tanh.approx.f32 %0, %1;" : "=f"(r) : "f"(v));
  return r;
}
__device__ __forceinline__ uint64_t mk_desc(uint32_t addr, uint32_t lbo, uint32_t sbo, uint32_t mode) {
  return (uint64_t)((addr & 0x3FFFF) >> 4) | ((uint64_t)(lbo >> 4) << 16) | ((uint64_t)(sbo >> 4) << 32) | ((uint64_t)mode << 62);
}
__device__ __forceinline__ void stmatrix_x4(uint32_t addr, uint32_t r0, uint32_t r1, uint32_t r2, uint32_t r3) {
  asm volatile("stmatrix.sync.aligned.m8n8.x4.shared.b16 [%0], {%1, %2, %3, %4};" ::"r"(addr), "r"(r0), "r"(r1), "r"(r2), "r"(r3) : "memory");
}

template <int TA, int TB>
__device__ __forceinline__ void wgmma_ss_n256(float (&d)[128], uint64_t da, uint64_t db, int sd) {
  asm volatile("{\n.reg .pred p;\nsetp.ne.b32 p, %130, 0;\n"
      "wgmma.mma_async.sync.aligned.m64n256k16.f32.bf16.bf16 {"
      "%0, %1, %2, %3, %4, %5, %6, %7, %8, %9, %10, %11, %12, %13, %14, %15, %16, %17, %18, %19, %20, %21, %22, %23, "
      "%24, %25, %26, %27, %28, %29, %30, %31, %32, %33, %34, %35, %36, %37, %38, %39, %40, %41, %42, %43, %44, %45, "
      "%46, %47, %48, %49, %50, %51, %52, %53, %54, %55, %56, %57, %58, %59, %60, %61, %62, %63, %64, %65, %66, %67, "
      "%68, %69, %70, %71, %72, %73, %74, %75, %76, %77, %78, %79, %80, %81, %82, %83, %84, %85, %86, %87, %88, %89, "
      "%90, %91, %92, %93, %94, %95, %96, %97, %98, %99, %100, %101, %102, %103, %104, %105, %106, %107, %108, %109, "
      "%110, %111, %112, %113, %114, %115, %116, %117, %118, %119, %120, %121, %122, %123, %124, %125, %126, %127"
      "}, %128, %129, p, 1, 1, %131, %132;\n}\n"
      : "+f"(d[0]), "+f"(d[1]), "+f"(d[2]), "+f"(d[3]), "+f"(d[4]), "+f"(d[5]), "+f"(d[6]), "+f"(d[7]), "+f"(d[8]),
        "+f"(d[9]), "+f"(d[10]), "+f"(d[11]), "+f"(d[12]), "+f"(d[13]), "+f"(d[14]), "+f"(d[15]), "+f"(d[16]),
        "+f"(d[17]), "+f"(d[18]), "+f"(d[19]), "+f"(d[20]), "+f"(d[21]), "+f"(d[22]), "+f"(d[23]), "+f"(d[24]),
        "+f"(d[25]), "+f"(d[26]), "+f"(d[27]), "+f"(d[28]), "+f"(d[29]), "+f"(d[30]), "+f"(d[31]), "+f"(d[32]),
        "+f"(d[33]), "+f"(d[34]), "+f"(d[35]), "+f"(d[36]), "+f"(d[37]), "+f"(d[38]), "+f"(d[39]), "+f"(d[40]),
        "+f"(d[41]), "+f"(d[42]), "+f"(d[43]), "+f"(d[44]), "+f"(d[45]), "+f"(d[46]), "+f"(d[47]), "+f"(d[48]),
        "+f"(d[49]), "+f"(d[50]), "+f"(d[51]), "+f"(d[52]), "+f"(d[53]), "+f"(d[54]), "+f"(d[55]), "+f"(d[56]),
        "+f"(d[57]), "+f"(d[58]), "+f"(d[59]), "+f"(d[60]), "+f"(d[61]), "+f"(d[62]), "+f"(d[63]), "+f"(d[64]),
        "+f"(d[65]), "+f"(d[66]), "+f"(d[67]), "+f"(d[68]), "+f"(d[69]), "+f"(d[70]), "+f"(d[71]), "+f"(d[72]),
        "+f"(d[73]), "+f"(d[74]), "+f"(d[75]), "+f"(d[76]), "+f"(d[77]), "+f"(d[78]), "+f"(d[79]), "+f"(d[80]),
        "+f"(d[81]), "+f"(d[82]), "+f"(d[83]), "+f"(d[84]), "+f"(d[85]), "+f"(d[86]), "+f"(d[87]), "+f"(d[88]),
        "+f"(d[89]), "+f"(d[90]), "+f"(d[91]), "+f"(d[92]), "+f"(d[93]), "+f"(d[94]), "+f"(d[95]), "+f"(d[96]),
        "+f"(d[97]), "+f"(d[98]), "+f"(d[99]), "+f"(d[100]), "+f"(d[101]), "+f"(d[102]), "+f"(d[103]), "+f"(d[104]),
        "+f"(d[105]), "+f"(d[106]), "+f"(d[107]), "+f"(d[108]), "+f"(d[109]), "+f"(d[110]), "+f"(d[111]),
        "+f"(d[112]), "+f"(d[113]), "+f"(d[114]), "+f"(d[115]), "+f"(d[116]), "+f"(d[117]), "+f"(d[118]),
        "+f"(d[119]), "+f"(d[120]), "+f"(d[121]), "+f"(d[122]), "+f"(d[123]), "+f"(d[124]), "+f"(d[125]),
        "+f"(d[126]), "+f"(d[127])
      : "l"(da), "l"(db), "r"(sd), "n"(TA), "n"(TB));
}
template <int TA, int TB>
__device__ __forceinline__ void wgmma_ss_n128(float (&d)[64], uint64_t da, uint64_t db, int sd) {
  asm volatile("{\n.reg .pred p;\nsetp.ne.b32 p, %66, 0;\n"
      "wgmma.mma_async.sync.aligned.m64n128k16.f32.bf16.bf16 {"
      "%0, %1, %2, %3, %4, %5, %6, %7, %8, %9, %10, %11, %12, %13, %14, %15, %16, %17, %18, %19, %20, %21, %22, %23, "
      "%24, %25, %26, %27, %28, %29, %30, %31, %32, %33, %34, %35, %36, %37, %38, %39, %40, %41, %42, %43, %44, %45, "
      "%46, %47, %48, %49, %50, %51, %52, %53, %54, %55, %56, %57, %58, %59, %60, %61, %62, %63"
      "}, %64, %65, p, 1, 1, %67, %68;\n}\n"
      : "+f"(d[0]), "+f"(d[1]), "+f"(d[2]), "+f"(d[3]), "+f"(d[4]), "+f"(d[5]), "+f"(d[6]), "+f"(d[7]), "+f"(d[8]),
        "+f"(d[9]), "+f"(d[10]), "+f"(d[11]), "+f"(d[12]), "+f"(d[13]), "+f"(d[14]), "+f"(d[15]), "+f"(d[16]),
        "+f"(d[17]), "+f"(d[18]), "+f"(d[19]), "+f"(d[20]), "+f"(d[21]), "+f"(d[22]), "+f"(d[23]), "+f"(d[24]),
        "+f"(d[25]), "+f"(d[26]), "+f"(d[27]), "+f"(d[28]), "+f"(d[29]), "+f"(d[30]), "+f"(d[31]), "+f"(d[32]),
        "+f"(d[33]), "+f"(d[34]), "+f"(d[35]), "+f"(d[36]), "+f"(d[37]), "+f"(d[38]), "+f"(d[39]), "+f"(d[40]),
        "+f"(d[41]), "+f"(d[42]), "+f"(d[43]), "+f"(d[44]), "+f"(d[45]), "+f"(d[46]), "+f"(d[47]), "+f"(d[48]),
        "+f"(d[49]), "+f"(d[50]), "+f"(d[51]), "+f"(d[52]), "+f"(d[53]), "+f"(d[54]), "+f"(d[55]), "+f"(d[56]),
        "+f"(d[57]), "+f"(d[58]), "+f"(d[59]), "+f"(d[60]), "+f"(d[61]), "+f"(d[62]), "+f"(d[63])
      : "l"(da), "l"(db), "r"(sd), "n"(TA), "n"(TB));
}
template <int TA, int TB>
__device__ __forceinline__ void wgmma_ss_n64(float (&d)[32], uint64_t da, uint64_t db, int sd) {
  asm volatile("{\n.reg .pred p;\nsetp.ne.b32 p, %34, 0;\n"
      "wgmma.mma_async.sync.aligned.m64n64k16.f32.bf16.bf16 {"
      "%0, %1, %2, %3, %4, %5, %6, %7, %8, %9, %10, %11, %12, %13, %14, %15, %16, %17, %18, %19, %20, %21, %22, %23, "
      "%24, %25, %26, %27, %28, %29, %30, %31"
      "}, %32, %33, p, 1, 1, %35, %36;\n}\n"
      : "+f"(d[0]), "+f"(d[1]), "+f"(d[2]), "+f"(d[3]), "+f"(d[4]), "+f"(d[5]), "+f"(d[6]), "+f"(d[7]), "+f"(d[8]),
        "+f"(d[9]), "+f"(d[10]), "+f"(d[11]), "+f"(d[12]), "+f"(d[13]), "+f"(d[14]), "+f"(d[15]), "+f"(d[16]),
        "+f"(d[17]), "+f"(d[18]), "+f"(d[19]), "+f"(d[20]), "+f"(d[21]), "+f"(d[22]), "+f"(d[23]), "+f"(d[24]),
        "+f"(d[25]), "+f"(d[26]), "+f"(d[27]), "+f"(d[28]), "+f"(d[29]), "+f"(d[30]), "+f"(d[31])
      : "l"(da), "l"(db), "r"(sd), "n"(TA), "n"(TB));
}
template <int SA, int TB>
__device__ __forceinline__ void wgmma_rs_n64(float (&d)[32], uint32_t a0, uint32_t a1, uint32_t a2, uint32_t a3, uint64_t db, int sd) {
  asm volatile("{\n.reg .pred p;\nsetp.ne.b32 p, %37, 0;\n"
      "wgmma.mma_async.sync.aligned.m64n64k16.f32.bf16.bf16 {"
      "%0, %1, %2, %3, %4, %5, %6, %7, %8, %9, %10, %11, %12, %13, %14, %15, %16, %17, %18, %19, %20, %21, %22, %23, "
      "%24, %25, %26, %27, %28, %29, %30, %31"
      "}, {%32, %33, %34, %35}, %36, p, %38, 1, %39;\n}\n"
      : "+f"(d[0]), "+f"(d[1]), "+f"(d[2]), "+f"(d[3]), "+f"(d[4]), "+f"(d[5]), "+f"(d[6]), "+f"(d[7]), "+f"(d[8]),
        "+f"(d[9]), "+f"(d[10]), "+f"(d[11]), "+f"(d[12]), "+f"(d[13]), "+f"(d[14]), "+f"(d[15]), "+f"(d[16]),
        "+f"(d[17]), "+f"(d[18]), "+f"(d[19]), "+f"(d[20]), "+f"(d[21]), "+f"(d[22]), "+f"(d[23]), "+f"(d[24]),
        "+f"(d[25]), "+f"(d[26]), "+f"(d[27]), "+f"(d[28]), "+f"(d[29]), "+f"(d[30]), "+f"(d[31])
      : "r"(a0), "r"(a1), "r"(a2), "r"(a3), "l"(db), "r"(sd), "n"(SA), "n"(TB));
}

__device__ __forceinline__ uint32_t BAR_FULL(uint32_t sb, int i) { return sb + SM_BAR + 8 * i; }
__device__ __forceinline__ uint32_t BAR_EMPTY(uint32_t sb, int i) { return sb + SM_BAR + 64 + 8 * i; }
__device__ __forceinline__ uint32_t BAR_X(uint32_t sb, int i) { return sb + SM_BAR + 128 + 8 * i; }
__device__ __forceinline__ uint32_t BAR_Y(uint32_t sb, int i) { return sb + SM_BAR + 192 + 8 * i; }
__device__ __forceinline__ uint32_t BAR_XFREE(uint32_t sb) { return sb + SM_BAR + 256; }

__device__ __forceinline__ uint32_t BAR_E2(uint32_t sb, int i) { return sb + SM_BAR + 264 + 8 * i; }
#define CMASK 0x194u
#define XORDER 0, 1, 11, 2, 3, 12, 13, 4, 5, 14, 6, 15, 16
#define XSPREAD 2
#define PFAT 3
#define SKEW 3
#define GL1 0
#define GS0 2
#define GL2 4
#define GS1 5
constexpr int Q_G1B = 18, Q_G2 = 32, Q_XR = 39, Q_P3 = 46, Q_END = 50;

__device__ __forceinline__ uint32_t y_addr(int kb) { return kb < 3 ? SM_RING + (kb + (Q_G2 + 4) % NSTAGE) * STAGE_BYTES : SM_X + (kb - 3) * 16384; }
static_assert((Q_G2 + 4) % NSTAGE + 2 < NSTAGE, "");

struct Ring {
  uint32_t slot, phase;
  __device__ __forceinline__ void next() { if (++slot == NSTAGE) { slot = 0; phase ^= 1; } }
};

__device__ __forceinline__ void release_slot(uint32_t sb, uint32_t slot, int tid, int times) {
  if (tid < 2 * times) mbar_arrive_cluster(BAR_EMPTY(sb, slot), tid & 1);
}

__device__ __forceinline__ void ffn_consumer(uint32_t sb, uint8_t* smem, const Params& p, int bid, int wg, int tid, int mt, int jj) {
  const int lane = tid & 31, warp = tid >> 5, q = lane & 3, r0 = 16 * warp + (lane >> 2);
  uint32_t* const my_epoch = &p.s->epoch[blockIdx.x * 12 + (threadIdx.x >> 5)];
  const uint32_t epoch = ld_relaxed(my_epoch) + 1;
  Ring rg{0, 0};
  uint32_t u[64];
  float acc[128];
  uint32_t prev = 0, cmask = CMASK;
  int st = 0;
  auto g1_stage = [&](uint32_t slot, int s) {
    const uint64_t da = mk_desc(sb + SM_X + (s >> 1) * 16384 + wg * 8192 + (s & 1) * 64, 16, 1024, 1);
    const uint64_t db = mk_desc(sb + SM_RING + slot * STAGE_BYTES, 4096, 1024, 1);
    wg_fence();
    wgmma_ss_n256<0, 1>(acc, da, db, s != 0);
    wgmma_ss_n256<0, 1>(acc, da + 2, db + 128, 1);
    wg_commit();
  };
  if (wg == 1) {
    float ap[64];
    constexpr int QX = 32 - __builtin_clz(CMASK);
    constexpr int NPRE = QX + 1;
#pragma unroll
    for (int qi = 0; qi < NPRE; qi++) {
      const int slot = qi % NSTAGE, nc = __builtin_popcount(CMASK & ((1u << qi) - 1));
      if (qi == 0) TL(60);
      mbar_wait(BAR_FULL(sb, slot), (qi / NSTAGE) & 1);
      if (qi == 0) TL(61);
      if ((CMASK >> qi) & 1) {
#pragma unroll
        for (int kb = 2 * nc; kb < 2 * nc + 2 && kb < 7; kb++) {
          const uint64_t da = mk_desc(sb + SM_RING + slot * STAGE_BYTES + (kb & 1) * 8192, 8192, 1024, 1);
          const uint64_t db = mk_desc(sb + SM_X + kb * 16384, 16, 1024, 1);
          mbar_wait(BAR_X(sb, kb), 0);
          TL(16 + kb);
          wg_fence();
#pragma unroll
          for (int kk = 0; kk < 4; kk++) wgmma_ss_n128<1, 0>(ap, da + kk * 128, db + kk * 2, (kb | kk) != 0);
          wg_commit();
        }
      } else {
        if (((qi - nc) & 1) == 0 && qi - nc >= 4 * nc) mbar_wait(BAR_X(sb, (qi - nc) >> 1), 0);
        TL(32 + qi - nc);
        g1_stage(slot, qi - nc);
      }
      if (qi > 0) {
        wg_wait<1>();
        if (qi < QX) release_slot(sb, (qi - 1) % NSTAGE, tid, ((CMASK >> (qi - 1)) & 1) ? 2 : 1);
      }
    }
    fence_regs(ap);
    TL(2);
    bar_sync(6, 128);
    uint8_t* const xs = smem + SM_RING + ((QX - 1) % NSTAGE) * STAGE_BYTES + (r0 >> 2) * 1024 + (r0 & 3) * 128 + ((q ^ (mt & 3)) << 4);
    const bool odd = 64 * jj + r0 == 1;
#pragma unroll
    for (int t = 0; t < 4; t++)
#pragma unroll
      for (int h = 0; h < 2; h++) {
        const uint4 v = make_uint4(pack2(ap[16 * t + 2 * h], ap[16 * t + 2 * h + 1]), pack2(ap[16 * t + 4 + 2 * h], ap[16 * t + 5 + 2 * h]),
                                   pack2(ap[16 * t + 8 + 2 * h], ap[16 * t + 9 + 2 * h]), pack2(ap[16 * t + 12 + 2 * h], ap[16 * t + 13 + 2 * h]));
        uint4* const d = reinterpret_cast<uint4*>(xs + h * 2048 + (t & 1) * 512 + (t >> 1) * 64);
        if (h == 0 && odd) {
          *d = make_uint4(0, 0, 0, 0);
          *reinterpret_cast<uint4*>(smem + SM_ODD + (t & 1) * 128 + (t >> 1) * 64 + ((q ^ (mt & 3)) << 4)) = v;
        } else {
          *d = v;
        }
      }
    fence_async_smem();
    bar_arrive(7, 160);
    st = NPRE - 4; cmask = 0; prev = (NPRE - 1) % NSTAGE;
    rg.slot = NPRE % NSTAGE; rg.phase = (NPRE / NSTAGE) & 1;
  }
#pragma unroll 1
  for (int pass = 0; pass < 2; pass++) {
#pragma unroll 1
    for (; st < 14; st++) {
      while (cmask & 1) { cmask >>= 1; rg.next(); }
      cmask >>= 1;
      if (pass == 0 && (st & 1) == 0) mbar_wait(BAR_X(sb, st >> 1), 0);
      if (st == 14 - SKEW && wg == 1) bar_sync(9 + pass, 256);
      mbar_wait(BAR_FULL(sb, rg.slot), rg.phase);
      TL(32 + 14 * pass + st);
      g1_stage(rg.slot, st);
      wg_wait<1>();
      if (st > 0) release_slot(sb, prev, tid, 1);
      prev = rg.slot;
      rg.next();
    }
    st = 0;
    if (wg == 0) bar_arrive(9 + pass, 256);
    wg_wait<0>();
    fence_regs(acc);
    release_slot(sb, prev, tid, 1);
    if (pass == 1 && tid < 2) mbar_arrive_cluster(BAR_XFREE(sb), tid);
    TL(3 + 2 * pass);
#pragma unroll
    for (int i = 0; i < 32; i++) {
      const float g0 = 0.5f * acc[2 * i], g1 = 0.5f * acc[2 * i + 1];
      const float s0 = fmaf(g0, tanh_fast(g0), g0), s1 = fmaf(g1, tanh_fast(g1), g1);
      u[32 + i] = pack2(s0 * acc[64 + 2 * i], s1 * acc[64 + 2 * i + 1]);
    }
    if (pass == 0) {
#pragma unroll
      for (int i = 0; i < 32; i++) u[i] = u[32 + i];
    }
    TL(4 + 2 * pass);
  }
  fence_regs(u);
  float accA[32], accB[32];
  auto stage = [&](float (&acc)[32], int qi) {
    const int st = qi & 1;
    if (qi < Q_XR) mbar_wait(BAR_FULL(sb, qi % NSTAGE), (qi / NSTAGE) & 1);
    else mbar_wait(BAR_X(sb, qi - Q_XR), 1);
    const uint64_t db = mk_desc(sb + (qi < Q_XR ? SM_RING + (qi % NSTAGE) * STAGE_BYTES : SM_X + (qi - Q_XR) * 16384), 8192, 1024, 1);
    wg_fence();
#pragma unroll
    for (int kk = 0; kk < 8; kk++) {
      const uint32_t* a = u + 32 * st + 4 * kk;
      wgmma_rs_n64<1, 1>(acc, a[0], a[1], a[2], a[3], db + kk * 128, (st | kk) != 0);
    }
    wg_commit();
  };
  auto retire = [&](int qi) {
    wg_wait<1>();
    if (qi >= Q_G2 && qi < Q_G2 + 4) release_slot(sb, qi % NSTAGE, tid, 1);
    else if (qi >= Q_G2 + 4 && qi < Q_G2 + 11 && tid == 0) mbar_arrive(BAR_E2(sb, qi - Q_G2 - 4));
  };
  const uint32_t par = epoch & 1;
  auto put = [&](float (&acc)[32], int c) {
    fence_regs(acc);
    int o = jj + 1 + c;
    if (o >= 7) o -= 7;
    uint4* dst = p.s->part + ((((mt * 7 + o) * 6 + c) * 2 + wg) * 4) * 128 + tid;
#pragma unroll
    for (int v = 0; v < 4; v++) {
      const float* a = acc + 8 * v;
      st_relaxed(dst + v * 128, make_uint4((pack2(a[0], a[1]) & ~1u) | par, pack2(a[2], a[3]), pack2(a[4], a[5]), pack2(a[6], a[7])));
    }
  };
  const uint4* const src = p.s->part + (((mt * 7 + jj) * 6 * 2 + wg) * 4) * 128 + tid;
  auto gload = [&](uint4 (&pv)[8], int c) {
#pragma unroll
    for (int i = 0; i < 8; i++) pv[i] = ld_relaxed(src + ((2 * c + (i >> 2)) * 8 + (i & 3)) * 128);
  };
  auto gsum = [&](uint4 (&pv)[8], int c) {
#pragma unroll 1
    for (uint32_t n = 0; n < SPIN_LIMIT; n++) {
      uint32_t bad = 0;
#pragma unroll
      for (int i = 0; i < 8; i++) bad |= pv[i].x ^ par;
      if (!__any_sync(0xffffffffu, bad & 1)) break;
      gload(pv, c);
    }
    TL(24 + c);
#pragma unroll
    for (int i = 0; i < 8; i++) {
      const float t[8] = {bf_lo(pv[i].x), bf_hi(pv[i].x), bf_lo(pv[i].y), bf_hi(pv[i].y), bf_lo(pv[i].z), bf_hi(pv[i].z), bf_lo(pv[i].w), bf_hi(pv[i].w)};
#pragma unroll
      for (int k = 0; k < 8; k++) accA[8 * (i & 3) + k] += t[k];
    }
  };
  uint4 pv0[8], pv1[8], pv2[8];
  const int row = 128 * mt + 64 * wg + r0;
  uint32_t gt0, gt1;
#pragma unroll
  for (int c2 = 0; c2 < 4; c2++) {
    const int qi = Q_G2 + 4 * c2;
    stage(accA, qi);
    retire(qi - 1);
    stage(accA, qi + 1);
    if (c2 == 3) TL(27);
    if (c2 > 0) put(accB, 2 * c2 - 1);
    TL(7 + c2);
    if (c2 == 3) break;
    retire(qi);
    stage(accB, qi + 2);
    retire(qi + 1);
    stage(accB, qi + 3);
    put(accA, 2 * c2);
    if (c2 == 2) { gload(pv0, 0); gt0 = ld_relaxed(&p.s->gate[row]); gt1 = ld_relaxed(&p.s->gate[row + 8]); }
    retire(qi + 2);
  }
#pragma unroll
  for (int kb = 0; kb < 7; kb++) {
    const int qt = Q_XR + (kb >> 1);
    if ((kb & 1) == 0) mbar_wait(BAR_FULL(sb, qt % NSTAGE), (qt / NSTAGE) & 1);
    mbar_wait(BAR_Y(sb, kb), 0);
    const uint64_t da = mk_desc(sb + y_addr(kb) + wg * 8192, 8192, 1024, 1);
    const uint64_t db = mk_desc(sb + SM_RING + (qt % NSTAGE) * STAGE_BYTES + (kb & 1) * 8192, 16, 1024, 1);
    wg_fence();
#pragma unroll
    for (int kk = 0; kk < 4; kk++) wgmma_ss_n64<1, 0>(accB, da + kk * 128, db + kk * 2, (kb | kk) != 0);
    wg_commit();
    if (kb == GL1) gload(pv1, 1);
    if (kb == 1) { wg_wait<2>(); fence_regs(accA); TL(15); }
    if (kb == GS0) gsum(pv0, 0);
    if (kb == GL2) gload(pv2, 2);
    if (kb == GS1) gsum(pv1, 1);
  }
  TL(11);
  for (uint32_t n = 0; (((gt0 ^ epoch) | (gt1 ^ epoch)) & 0xffffu) && n < SPIN_LIMIT; n++) {
    gt0 = ld_relaxed(&p.s->gate[row]); gt1 = ld_relaxed(&p.s->gate[row + 8]);
  }
  gsum(pv2, 2);
  const float ga0 = bf_hi(gt0), ga1 = bf_hi(gt1);
  TL(12);
  wg_wait<0>();
  fence_regs(accB);
  TL(13);
  const float gb0 = bf_round(1.f - ga0), gb1 = bf_round(1.f - ga1);
  const float gs0 = ga0 * (2.f / (float)(S_ * D_)), gs1 = ga1 * (2.f / (float)(S_ * D_));
  uint4* const o = reinterpret_cast<uint4*>(p.out + (size_t)row * D_ + 64 * jj + 8 * q);
#pragma unroll
  for (int h = 0; h < 2; h++) {
    const float gs = h ? gs1 : gs0, gb = h ? gb1 : gb0;
#pragma unroll
    for (int k = 0; k < 2; k++) {
      uint32_t w[4];
#pragma unroll
      for (int j = 0; j < 4; j++) {
        const int i = 16 * k + 4 * j + 2 * h;
        w[j] = pack2(fmaf(gs, accB[i], gb * accA[i]), fmaf(gs, accB[i + 1], gb * accA[i + 1]));
      }
      const bool o1 = q & 1, o2 = q & 2;
      uint32_t a = __shfl_xor_sync(0xffffffffu, o1 ? w[0] : w[1], 1), b = __shfl_xor_sync(0xffffffffu, o1 ? w[2] : w[3], 1);
      if (o1) { w[0] = a; w[2] = b; } else { w[1] = a; w[3] = b; }
      a = __shfl_xor_sync(0xffffffffu, o2 ? w[0] : w[2], 2); b = __shfl_xor_sync(0xffffffffu, o2 ? w[1] : w[3], 2);
      if (o2) { w[0] = a; w[1] = b; } else { w[2] = a; w[3] = b; }
      o[h * D_ + 4 * k] = make_uint4(w[0], w[1], w[2], w[3]);
    }
  }
  if (lane == 0) *my_epoch = epoch;
  TL(14);
}

__device__ __forceinline__ void ring_issue(uint32_t sb, const Params& p, int qi, uint32_t slot, bool wait, uint32_t phase, int jj, uint32_t rank) {
  const CUtensorMap* m;
  int c0, c1, c2 = 0;
  bool half = false, is3d = false;
  if (qi < Q_G2) {
    const int nc = __popc(CMASK & ((1u << qi) - 1));
    if ((CMASK >> qi) & 1) {
      m = &p.ct; c0 = 64 * jj; c1 = 128 * nc + 64 * rank; half = nc == 3;
    } else {
      const int pass = qi >= Q_G1B;
      m = rank ? &p.wu : &p.wg; c0 = 0; c1 = 32 * (qi - nc - 14 * pass); c2 = 4 * jj + 2 * pass; is3d = true;
    }
  } else if (qi < Q_P3) {
    int o = jj + 1 + ((qi - Q_G2) >> 1);
    if (o >= 7) o -= 7;
    m = &p.wd; c0 = 64 * o; c1 = 256 * jj + 128 * (qi & 1) + 64 * rank;
  } else {
    m = &p.ct; c0 = 128 * (qi - Q_P3) + 64 * rank; c1 = 64 * jj; half = qi == Q_END - 1;
  }
  uint32_t bar = BAR_FULL(sb, slot), dst = sb + SM_RING + slot * STAGE_BYTES + rank * 8192;
  if (qi >= Q_XR && qi < Q_P3) {
    bar = BAR_X(sb, qi - Q_XR); dst = sb + SM_X + (qi - Q_XR) * 16384 + rank * 8192;
    if (qi < Q_XR + 2) mbar_wait_cluster(BAR_XFREE(sb), 0);
  } else {
    if (wait) mbar_wait_cluster(BAR_EMPTY(sb, slot), phase ^ (qi >= Q_P3));
    mbar_expect_tx(bar, half ? 8192 : 16384);
  }
  if (is3d) tma3d_mc(dst, m, c0, c1, c2, bar);
  else if (!(half && rank)) tma2d_mc(dst, m, c0, c1, bar);
}

__device__ __forceinline__ void ffn_producer(uint32_t sb, const uint8_t* smem, int bid, const Params& p, int warp, int lane, int mt, int jj, uint32_t rank) {
  if (warp < 2) {
    if (lane == 0) {
      uint32_t slot = warp, phase = 0;
#pragma unroll 1
      for (int qi = NSTAGE + warp; qi < Q_END; qi += 2) {
        ring_issue(sb, p, qi, slot, true, phase, jj, rank);
        TL(10 + qi);
        slot += 2;
        if (slot >= NSTAGE) { slot -= NSTAGE; phase ^= 1; }
      }
    }
  } else {
    const int wg = warp - 2;
    uint32_t* const my_epoch = &p.s->epoch[blockIdx.x * 12 + 8 + warp];
    const uint32_t epoch = ld_relaxed(my_epoch) + 1;
    if (wg == 0) {
      if (lane == 0) { prefetch_tmap(&p.wd); prefetch_tmap(&p.yt); }
      {
        const uint4* gw4 = reinterpret_cast<const uint4*>(p.gate_w);
        const uint4 ga = __ldg(gw4 + lane), gb = lane < 24 ? __ldg(gw4 + 32 + lane) : make_uint4(0, 0, 0, 0);
        if (lane < 7) { mbar_wait(BAR_X(sb, lane), 0); mbar_expect_tx(BAR_X(sb, lane), 16384); mbar_expect_tx(BAR_Y(sb, lane), 16384); }
        __syncwarp();
        float mine = 0.f;
#pragma unroll 1
        for (int u = 0; u < 19; u++) {
          const int r = min(19 * jj + u, 127);
          const uint8_t* xr = smem + SM_X + (lane >> 3) * 16384 + r * 128 + (((lane ^ r) & 7) << 4);
          const uint4 xa = *reinterpret_cast<const uint4*>(xr);
          const uint4 xb = lane < 24 ? *reinterpret_cast<const uint4*>(xr + 65536) : make_uint4(0, 0, 0, 0);
          float s = 0.f;
          auto dot2 = [&](uint32_t a, uint32_t b) {
            const uint32_t pr = mul2(a, b);
            s += bf_lo(pr) + bf_hi(pr);
          };
          dot2(xa.x, ga.x); dot2(xa.y, ga.y); dot2(xa.z, ga.z); dot2(xa.w, ga.w);
          dot2(xb.x, gb.x); dot2(xb.y, gb.y); dot2(xb.z, gb.z); dot2(xb.w, gb.w);
#pragma unroll
          for (int o = 16; o > 0; o >>= 1) s += __shfl_xor_sync(0xffffffffu, s, o);
          if (lane == u) mine = s;
        }
        if (lane < 19 && 19 * jj + lane < 128)
          st_relaxed(&p.s->gate[128 * mt + 19 * jj + lane], pack2(0.f, 1.f / (1.f + __expf(-bf_round(mine)))) | (epoch & 0xffffu));
      }
      TL(9);
      if (lane < 2) mbar_arrive_cluster(BAR_XFREE(sb), lane);
    } else {
      if (lane == 0) prefetch_tmap(&p.x1);
      mbar_wait(BAR_X(sb, PFAT), 0);
      if (lane < 6) {
        int row = 176 + 3 * bid + (lane >> 1);
        if (row >= D_) row -= D_;
        l2_prefetch(((lane & 1) ? p.pwu : p.pwg) + row * F_, F_ * 2);
      }
      TL(2);
      bar_sync(7, 160);
      if (lane == 0) {
        constexpr int slot = (31 - __builtin_clz(CMASK)) % NSTAGE;
        asm volatile("cp.async.bulk.tensor.2d.global.shared::cta.bulk_group [%0, {%2, %3}], [%1];"
                     ::"l"(&p.x1), "r"(sb + SM_RING + slot * STAGE_BYTES), "r"(64 * mt), "r"(128 * jj) : "memory");
        if (jj == 0) {
          bulk_s2g(p.s->x1t + 112 * 1024 + 8 * mt, sb + SM_ODD, 128);
          bulk_s2g(p.s->x1t + 112 * 1024 + 512 + 8 * mt, sb + SM_ODD + 128, 128);
        }
        asm volatile("cp.async.bulk.commit_group;" ::: "memory");
        asm volatile("cp.async.bulk.wait_group.read 0;" ::: "memory");
#pragma unroll
        for (int i = 0; i < 4; i++) mbar_arrive_cluster(BAR_EMPTY(sb, slot), i & 1);
        TL(6);
        asm volatile("cp.async.bulk.wait_group 0;" ::: "memory");
        red_add(&p.s->cnt_x1[jj * 32], 1);
        l2_prefetch(p.pwd + bid * 16 * D_, 32 * D_);
      }
      __syncwarp();
      TL(5);
    }
    mbar_wait(BAR_XFREE(sb), 0);
    TL(3);
    const int kb = 2 * lane + wg;
    bool todo = kb < 7;
    uint32_t n = 0;
    while (__any_sync(0xffffffffu, todo)) {
      if (todo) {
        uint32_t v, ok;
        asm volatile("ld.acquire.gpu.global.u32 %0, [%1];" : "=r"(v) : "l"(&p.s->cnt_y[kb * 32]) : "memory");
        asm volatile("{\n.reg .pred p;\nmbarrier.test_wait.parity.shared::cta.b64 p, [%1], 0;\nselp.u32 %0, 1, 0, p;\n}"
                     : "=r"(ok) : "r"(BAR_E2(sb, kb)) : "memory");
        if ((ok && (int32_t)(v - epoch * (kb ? 16 : 17)) >= 0) || ++n > SPIN_LIMIT) {
          tma3d(sb + y_addr(kb), &p.yt, 0, 64 * kb, 2 * mt, BAR_Y(sb, kb));
          todo = false;
        }
      }
    }
    TL(4);
    if (lane == 0) *my_epoch = epoch;
  }
}

__device__ __forceinline__ void spectral_cta(uint32_t sb, uint8_t* smem, const Params& p, int sc, int wg) {
  const int t384 = threadIdx.x, lane = t384 & 31, warp12 = t384 >> 5, tid = t384 & 127;
  const int warp = tid >> 5, q = lane & 3;
  const int sl0 = 6 * sc + min(sc, 8), nsl = sc < 8 ? 7 : 6;
  if (t384 == 320) {
#pragma unroll 1
    for (int i = 0; i < nsl; i++) {
      mbar_expect_tx(BAR_X(sb, i), 2 * SLAB_BYTES);
      const int row = 128 * ((sl0 + i) >> 3) + 8 * ((sl0 + i) & 7);
      const uint32_t dst = sb + SP_Z + 2 * i * SLAB_BYTES;
      bulk_g2s(dst, p.w_r + row * DF_, SLAB_BYTES / 2, BAR_X(sb, i));
      bulk_g2s(dst + SLAB_BYTES / 2, p.w_r + (row + 64) * DF_, SLAB_BYTES / 2, BAR_X(sb, i));
      bulk_g2s(dst + SLAB_BYTES, p.w_i + row * DF_, SLAB_BYTES / 2, BAR_X(sb, i));
      bulk_g2s(dst + 3 * SLAB_BYTES / 2, p.w_i + (row + 64) * DF_, SLAB_BYTES / 2, BAR_X(sb, i));
    }
    if (sc < 19) {
      mbar_expect_tx(BAR_Y(sb, 6), 24576);
      bulk_g2s(sb + SP_TW, p.spec, 24576, BAR_Y(sb, 6));
    }
  }
  uint32_t* const my_epoch = &p.s->epoch[blockIdx.x * 12 + warp12];
  const uint32_t epoch = ld_relaxed(my_epoch) + 1;
  uint32_t fe[16], tw[16];
#pragma unroll
  for (int i = 0; i < 4; i++) {
    const uint4 a = __ldg(reinterpret_cast<const uint4*>(p.spec->fe) + i * 128 + tid);
    const uint4 b = __ldg(reinterpret_cast<const uint4*>(p.spec->tw) + i * 128 + tid);
    fe[4 * i] = a.x; fe[4 * i + 1] = a.y; fe[4 * i + 2] = a.z; fe[4 * i + 3] = a.w;
    tw[4 * i] = b.x; tw[4 * i + 1] = b.y; tw[4 * i + 2] = b.z; tw[4 * i + 3] = b.w;
  }
  __syncwarp();
  asm volatile("barrier.cluster.wait.acquire.aligned;" ::: "memory");
#pragma unroll 2
  for (int un = wg; un < 8 * nsl; un += 3) {
    const int i = un >> 3, sl = sl0 + i, pr = 16 * (un & 7) + 4 * (lane >> 3) + warp, r = lane & 7;
    mbar_wait(BAR_X(sb, i), 0);
    if (pr < 113) {
      const uint16_t* w = reinterpret_cast<const uint16_t*>(smem + SP_Z + 2 * i * SLAB_BYTES) + r * DF_ + 2 * pr;
      const uint32_t m = pr < 112 ? 0xffffffffu : 0u;
      p.s->wt[pr * 1024 + sl * 8 + (r ^ ((sl >> 2) & 6))] =
          make_uint4(w[0] | ((uint32_t)w[8 * DF_] << 16), w[16 * DF_] | ((uint32_t)w[24 * DF_] << 16),
                     (w[1] | ((uint32_t)w[8 * DF_ + 1] << 16)) & m, (w[16 * DF_ + 1] | ((uint32_t)w[24 * DF_ + 1] << 16)) & m);
    }
  }
  __syncthreads();
  if (t384 == 352) { fence_gpu(); red_add(&p.s->cnt_w[0], 1); }
  TL(1);
  if (sc == 19) return;
  const int nrnd = (sc == 18 && wg == 2) ? 1 : 2;
  if (tid == 32) {
    wait_counter(&p.s->cnt_w[0], epoch * NSPEC);
    fence_async();
    for (int rnd = 0; rnd < nrnd; rnd++) {
      const int item = wg + 3 * rnd;
      mbar_expect_tx(BAR_Y(sb, item), 16384);
      bulk_g2s(sb + SP_W + item * 16384, p.s->wt + (6 * sc + item) * 1024, 16384, BAR_Y(sb, item));
    }
  } else if (tid == 0) {
#pragma unroll 1
    for (int rnd = 0; rnd < nrnd; rnd++) {
      const int item = wg + 3 * rnd, pr = 6 * sc + item;
      wait_counter(&p.s->cnt_x1[(pr < 112 ? pr >> 4 : 0) * 32], epoch * 16);
      const uint32_t bar = BAR_FULL(sb, item), z = sb + SP_Z + item * 16384;
      mbar_expect_tx(bar, 16384);
      bulk_g2s(z, p.s->x1t + pr * 1024, 16384, bar);
    }
  }
  __syncwarp();
  fence_regs(fe); fence_regs(tw);
  mbar_wait(BAR_Y(sb, 6), 0);
  TL(3);
  const uint64_t dT_n = mk_desc(sb + SP_T, 8192, 1024, 1);
#pragma unroll 1
  for (int rnd = 0; rnd < nrnd; rnd++) {
    const int item = wg + 3 * rnd, pr = 6 * sc + item;
    const uint32_t z = sb + SP_Z + item * 16384;
    uint32_t fa[16], fb[16];
    auto load_frag = [&](int off) {
#pragma unroll
      for (int i = 0; i < 4; i++) {
        const uint4 a = *reinterpret_cast<const uint4*>(smem + SP_TW + off + i * 2048 + tid * 16);
        fa[4 * i] = a.x; fa[4 * i + 1] = a.y; fa[4 * i + 2] = a.z; fa[4 * i + 3] = a.w;
      }
      fence_regs(fa);
    };
    load_frag(0);
    mbar_wait(BAR_FULL(sb, item), 0);
    TL(4 + 8 * rnd);
    if (rnd == 0 && wg > 0) bar_sync(3 + wg, 256);
    float aR[32], aI[32];
    {
      const uint64_t de = mk_desc(z, 4096, 512, 2);
      wg_fence();
#pragma unroll
      for (int kk = 0; kk < 4; kk++) {
        wgmma_rs_n64<1, 1>(aR, fe[4 * kk], fe[4 * kk + 1], fe[4 * kk + 2], fe[4 * kk + 3], de + kk * 64, kk != 0);
        wgmma_rs_n64<1, 1>(aI, fa[4 * kk], fa[4 * kk + 1], fa[4 * kk + 2], fa[4 * kk + 3], de + 512 + kk * 64, kk != 0);
      }
      wg_commit();
      if (rnd == 0 && wg < 2) bar_arrive(4 + wg, 256);
      wg_wait<0>();
      fence_regs(aR); fence_regs(aI);
    }
    TL(5 + 8 * rnd);
#pragma unroll
    for (int v = 0; v < 8; v++) {
      uint32_t* f = (v < 4 ? fa : fb) + 2 * (v & 3);
      const uint32_t* t = tw + 2 * (v & 3);
      const float *e = aR + 4 * v, *o = aI + 4 * v;
      const uint32_t er = pack2(e[0], e[1]), ei = pack2(e[2], e[3]), qr = pack2(o[0], o[1]), qi = pack2(o[2], o[3]);
      const uint32_t u0r = add2(er, qr), u0i = add2(ei, qi), u1r = sub2(er, qr), u1i = sub2(ei, qi);
      f[0] = fma2(u0r, t[0], mul2(u0i, t[8]));
      f[8] = fms2(u0i, t[0], mul2(u0r, t[8]));
      f[1] = fma2(u1r, t[1], mul2(u1i, t[9]));
      f[9] = fms2(u1i, t[1], mul2(u1r, t[9]));
    }
    fence_regs(fa); fence_regs(fb);
    wg_fence();
#pragma unroll
    for (int kk = 0; kk < 4; kk++) {
      wgmma_rs_n64<1, 1>(aR, fa[4 * kk], fa[4 * kk + 1], fa[4 * kk + 2], fa[4 * kk + 3], dT_n + kk * 128, kk != 0);
      wgmma_rs_n64<1, 1>(aI, fb[4 * kk], fb[4 * kk + 1], fb[4 * kk + 2], fb[4 * kk + 3], dT_n + kk * 128, kk != 0);
    }
    wg_commit();
    mbar_wait(BAR_Y(sb, item), 0);
    wg_wait<0>();
    fence_regs(aR); fence_regs(aI);
    TL(6 + 8 * rnd);
    {
      const uint8_t* wp = smem + SP_W + item * 16384 + q * 1024 + warp * 128 + (((lane >> 2) ^ (2 * q)) << 4);
#pragma unroll
      for (int jb = 0; jb < 4; jb++) {
#pragma unroll
        for (int h = 0; h < 2; h++) {
          const uint4 w = *reinterpret_cast<const uint4*>(wp + jb * 4096 + h * 512);
          const int i = 4 * jb + 2 * h;
          const uint32_t ar = pack2(aR[i], aR[i + 1]), ai = pack2(aR[16 + i], aR[17 + i]);
          const uint32_t br = pack2(aI[i], aI[i + 1]), bi = pack2(aI[16 + i], aI[17 + i]);
          fa[2 * jb + h] = fms2(ar, w.x, mul2(ai, w.y));
          fa[8 + 2 * jb + h] = fma2(ar, w.y, mul2(ai, w.x));
          fb[2 * jb + h] = fms2(br, w.z, mul2(bi, w.w));
          fb[8 + 2 * jb + h] = fma2(br, w.w, mul2(bi, w.z));
        }
      }
    }
    fence_regs(fa); fence_regs(fb);
    wg_fence();
#pragma unroll
    for (int kk = 0; kk < 4; kk++) {
      wgmma_rs_n64<1, 0>(aR, fa[4 * kk], fa[4 * kk + 1], fa[4 * kk + 2], fa[4 * kk + 3], dT_n + kk * 2, kk != 0);
      wgmma_rs_n64<1, 0>(aI, fb[4 * kk], fb[4 * kk + 1], fb[4 * kk + 2], fb[4 * kk + 3], dT_n + kk * 2, kk != 0);
    }
    wg_commit();
    wg_wait<0>();
    fence_regs(aR); fence_regs(aI);
    TL(7 + 8 * rnd);
#pragma unroll
    for (int v = 0; v < 8; v++) {
      const float* a = (v < 4 ? aR : aI) + 4 * (v & 3);
      const uint32_t* t = tw + 2 * (v & 3);
      const uint32_t u0r = pack2(a[0], a[1]), u1r = pack2(a[2], a[3]), u0i = pack2(a[16], a[17]), u1i = pack2(a[18], a[19]);
      const uint32_t t0r = fms2(u0r, t[0], mul2(u0i, t[8])), t0i = fma2(u0i, t[0], mul2(u0r, t[8]));
      const uint32_t t1r = fms2(u1r, t[1], mul2(u1i, t[9])), t1i = fma2(u1i, t[1], mul2(u1r, t[9]));
      fa[v] = add2(t0i, t1i); fa[8 + v] = add2(t0r, t1r);
      fb[v] = sub2(t0i, t1i); fb[8 + v] = sub2(t0r, t1r);
    }
    bar_sync(1 + wg, 128);
#pragma unroll
    for (int u = 0; u < 4; u++) {
      const uint32_t a = z + (32 * (u >> 1) + 8 * warp + (lane & 7)) * 128 + (((4 * (u & 1) + (lane >> 3)) ^ (lane & 7)) << 4);
      stmatrix_x4(a, fa[4 * u], fa[4 * u + 1], fa[4 * u + 2], fa[4 * u + 3]);
      stmatrix_x4(a + 8192, fb[4 * u], fb[4 * u + 1], fb[4 * u + 2], fb[4 * u + 3]);
    }
    load_frag(8192);
    fence_async_smem();
    bar_sync(1 + wg, 128);
    TL(8 + 8 * rnd);
    {
      const uint64_t de = mk_desc(z, 8192, 1024, 1);
      wg_fence();
#pragma unroll
      for (int kk = 0; kk < 4; kk++) {
        wgmma_rs_n64<1, 1>(aR, fe[4 * kk], fe[4 * kk + 1], fe[4 * kk + 2], fe[4 * kk + 3], de + kk * 128, kk != 0);
        wgmma_rs_n64<1, 1>(aI, fa[4 * kk], fa[4 * kk + 1], fa[4 * kk + 2], fa[4 * kk + 3], de + 512 + kk * 128, kk != 0);
      }
      wg_commit();
      wg_wait<0>();
      fence_regs(aR); fence_regs(aI);
    }
    TL(9 + 8 * rnd);
    const bool edge = pr == 0 || pr == 112;
    if (edge) {
#pragma unroll
      for (int i = 0; i < 16; i++) { aR[i] *= 0.5f; aI[i] *= 0.5f; }
    }
#pragma unroll
    for (int i = 0; i < 8; i++) {
      const float* a = ((i & 1) ? aI : aR) + 16 * (i >> 2) + 2 - (i & 2);
      *reinterpret_cast<uint4*>(smem + SP_W + item * 16384 + (i >> 1) * 4096 + (i & 1) * 64 + (tid >> 2) * 128 + q * 16) =
          make_uint4(pack2(a[0], a[1]), pack2(a[4], a[5]), pack2(a[8], a[9]), pack2(a[12], a[13]));
    }
    fence_async_smem();
    bar_sync(1 + wg, 128);
    if (tid == 0) {
      const uint32_t src = sb + SP_W + item * 16384;
      __nv_bfloat16* dst = p.s->yt + (size_t)(pr < 112 ? 4 * pr : 1) * S_;
      bulk_s2g(dst, src, edge ? 4096 : 16384);
      if (pr == 0) bulk_s2g(dst + 2 * S_, src + 8192, 8192);
      asm volatile("cp.async.bulk.commit_group;" ::: "memory");
      if (rnd == nrnd - 1) {
        asm volatile("cp.async.bulk.wait_group 0;" ::: "memory");
        TL(11);
        red_add(&p.s->cnt_y[(pr < 112 ? pr >> 4 : 0) * 32], 1);
        if (rnd) red_add(&p.s->cnt_y[((pr - 3) >> 4) * 32], 1);
      }
    }
    __syncwarp();
    TL(10 + 8 * rnd);
  }
  if (lane == 0) *my_epoch = epoch;
}

__global__ void __cluster_dims__(2, 1, 1) __launch_bounds__(384, 1)
fused_kernel(const __grid_constant__ Params p) {
  extern __shared__ __align__(1024) uint8_t smem[];
  const uint32_t sb = smem_u32(smem);
  TL(0);
  const uint32_t rank = blockIdx.x & 1;
  const int hc = blockIdx.x >> 1;
  int grp, jj;
  if (hc < 4) { grp = 8; jj = hc; }
  else if (hc < 36) { grp = (hc - 4) & 7; jj = (hc - 4) >> 3; }
  else if (hc < 57) { jj = (hc - 36) / 7; grp = 1 + (hc - 36) - 7 * jj; jj += 4; }
  else if (hc < 60) { grp = 0; jj = hc - 53; }
  else { grp = 8; jj = hc - 56; }
  const int mt = 2 * grp + rank, bid = 2 * (7 * grp + jj) + rank;
  if (threadIdx.x == 256) {
#pragma unroll
    for (int i = 0; i < NSTAGE; i++) { mbar_init(BAR_FULL(sb, i), 1); mbar_init(BAR_EMPTY(sb, i), 4); }
    asm volatile("fence.mbarrier_init.release.cluster;" ::: "memory");
  } else if (threadIdx.x == 320) {
#pragma unroll
    for (int i = 0; i < NSTAGE; i++) { mbar_init(BAR_X(sb, i), 1); mbar_init(BAR_Y(sb, i), 1); }
    mbar_init(BAR_XFREE(sb), 6);
#pragma unroll
    for (int i = 0; i < 7; i++) mbar_init(BAR_E2(sb, i), 2);
    asm volatile("fence.mbarrier_init.release.cluster;" ::: "memory");
  } else if (threadIdx.x == 288) {
    prefetch_tmap(rank ? &p.wu : &p.wg); prefetch_tmap(&p.ct);
  }
  __syncwarp();
  asm volatile("barrier.cluster.arrive.relaxed.aligned;" ::: "memory");
  const int wg = __shfl_sync(0xffffffffu, threadIdx.x >> 7, 0);
  if (bid >= NFFN) {
    spectral_cta(sb, smem, p, bid - NFFN, wg);
  } else if (wg < 2) {
    asm volatile("setmaxnreg.inc.sync.aligned.u32 232;");
    asm volatile("barrier.cluster.wait.acquire.aligned;" ::: "memory");
    TL(1);
    ffn_consumer(sb, smem, p, bid, wg, threadIdx.x & 127, mt, jj);
  } else {
    asm volatile("setmaxnreg.dec.sync.aligned.u32 40;");
    if (threadIdx.x == 320) {
      mbar_expect_tx(BAR_X(sb, 0), 16384);
      tma2d(sb + SM_X, &p.x, 0, 128 * mt, BAR_X(sb, 0));
    }
    __syncwarp();
    asm volatile("barrier.cluster.wait.acquire.aligned;" ::: "memory");
    TL(1);
    if (threadIdx.x == 320) {
      constexpr int order[13] = {XORDER};
#pragma unroll
      for (int i = 0; i < 13; i++) {
        if (order[i] < 8) {
          ring_issue(sb, p, order[i], order[i], false, 0, jj, rank);
        } else {
          const int kb = order[i] - 10;
          mbar_expect_tx(BAR_X(sb, kb), 16384);
          tma2d(sb + SM_X + kb * 16384, &p.x, 64 * kb, 128 * mt, BAR_X(sb, kb));
        }
      }
      TL(2);
    } else if (threadIdx.x == 352) {
    }
    __syncwarp();
    ffn_producer(sb, smem, bid, p, (threadIdx.x >> 5) & 3, threadIdx.x & 31, mt, jj, rank);
  }
}

typedef CUresult (*EncodeFn)(CUtensorMap*, CUtensorMapDataType, cuuint32_t, void*, const cuuint64_t*, const cuuint64_t*,
                             const cuuint32_t*, const cuuint32_t*, CUtensorMapInterleave, CUtensorMapSwizzle,
                             CUtensorMapL2promotion, CUtensorMapFloatOOBfill);

void make_map(EncodeFn fn, CUtensorMap* m, const void* base, int rank, const cuuint64_t* dims, const cuuint64_t* strides,
              const cuuint32_t* box, CUtensorMapSwizzle sw) {
  const cuuint32_t es[4] = {1, 1, 1, 1};
  fn(m, CU_TENSOR_MAP_DATA_TYPE_BFLOAT16, rank, const_cast<void*>(base), dims, strides, box, es,
     CU_TENSOR_MAP_INTERLEAVE_NONE, sw, CU_TENSOR_MAP_L2_PROMOTION_L2_256B, CU_TENSOR_MAP_FLOAT_OOB_FILL_NONE);
}

}

extern "C" void kernel_launch(void* const* d_in, const int* in_sizes, int n_in, void* d_out, int out_size) {
  const __nv_bfloat16* x = (const __nv_bfloat16*)d_in[0];
  const __nv_bfloat16* w_r = (const __nv_bfloat16*)d_in[1];
  const __nv_bfloat16* w_i = (const __nv_bfloat16*)d_in[2];
  const __nv_bfloat16* wg = (const __nv_bfloat16*)d_in[4];
  const __nv_bfloat16* wu = (const __nv_bfloat16*)d_in[5];
  const __nv_bfloat16* wd = (const __nv_bfloat16*)d_in[6];
  const __nv_bfloat16* gate_w = (const __nv_bfloat16*)d_in[7];

  void* fnp = nullptr;
  cudaDriverEntryPointQueryResult qr;
  cudaGetDriverEntryPoint("cuTensorMapEncodeTiled", &fnp, cudaEnableDefault, &qr);
  EncodeFn fn = (EncodeFn)fnp;
  void *ctab, *spec, *scr;
  cudaGetSymbolAddress(&ctab, g_ctab);
  cudaGetSymbolAddress(&spec, g_spec);
  cudaGetSymbolAddress(&scr, g_scratch);
  const void* yt = (const char*)scr + offsetof(Scratch, yt);
  Params p;
  p.s = (Scratch*)scr; p.out = (__nv_bfloat16*)d_out;
  p.px = x; p.w_r = w_r; p.w_i = w_i; p.gate_w = gate_w; p.pwg = wg; p.pwu = wu; p.pwd = wd;
  p.ctab = (const tab::Table*)ctab; p.spec = (const tab::Spec*)spec;
  {
    const cuuint64_t d[2] = {D_, S_}, s[1] = {D_ * 2};
    const cuuint32_t b[2] = {64, 128};
    make_map(fn, &p.x, x, 2, d, s, b, CU_TENSOR_MAP_SWIZZLE_128B);
  }
  {
    const cuuint64_t d[3] = {64, D_, F_ / 64}, s[2] = {F_ * 2, 128};
    const cuuint32_t b[3] = {64, 32, 2};
    make_map(fn, &p.wg, wg, 3, d, s, b, CU_TENSOR_MAP_SWIZZLE_128B);
    make_map(fn, &p.wu, wu, 3, d, s, b, CU_TENSOR_MAP_SWIZZLE_128B);
  }
  {
    const cuuint64_t d[2] = {D_, F_}, s[1] = {D_ * 2};
    const cuuint32_t b[2] = {64, 64};
    make_map(fn, &p.wd, wd, 2, d, s, b, CU_TENSOR_MAP_SWIZZLE_128B);
  }
  {
    const cuuint64_t d[2] = {D_, D_}, s[1] = {D_ * 2};
    const cuuint32_t b[2] = {64, 64};
    make_map(fn, &p.ct, ctab, 2, d, s, b, CU_TENSOR_MAP_SWIZZLE_128B);
  }
  {
    const cuuint64_t d[3] = {64, D_, S_ / 64}, s[2] = {S_ * 2, 128};
    const cuuint32_t b[3] = {64, 64, 2};
    make_map(fn, &p.yt, yt, 3, d, s, b, CU_TENSOR_MAP_SWIZZLE_128B);
  }
  {
    const cuuint64_t d[2] = {1024, 113 * 8}, s[1] = {2048};
    const cuuint32_t b[2] = {64, 128};
    make_map(fn, &p.x1, (const char*)scr + offsetof(Scratch, x1t), 2, d, s, b, CU_TENSOR_MAP_SWIZZLE_NONE);
  }
  cudaFuncSetAttribute(fused_kernel, cudaFuncAttributeMaxDynamicSharedMemorySize, SM_TOTAL);
  fused_kernel<<<NCTA, 384, SM_TOTAL, cudaStreamPerThread>>>(p, x, w_r, w_i, gate_w, wd, (__nv_bfloat16*)d_out);
}
```

```cpp
#include <cuda_runtime.h>
#include <cuda_bf16.h>
#include <cuda.h>
#include <stdint.h>
#include <stddef.h>

namespace {

constexpr int S_ = 2048, D_ = 448, F_ = 1792, DF_ = 225;
constexpr int NFFN = 112, NSPEC = 20, NCTA = NFFN + NSPEC;
constexpr int NSTAGE = 7, STAGE_BYTES = 16384;
constexpr int SM_X = 0, SM_RING = 114688, SM_BAR = 229376, SM_TOTAL = SM_BAR + 512;
constexpr int SP_Z = 0, SP_W = 98304, SP_TW = 198656, SP_T = 215040, SLAB_BYTES = 16 * DF_ * 2;
constexpr uint32_t SPIN_LIMIT = 1u << 20;

namespace tab {
constexpr double PI = 3.14159265358979323846264338327950288;
constexpr double csin(double x) {
  double t = x, s = x;
  for (int i = 1; i < 20; i++) { t = -t * x * x / ((2 * i) * (2 * i + 1)); s += t; }
  return s;
}
constexpr double ccos(double x) {
  double t = 1, s = 1;
  for (int i = 1; i < 20; i++) { t = -t * x * x / ((2 * i - 1) * (2 * i)); s += t; }
  return s;
}
constexpr uint32_t to_bf16(double v) {
  uint32_t sign = v < 0 ? 0x8000u : 0u;
  double a = v < 0 ? -v : v;
  if (a < 1e-12) return 0;
  int e = 0;
  while (a >= 2.0) { a /= 2; e++; }
  while (a < 1.0) { a *= 2; e--; }
  double m = a * 128.0;
  int mi = (int)m;
  double fr = m - mi;
  if (fr > 0.5 || (fr == 0.5 && (mi & 1))) mi++;
  if (mi == 256) { mi = 128; e++; }
  return sign | (uint32_t)((e + 127) << 7) | (uint32_t)(mi - 128);
}
struct Base { uint32_t v[448]; };
constexpr Base make_base() {
  Base b{};
  for (int m = 0; m < 448; m++) {
    int mm = m > 224 ? m - 448 : m;
    double ang = 2 * PI * mm / 448.0;
    b.v[m] = to_bf16(ccos(ang)) | (to_bf16(-csin(ang)) << 16);
  }
  return b;
}
constexpr Base base = make_base();
struct Row { uint32_t v[224]; };
constexpr Row make_row(int d) {
  Row r{};
  r.v[0] = 0x3f80u | ((d & 1) ? 0xbf800000u : 0x3f800000u);
  int m = 0;
  for (int c = 1; c < 224; c++) { m += d; if (m >= 448) m -= 448; r.v[c] = base.v[m]; }
  return r;
}
struct Table { Row r[448]; };
constexpr Table make_table() {
  Table t{};
  for (int d = 0; d < 448; d++) t.r[d] = make_row(d);
  return t;
}
struct Cs { double c[2048], s[2048]; };
constexpr Cs make_cs() {
  Cs t{};
  for (int m = 0; m <= 256; m++) {
    const double a = 2 * PI * m / 2048.0, c = ccos(a), s = csin(a);
    t.c[m] = c; t.s[m] = s;
    t.c[512 - m] = s; t.s[512 - m] = c;
  }
  for (int m = 513; m < 2048; m++) { t.c[m] = -t.s[m - 512]; t.s[m] = t.c[m - 512]; }
  return t;
}
constexpr Cs cs = make_cs();
struct Spec {
  uint32_t fo[2048], fot[2048];
  uint16_t t32[4096];
  uint32_t fe[2048];
  uint32_t tw[2048];
};
constexpr uint32_t blk(int h, int c, int a) { return to_bf16(h == c ? cs.c[a & 2047] : (h ? -cs.s[a & 2047] : cs.s[a & 2047])); }
constexpr Spec make_spec() {
  Spec t{};
  for (int row = 0; row < 64; row++)
    for (int col = 0; col < 64; col++) {
      const int c = row & 31, k2 = col & 31, n2 = 8 * ((c >> 1) & 3) + 2 * (c >> 3) + (c & 1), m = 64 * ((n2 * k2) & 31);
      const double v = (row >> 5) == (col >> 5) ? cs.c[m] : (row < 32 ? -cs.s[m] : cs.s[m]);
      t.t32[row * 64 + (((col >> 3) ^ (row & 7)) << 3) + (col & 7)] = (uint16_t)to_bf16(v);
    }
  for (int th = 0; th < 128; th++)
    for (int i = 0; i < 16; i++) {
      const int r = 8 * (th >> 5) + ((th & 31) >> 2), h = i & 1, c = i >> 3, m = 8 * ((i >> 1) & 3) + 2 * (th & 3);
      const int o = ((i >> 2) * 128 + th) * 4 + (i & 3);
      t.fe[o] = blk(h, c, 64 * m * r) | (blk(h, c, 64 * (m + 1) * r) << 16);
      t.fo[o] = blk(h, c, 32 * (2 * m + 1) * r) | (blk(h, c, 32 * (2 * m + 3) * r) << 16);
      t.fot[o] = blk(h, c, 32 * (2 * r + 1) * m) | (blk(h, c, 32 * (2 * r + 1) * (m + 1)) << 16);
      const int k1 = r + 32 * h, n2 = 8 * (th & 3) + 2 * ((i >> 1) & 3);
      t.tw[o] = blk(0, c, n2 * k1) | (blk(0, c, (n2 + 1) * k1) << 16);
    }
  return t;
}
}
}

__device__ __align__(1024) const tab::Table g_ctab = tab::make_table();
__device__ __align__(1024) const tab::Spec g_spec = tab::make_spec();

struct Scratch {
  uint32_t cnt_w[32];
  uint32_t cnt_x1[7 * 32];
  uint32_t cnt_y[7 * 32];
  uint32_t epoch[NCTA * 12 + 240 + 256];
  uint32_t gate[S_];
  uint4 x1t[113 * 1024];
  __nv_bfloat16 yt[D_ * S_];
  uint4 wt[114 * 1024];
  uint4 part[16 * 7 * 6 * 2 * 4 * 128];
};
static_assert(offsetof(Scratch, x1t) % 1024 == 0, "alignment");
__device__ __align__(1024) Scratch g_scratch;
#define TL(i)

namespace {

struct Params {
  Scratch* s;
  __nv_bfloat16* out;
  const __nv_bfloat16 *px, *w_r, *w_i, *gate_w, *pwg, *pwu, *pwd;
  const tab::Table* ctab;
  const tab::Spec* spec;
  CUtensorMap x, wg, wu, wd, ct, yt;
};

__device__ __forceinline__ uint32_t smem_u32(const void* p) { return (uint32_t)__cvta_generic_to_shared(p); }
__device__ __forceinline__ void mbar_init(uint32_t bar, uint32_t cnt) {
  asm volatile("mbarrier.init.shared::cta.b64 [%0], %1;" ::"r"(bar), "r"(cnt) : "memory");
}
__device__ __forceinline__ void mbar_expect_tx(uint32_t bar, uint32_t bytes) {
  asm volatile("mbarrier.arrive.expect_tx.shared::cta.b64 _, [%0], %1;" ::"r"(bar), "r"(bytes) : "memory");
}
__device__ __forceinline__ void mbar_arrive(uint32_t bar) {
  asm volatile("mbarrier.arrive.shared::cta.b64 _, [%0];" ::"r"(bar) : "memory");
}
__device__ __forceinline__ void mbar_arrive_cluster(uint32_t bar, uint32_t cta) {
  asm volatile("{\n.reg .b32 ra;\nmapa.shared::cluster.u32 ra, %0, %1;\n"
               "mbarrier.arrive.shared::cluster.b64 _, [ra];\n}" ::"r"(bar), "r"(cta) : "memory");
}
__device__ __forceinline__ void mbar_wait(uint32_t bar, uint32_t parity) {
  uint32_t ok, n = 0;
  do {
    asm volatile("{\n.reg .pred p;\nmbarrier.try_wait.parity.shared::cta.b64 p, [%1], %2;\nselp.u32 %0, 1, 0, p;\n}"
                 : "=r"(ok) : "r"(bar), "r"(parity) : "memory");
  } while (!ok && ++n < SPIN_LIMIT);
}
__device__ __forceinline__ void mbar_wait_cluster(uint32_t bar, uint32_t parity) {
  uint32_t ok, n = 0;
  do {
    asm volatile("{\n.reg .pred p;\nmbarrier.try_wait.parity.acquire.cluster.shared::cta.b64 p, [%1], %2;\nselp.u32 %0, 1, 0, p;\n}"
                 : "=r"(ok) : "r"(bar), "r"(parity) : "memory");
  } while (!ok && ++n < SPIN_LIMIT);
}
__device__ __forceinline__ void tma2d(uint32_t dst, const CUtensorMap* m, int c0, int c1, uint32_t bar) {
  asm volatile("cp.async.bulk.tensor.2d.shared::cluster.global.mbarrier::complete_tx::bytes [%0], [%1, {%3, %4}], [%2];"
               ::"r"(dst), "l"(m), "r"(bar), "r"(c0), "r"(c1) : "memory");
}
__device__ __forceinline__ void tma3d(uint32_t dst, const CUtensorMap* m, int c0, int c1, int c2, uint32_t bar) {
  asm volatile("cp.async.bulk.tensor.3d.shared::cluster.global.mbarrier::complete_tx::bytes [%0], [%1, {%3, %4, %5}], [%2];"
               ::"r"(dst), "l"(m), "r"(bar), "r"(c0), "r"(c1), "r"(c2) : "memory");
}
__device__ __forceinline__ void tma2d_mc(uint32_t dst, const CUtensorMap* m, int c0, int c1, uint32_t bar) {
  asm volatile("cp.async.bulk.tensor.2d.shared::cluster.global.mbarrier::complete_tx::bytes.multicast::cluster [%0], [%1, {%3, %4}], [%2], %5;"
               ::"r"(dst), "l"(m), "r"(bar), "r"(c0), "r"(c1), "h"((uint16_t)3) : "memory");
}
__device__ __forceinline__ void tma3d_mc(uint32_t dst, const CUtensorMap* m, int c0, int c1, int c2, uint32_t bar) {
  asm volatile("cp.async.bulk.tensor.3d.shared::cluster.global.mbarrier::complete_tx::bytes.multicast::cluster [%0], [%1, {%3, %4, %5}], [%2], %6;"
               ::"r"(dst), "l"(m), "r"(bar), "r"(c0), "r"(c1), "r"(c2), "h"((uint16_t)3) : "memory");
}
__device__ __forceinline__ void bulk_g2s(uint32_t dst, const void* src, uint32_t bytes, uint32_t bar) {
  asm volatile("cp.async.bulk.shared::cluster.global.mbarrier::complete_tx::bytes [%0], [%1], %2, [%3];"
               ::"r"(dst), "l"(src), "r"(bytes), "r"(bar) : "memory");
}
__device__ __forceinline__ void bulk_s2g(void* dst, uint32_t src, uint32_t bytes) {
  asm volatile("cp.async.bulk.global.shared::cta.bulk_group [%0], [%1], %2;" ::"l"(dst), "r"(src), "r"(bytes) : "memory");
}
__device__ __forceinline__ void prefetch_tmap(const CUtensorMap* m) {
  asm volatile("prefetch.tensormap [%0];" ::"l"(m) : "memory");
}
__device__ __forceinline__ void l2_prefetch(const void* p, uint32_t bytes) {
  asm volatile("cp.async.bulk.prefetch.L2.global [%0], %1;" ::"l"(p), "r"(bytes) : "memory");
}
__device__ __forceinline__ void wg_fence() { asm volatile("wgmma.fence.sync.aligned;" ::: "memory"); }
__device__ __forceinline__ void wg_commit() { asm volatile("wgmma.commit_group.sync.aligned;" ::: "memory"); }
template <int N> __device__ __forceinline__ void wg_wait() { asm volatile("wgmma.wait_group.sync.aligned %0;" ::"n"(N) : "memory"); }
template <int N> __device__ __forceinline__ void fence_regs(float (&d)[N]) {
#pragma unroll
  for (int i = 0; i < N; i++) asm volatile("" : "+f"(d[i])::"memory");
}
template <int N> __device__ __forceinline__ void fence_regs(uint32_t (&d)[N]) {
#pragma unroll
  for (int i = 0; i < N; i++) asm volatile("" : "+r"(d[i])::"memory");
}
__device__ __forceinline__ void bar_sync(int id, int n) { asm volatile("bar.sync %0, %1;" ::"r"(id), "r"(n) : "memory"); }
__device__ __forceinline__ void bar_arrive(int id, int n) { asm volatile("bar.arrive %0, %1;" ::"r"(id), "r"(n) : "memory"); }
__device__ __forceinline__ void fence_gpu() { asm volatile("fence.acq_rel.gpu;" ::: "memory"); }
__device__ __forceinline__ void fence_async() { asm volatile("fence.proxy.async;" ::: "memory"); }
__device__ __forceinline__ void fence_async_smem() { asm volatile("fence.proxy.async.shared::cta;" ::: "memory"); }
__device__ __forceinline__ void red_add(uint32_t* p, uint32_t v) {
  asm volatile("red.relaxed.gpu.global.add.u32 [%0], %1;" ::"l"(p), "r"(v) : "memory");
}
__device__ __forceinline__ uint32_t ld_relaxed(const uint32_t* p) {
  uint32_t v;
  asm volatile("ld.relaxed.gpu.global.u32 %0, [%1];" : "=r"(v) : "l"(p) : "memory");
  return v;
}
__device__ __forceinline__ void wait_counter(const uint32_t* p, uint32_t target) {
  uint32_t v, n = 0;
  while (true) {
    asm volatile("ld.acquire.gpu.global.u32 %0, [%1];" : "=r"(v) : "l"(p) : "memory");
    if ((int32_t)(v - target) >= 0 || ++n > SPIN_LIMIT) break;
  }
}
__device__ __forceinline__ uint4 ld_relaxed(const uint4* p) {
  uint4 v;
  asm volatile("ld.relaxed.gpu.global.v4.u32 {%0, %1, %2, %3}, [%4];" : "=r"(v.x), "=r"(v.y), "=r"(v.z), "=r"(v.w) : "l"(p) : "memory");
  return v;
}
__device__ __forceinline__ void st_relaxed(uint4* p, uint4 v) {
  asm volatile("st.relaxed.gpu.global.v4.u32 [%0], {%1, %2, %3, %4};" ::"l"(p), "r"(v.x), "r"(v.y), "r"(v.z), "r"(v.w) : "memory");
}
__device__ __forceinline__ void st_relaxed(uint32_t* p, uint32_t v) {
  asm volatile("st.relaxed.gpu.global.u32 [%0], %1;" ::"l"(p), "r"(v) : "memory");
}
__device__ __forceinline__ uint32_t pack2(float lo, float hi) {
  uint32_t r;
  asm("cvt.rn.bf16x2.f32 %0, %1, %2;" : "=r"(r) : "f"(hi), "f"(lo));
  return r;
}
__device__ __forceinline__ uint32_t mul2(uint32_t a, uint32_t b) {
  uint32_t r;
  asm("mul.rn.bf16x2 %0, %1, %2;" : "=r"(r) : "r"(a), "r"(b));
  return r;
}
__device__ __forceinline__ uint32_t fma2(uint32_t a, uint32_t b, uint32_t c) {
  uint32_t r;
  asm("fma.rn.bf16x2 %0, %1, %2, %3;" : "=r"(r) : "r"(a), "r"(b), "r"(c));
  return r;
}
__device__ __forceinline__ uint32_t add2(uint32_t a, uint32_t b) {
  uint32_t r;
  asm("add.rn.bf16x2 %0, %1, %2;" : "=r"(r) : "r"(a), "r"(b));
  return r;
}
__device__ __forceinline__ uint32_t sub2(uint32_t a, uint32_t b) {
  uint32_t r;
  asm("sub.rn.bf16x2 %0, %1, %2;" : "=r"(r) : "r"(a), "r"(b));
  return r;
}
__device__ __forceinline__ uint32_t fms2(uint32_t a, uint32_t b, uint32_t c) {
  uint32_t r;
  asm("{\n.reg .b32 n;\nneg.bf16x2 n, %3;\nfma.rn.bf16x2 %0, %1, %2, n;\n}" : "=r"(r) : "r"(a), "r"(b), "r"(c));
  return r;
}
__device__ __forceinline__ float bf_lo(uint32_t v) { return __uint_as_float(v << 16); }
__device__ __forceinline__ float bf_hi(uint32_t v) { return __uint_as_float(v & 0xffff0000u); }
__device__ __forceinline__ float bf_round(float v) { return bf_lo(pack2(v, 0.f)); }
__device__ __forceinline__ float tanh_fast(float v) {
  float r;
  asm("tanh.approx.f32 %0, %1;" : "=f"(r) : "f"(v));
  return r;
}
__device__ __forceinline__ uint64_t mk_desc(uint32_t addr, uint32_t lbo, uint32_t sbo, uint32_t mode) {
  return (uint64_t)((addr & 0x3FFFF) >> 4) | ((uint64_t)(lbo >> 4) << 16) | ((uint64_t)(sbo >> 4) << 32) | ((uint64_t)mode << 62);
}
__device__ __forceinline__ void stmatrix_x4(uint32_t addr, uint32_t r0, uint32_t r1, uint32_t r2, uint32_t r3) {
  asm volatile("stmatrix.sync.aligned.m8n8.x4.shared.b16 [%0], {%1, %2, %3, %4};" ::"r"(addr), "r"(r0), "r"(r1), "r"(r2), "r"(r3) : "memory");
}

template <int TA, int TB>
__device__ __forceinline__ void wgmma_ss_n256(float (&d)[128], uint64_t da, uint64_t db, int sd) {
  asm volatile("{\n.reg .pred p;\nsetp.ne.b32 p, %130, 0;\n"
      "wgmma.mma_async.sync.aligned.m64n256k16.f32.bf16.bf16 {"
      "%0, %1, %2, %3, %4, %5, %6, %7, %8, %9, %10, %11, %12, %13, %14, %15, %16, %17, %18, %19, %20, %21, %22, %23, "
      "%24, %25, %26, %27, %28, %29, %30, %31, %32, %33, %34, %35, %36, %37, %38, %39, %40, %41, %42, %43, %44, %45, "
      "%46, %47, %48, %49, %50, %51, %52, %53, %54, %55, %56, %57, %58, %59, %60, %61, %62, %63, %64, %65, %66, %67, "
      "%68, %69, %70, %71, %72, %73, %74, %75, %76, %77, %78, %79, %80, %81, %82, %83, %84, %85, %86, %87, %88, %89, "
      "%90, %91, %92, %93, %94, %95, %96, %97, %98, %99, %100, %101, %102, %103, %104, %105, %106, %107, %108, %109, "
      "%110, %111, %112, %113, %114, %115, %116, %117, %118, %119, %120, %121, %122, %123, %124, %125, %126, %127"
      "}, %128, %129, p, 1, 1, %131, %132;\n}\n"
      : "+f"(d[0]), "+f"(d[1]), "+f"(d[2]), "+f"(d[3]), "+f"(d[4]), "+f"(d[5]), "+f"(d[6]), "+f"(d[7]), "+f"(d[8]),
        "+f"(d[9]), "+f"(d[10]), "+f"(d[11]), "+f"(d[12]), "+f"(d[13]), "+f"(d[14]), "+f"(d[15]), "+f"(d[16]),
        "+f"(d[17]), "+f"(d[18]), "+f"(d[19]), "+f"(d[20]), "+f"(d[21]), "+f"(d[22]), "+f"(d[23]), "+f"(d[24]),
        "+f"(d[25]), "+f"(d[26]), "+f"(d[27]), "+f"(d[28]), "+f"(d[29]), "+f"(d[30]), "+f"(d[31]), "+f"(d[32]),
        "+f"(d[33]), "+f"(d[34]), "+f"(d[35]), "+f"(d[36]), "+f"(d[37]), "+f"(d[38]), "+f"(d[39]), "+f"(d[40]),
        "+f"(d[41]), "+f"(d[42]), "+f"(d[43]), "+f"(d[44]), "+f"(d[45]), "+f"(d[46]), "+f"(d[47]), "+f"(d[48]),
        "+f"(d[49]), "+f"(d[50]), "+f"(d[51]), "+f"(d[52]), "+f"(d[53]), "+f"(d[54]), "+f"(d[55]), "+f"(d[56]),
        "+f"(d[57]), "+f"(d[58]), "+f"(d[59]), "+f"(d[60]), "+f"(d[61]), "+f"(d[62]), "+f"(d[63]), "+f"(d[64]),
        "+f"(d[65]), "+f"(d[66]), "+f"(d[67]), "+f"(d[68]), "+f"(d[69]), "+f"(d[70]), "+f"(d[71]), "+f"(d[72]),
        "+f"(d[73]), "+f"(d[74]), "+f"(d[75]), "+f"(d[76]), "+f"(d[77]), "+f"(d[78]), "+f"(d[79]), "+f"(d[80]),
        "+f"(d[81]), "+f"(d[82]), "+f"(d[83]), "+f"(d[84]), "+f"(d[85]), "+f"(d[86]), "+f"(d[87]), "+f"(d[88]),
        "+f"(d[89]), "+f"(d[90]), "+f"(d[91]), "+f"(d[92]), "+f"(d[93]), "+f"(d[94]), "+f"(d[95]), "+f"(d[96]),
        "+f"(d[97]), "+f"(d[98]), "+f"(d[99]), "+f"(d[100]), "+f"(d[101]), "+f"(d[102]), "+f"(d[103]), "+f"(d[104]),
        "+f"(d[105]), "+f"(d[106]), "+f"(d[107]), "+f"(d[108]), "+f"(d[109]), "+f"(d[110]), "+f"(d[111]),
        "+f"(d[112]), "+f"(d[113]), "+f"(d[114]), "+f"(d[115]), "+f"(d[116]), "+f"(d[117]), "+f"(d[118]),
        "+f"(d[119]), "+f"(d[120]), "+f"(d[121]), "+f"(d[122]), "+f"(d[123]), "+f"(d[124]), "+f"(d[125]),
        "+f"(d[126]), "+f"(d[127])
      : "l"(da), "l"(db), "r"(sd), "n"(TA), "n"(TB));
}
template <int TA, int TB>
__device__ __forceinline__ void wgmma_ss_n128(float (&d)[64], uint64_t da, uint64_t db, int sd) {
  asm volatile("{\n.reg .pred p;\nsetp.ne.b32 p, %66, 0;\n"
      "wgmma.mma_async.sync.aligned.m64n128k16.f32.bf16.bf16 {"
      "%0, %1, %2, %3, %4, %5, %6, %7, %8, %9, %10, %11, %12, %13, %14, %15, %16, %17, %18, %19, %20, %21, %22, %23, "
      "%24, %25, %26, %27, %28, %29, %30, %31, %32, %33, %34, %35, %36, %37, %38, %39, %40, %41, %42, %43, %44, %45, "
      "%46, %47, %48, %49, %50, %51, %52, %53, %54, %55, %56, %57, %58, %59, %60, %61, %62, %63"
      "}, %64, %65, p, 1, 1, %67, %68;\n}\n"
      : "+f"(d[0]), "+f"(d[1]), "+f"(d[2]), "+f"(d[3]), "+f"(d[4]), "+f"(d[5]), "+f"(d[6]), "+f"(d[7]), "+f"(d[8]),
        "+f"(d[9]), "+f"(d[10]), "+f"(d[11]), "+f"(d[12]), "+f"(d[13]), "+f"(d[14]), "+f"(d[15]), "+f"(d[16]),
        "+f"(d[17]), "+f"(d[18]), "+f"(d[19]), "+f"(d[20]), "+f"(d[21]), "+f"(d[22]), "+f"(d[23]), "+f"(d[24]),
        "+f"(d[25]), "+f"(d[26]), "+f"(d[27]), "+f"(d[28]), "+f"(d[29]), "+f"(d[30]), "+f"(d[31]), "+f"(d[32]),
        "+f"(d[33]), "+f"(d[34]), "+f"(d[35]), "+f"(d[36]), "+f"(d[37]), "+f"(d[38]), "+f"(d[39]), "+f"(d[40]),
        "+f"(d[41]), "+f"(d[42]), "+f"(d[43]), "+f"(d[44]), "+f"(d[45]), "+f"(d[46]), "+f"(d[47]), "+f"(d[48]),
        "+f"(d[49]), "+f"(d[50]), "+f"(d[51]), "+f"(d[52]), "+f"(d[53]), "+f"(d[54]), "+f"(d[55]), "+f"(d[56]),
        "+f"(d[57]), "+f"(d[58]), "+f"(d[59]), "+f"(d[60]), "+f"(d[61]), "+f"(d[62]), "+f"(d[63])
      : "l"(da), "l"(db), "r"(sd), "n"(TA), "n"(TB));
}
template <int TA, int TB>
__device__ __forceinline__ void wgmma_ss_n64(float (&d)[32], uint64_t da, uint64_t db, int sd) {
  asm volatile("{\n.reg .pred p;\nsetp.ne.b32 p, %34, 0;\n"
      "wgmma.mma_async.sync.aligned.m64n64k16.f32.bf16.bf16 {"
      "%0, %1, %2, %3, %4, %5, %6, %7, %8, %9, %10, %11, %12, %13, %14, %15, %16, %17, %18, %19, %20, %21, %22, %23, "
      "%24, %25, %26, %27, %28, %29, %30, %31"
      "}, %32, %33, p, 1, 1, %35, %36;\n}\n"
      : "+f"(d[0]), "+f"(d[1]), "+f"(d[2]), "+f"(d[3]), "+f"(d[4]), "+f"(d[5]), "+f"(d[6]), "+f"(d[7]), "+f"(d[8]),
        "+f"(d[9]), "+f"(d[10]), "+f"(d[11]), "+f"(d[12]), "+f"(d[13]), "+f"(d[14]), "+f"(d[15]), "+f"(d[16]),
        "+f"(d[17]), "+f"(d[18]), "+f"(d[19]), "+f"(d[20]), "+f"(d[21]), "+f"(d[22]), "+f"(d[23]), "+f"(d[24]),
        "+f"(d[25]), "+f"(d[26]), "+f"(d[27]), "+f"(d[28]), "+f"(d[29]), "+f"(d[30]), "+f"(d[31])
      : "l"(da), "l"(db), "r"(sd), "n"(TA), "n"(TB));
}
template <int SA, int TB>
__device__ __forceinline__ void wgmma_rs_n64(float (&d)[32], uint32_t a0, uint32_t a1, uint32_t a2, uint32_t a3, uint64_t db, int sd) {
  asm volatile("{\n.reg .pred p;\nsetp.ne.b32 p, %37, 0;\n"
      "wgmma.mma_async.sync.aligned.m64n64k16.f32.bf16.bf16 {"
      "%0, %1, %2, %3, %4, %5, %6, %7, %8, %9, %10, %11, %12, %13, %14, %15, %16, %17, %18, %19, %20, %21, %22, %23, "
      "%24, %25, %26, %27, %28, %29, %30, %31"
      "}, {%32, %33, %34, %35}, %36, p, %38, 1, %39;\n}\n"
      : "+f"(d[0]), "+f"(d[1]), "+f"(d[2]), "+f"(d[3]), "+f"(d[4]), "+f"(d[5]), "+f"(d[6]), "+f"(d[7]), "+f"(d[8]),
        "+f"(d[9]), "+f"(d[10]), "+f"(d[11]), "+f"(d[12]), "+f"(d[13]), "+f"(d[14]), "+f"(d[15]), "+f"(d[16]),
        "+f"(d[17]), "+f"(d[18]), "+f"(d[19]), "+f"(d[20]), "+f"(d[21]), "+f"(d[22]), "+f"(d[23]), "+f"(d[24]),
        "+f"(d[25]), "+f"(d[26]), "+f"(d[27]), "+f"(d[28]), "+f"(d[29]), "+f"(d[30]), "+f"(d[31])
      : "r"(a0), "r"(a1), "r"(a2), "r"(a3), "l"(db), "r"(sd), "n"(SA), "n"(TB));
}

__device__ __forceinline__ uint32_t BAR_FULL(uint32_t sb, int i) { return sb + SM_BAR + 8 * i; }
__device__ __forceinline__ uint32_t BAR_EMPTY(uint32_t sb, int i) { return sb + SM_BAR + 64 + 8 * i; }
__device__ __forceinline__ uint32_t BAR_X(uint32_t sb, int i) { return sb + SM_BAR + 128 + 8 * i; }
__device__ __forceinline__ uint32_t BAR_Y(uint32_t sb, int i) { return sb + SM_BAR + 192 + 8 * i; }
__device__ __forceinline__ uint32_t BAR_XFREE(uint32_t sb) { return sb + SM_BAR + 256; }

__device__ __forceinline__ uint32_t BAR_E2(uint32_t sb, int i) { return sb + SM_BAR + 264 + 8 * i; }
#define CMASK 0x194u
#define XORDER 0, 1, 11, 2, 3, 12, 13, 4, 5, 14, 6, 15, 16
#define XSPREAD 2
#define PFAT 3
#define SKEW 3
#define GL1 0
#define GS0 2
#define GL2 4
#define GS1 5
constexpr int Q_G1B = 18, Q_G2 = 32, Q_XR = 39, Q_P3 = 46, Q_END = 50;

__device__ __forceinline__ uint32_t y_addr(int kb) { return kb < 3 ? SM_RING + (kb + (Q_G2 + 4) % NSTAGE) * STAGE_BYTES : SM_X + (kb - 3) * 16384; }
static_assert((Q_G2 + 4) % NSTAGE + 2 < NSTAGE, "");

struct Ring {
  uint32_t slot, phase;
  __device__ __forceinline__ void next() { if (++slot == NSTAGE) { slot = 0; phase ^= 1; } }
};

__device__ __forceinline__ void release_slot(uint32_t sb, uint32_t slot, int tid, int times) {
  if (tid < 2 * times) mbar_arrive_cluster(BAR_EMPTY(sb, slot), tid & 1);
}

__device__ __forceinline__ void ffn_consumer(uint32_t sb, const uint8_t* smem, const Params& p, int bid, int wg, int tid, int mt, int jj) {
  const int lane = tid & 31, warp = tid >> 5, q = lane & 3, r0 = 16 * warp + (lane >> 2);
  uint32_t* const my_epoch = &p.s->epoch[blockIdx.x * 12 + (threadIdx.x >> 5)];
  const uint32_t epoch = ld_relaxed(my_epoch) + 1;
  Ring rg{0, 0};
  uint32_t u[64];
  float acc[128];
  uint32_t prev = 0, cmask = CMASK;
  int st = 0;
  auto g1_stage = [&](uint32_t slot, int s) {
    const uint64_t da = mk_desc(sb + SM_X + (s >> 1) * 16384 + wg * 8192 + (s & 1) * 64, 16, 1024, 1);
    const uint64_t db = mk_desc(sb + SM_RING + slot * STAGE_BYTES, 4096, 1024, 1);
    wg_fence();
    wgmma_ss_n256<0, 1>(acc, da, db, s != 0);
    wgmma_ss_n256<0, 1>(acc, da + 2, db + 128, 1);
    wg_commit();
  };
  if (wg == 1) {
    float ap[64];
    constexpr int QX = 32 - __builtin_clz(CMASK);
    constexpr int NPRE = QX + XSPREAD;
    uint4* const x1dst = p.s->x1t + ((64 * jj + r0 + 8) >> 2) * 1024 + (r0 & 3) * 128 + 8 * mt + (q ^ (mt & 3));
    const int x1lo = 64 * jj + r0 == 1 ? 110 * 1024 - 128 : -2048;
#pragma unroll
    for (int qi = 0; qi < NPRE; qi++) {
      const int slot = qi % NSTAGE, nc = __builtin_popcount(CMASK & ((1u << qi) - 1));
      if (qi == 0) TL(60);
      mbar_wait(BAR_FULL(sb, slot), (qi / NSTAGE) & 1);
      if (qi == 0) TL(61);
      if ((CMASK >> qi) & 1) {
#pragma unroll
        for (int kb = 2 * nc; kb < 2 * nc + 2 && kb < 7; kb++) {
          const uint64_t da = mk_desc(sb + SM_RING + slot * STAGE_BYTES + (kb & 1) * 8192, 8192, 1024, 1);
          const uint64_t db = mk_desc(sb + SM_X + kb * 16384, 16, 1024, 1);
          mbar_wait(BAR_X(sb, kb), 0);
          TL(16 + kb);
          wg_fence();
#pragma unroll
          for (int kk = 0; kk < 4; kk++) wgmma_ss_n128<1, 0>(ap, da + kk * 128, db + kk * 2, (kb | kk) != 0);
          wg_commit();
        }
      } else {
        if (((qi - nc) & 1) == 0 && qi - nc >= 4 * nc) mbar_wait(BAR_X(sb, (qi - nc) >> 1), 0);
        TL(32 + qi - nc);
        g1_stage(slot, qi - nc);
      }
      if (qi > 0) {
        wg_wait<1>();
        release_slot(sb, (qi - 1) % NSTAGE, tid, ((CMASK >> (qi - 1)) & 1) ? 2 : 1);
      }
      if (qi >= QX) {
        if (qi == QX) { fence_regs(ap); TL(2); }
#pragma unroll
        for (int t = (qi - QX) * (4 / XSPREAD); t < (qi - QX + 1) * (4 / XSPREAD); t++)
#pragma unroll
        for (int h = 0; h < 2; h++)
          x1dst[(h ? 0 : x1lo) + 512 * (t & 1) + 4 * (t >> 1)] = make_uint4(pack2(ap[16 * t + 2 * h], ap[16 * t + 2 * h + 1]), pack2(ap[16 * t + 4 + 2 * h], ap[16 * t + 5 + 2 * h]),
                                             pack2(ap[16 * t + 8 + 2 * h], ap[16 * t + 9 + 2 * h]), pack2(ap[16 * t + 12 + 2 * h], ap[16 * t + 13 + 2 * h]));
      }
    }
    bar_arrive(7, 160);
    st = NPRE - 4; cmask = 0; prev = (NPRE - 1) % NSTAGE;
    rg.slot = NPRE % NSTAGE; rg.phase = (NPRE / NSTAGE) & 1;
  }
#pragma unroll 1
  for (int pass = 0; pass < 2; pass++) {
#pragma unroll 1
    for (; st < 14; st++) {
      while (cmask & 1) { cmask >>= 1; rg.next(); }
      cmask >>= 1;
      if (pass == 0 && (st & 1) == 0) mbar_wait(BAR_X(sb, st >> 1), 0);
      if (st == 14 - SKEW && wg == 1) bar_sync(9 + pass, 256);
      mbar_wait(BAR_FULL(sb, rg.slot), rg.phase);
      TL(32 + 14 * pass + st);
      g1_stage(rg.slot, st);
      wg_wait<1>();
      if (st > 0) release_slot(sb, prev, tid, 1);
      prev = rg.slot;
      rg.next();
    }
    st = 0;
    if (wg == 0) bar_arrive(9 + pass, 256);
    wg_wait<0>();
    fence_regs(acc);
    release_slot(sb, prev, tid, 1);
    if (pass == 1 && tid < 2) mbar_arrive_cluster(BAR_XFREE(sb), tid);
    TL(3 + 2 * pass);
#pragma unroll
    for (int i = 0; i < 32; i++) {
      const float g0 = 0.5f * acc[2 * i], g1 = 0.5f * acc[2 * i + 1];
      const float s0 = fmaf(g0, tanh_fast(g0), g0), s1 = fmaf(g1, tanh_fast(g1), g1);
      u[32 + i] = pack2(s0 * acc[64 + 2 * i], s1 * acc[64 + 2 * i + 1]);
    }
    if (pass == 0) {
#pragma unroll
      for (int i = 0; i < 32; i++) u[i] = u[32 + i];
    }
    TL(4 + 2 * pass);
  }
  fence_regs(u);
  float accA[32], accB[32];
  auto stage = [&](float (&acc)[32], int qi) {
    const int st = qi & 1;
    if (qi < Q_XR) mbar_wait(BAR_FULL(sb, qi % NSTAGE), (qi / NSTAGE) & 1);
    else mbar_wait(BAR_X(sb, qi - Q_XR), 1);
    const uint64_t db = mk_desc(sb + (qi < Q_XR ? SM_RING + (qi % NSTAGE) * STAGE_BYTES : SM_X + (qi - Q_XR) * 16384), 8192, 1024, 1);
    wg_fence();
#pragma unroll
    for (int kk = 0; kk < 8; kk++) {
      const uint32_t* a = u + 32 * st + 4 * kk;
      wgmma_rs_n64<1, 1>(acc, a[0], a[1], a[2], a[3], db + kk * 128, (st | kk) != 0);
    }
    wg_commit();
  };
  auto retire = [&](int qi) {
    wg_wait<1>();
    if (qi >= Q_G2 && qi < Q_G2 + 4) release_slot(sb, qi % NSTAGE, tid, 1);
    else if (qi >= Q_G2 + 4 && qi < Q_G2 + 11 && tid == 0) mbar_arrive(BAR_E2(sb, qi - Q_G2 - 4));
  };
  const uint32_t par = epoch & 1;
  auto put = [&](float (&acc)[32], int c) {
    fence_regs(acc);
    int o = jj + 1 + c;
    if (o >= 7) o -= 7;
    uint4* dst = p.s->part + ((((mt * 7 + o) * 6 + c) * 2 + wg) * 4) * 128 + tid;
#pragma unroll
    for (int v = 0; v < 4; v++) {
      const float* a = acc + 8 * v;
      st_relaxed(dst + v * 128, make_uint4((pack2(a[0], a[1]) & ~1u) | par, pack2(a[2], a[3]), pack2(a[4], a[5]), pack2(a[6], a[7])));
    }
  };
  const uint4* const src = p.s->part + (((mt * 7 + jj) * 6 * 2 + wg) * 4) * 128 + tid;
  auto gload = [&](uint4 (&pv)[8], int c) {
#pragma unroll
    for (int i = 0; i < 8; i++) pv[i] = ld_relaxed(src + ((2 * c + (i >> 2)) * 8 + (i & 3)) * 128);
  };
  auto gsum = [&](uint4 (&pv)[8], int c) {
#pragma unroll 1
    for (uint32_t n = 0; n < SPIN_LIMIT; n++) {
      uint32_t bad = 0;
#pragma unroll
      for (int i = 0; i < 8; i++) bad |= pv[i].x ^ par;
      if (!__any_sync(0xffffffffu, bad & 1)) break;
      gload(pv, c);
    }
    TL(24 + c);
#pragma unroll
    for (int i = 0; i < 8; i++) {
      const float t[8] = {bf_lo(pv[i].x), bf_hi(pv[i].x), bf_lo(pv[i].y), bf_hi(pv[i].y), bf_lo(pv[i].z), bf_hi(pv[i].z), bf_lo(pv[i].w), bf_hi(pv[i].w)};
#pragma unroll
      for (int k = 0; k < 8; k++) accA[8 * (i & 3) + k] += t[k];
    }
  };
  uint4 pv0[8], pv1[8], pv2[8];
  const int row = 128 * mt + 64 * wg + r0;
  uint32_t gt0, gt1;
#pragma unroll
  for (int c2 = 0; c2 < 4; c2++) {
    const int qi = Q_G2 + 4 * c2;
    stage(accA, qi);
    retire(qi - 1);
    stage(accA, qi + 1);
    if (c2 == 3) TL(27);
    if (c2 > 0) put(accB, 2 * c2 - 1);
    TL(7 + c2);
    if (c2 == 3) break;
    retire(qi);
    stage(accB, qi + 2);
    retire(qi + 1);
    stage(accB, qi + 3);
    put(accA, 2 * c2);
    if (c2 == 2) { gload(pv0, 0); gt0 = ld_relaxed(&p.s->gate[row]); gt1 = ld_relaxed(&p.s->gate[row + 8]); }
    retire(qi + 2);
  }
#pragma unroll
  for (int kb = 0; kb < 7; kb++) {
    const int qt = Q_XR + (kb >> 1);
    if ((kb & 1) == 0) mbar_wait(BAR_FULL(sb, qt % NSTAGE), (qt / NSTAGE) & 1);
    mbar_wait(BAR_Y(sb, kb), 0);
    const uint64_t da = mk_desc(sb + y_addr(kb) + wg * 8192, 8192, 1024, 1);
    const uint64_t db = mk_desc(sb + SM_RING + (qt % NSTAGE) * STAGE_BYTES + (kb & 1) * 8192, 16, 1024, 1);
    wg_fence();
#pragma unroll
    for (int kk = 0; kk < 4; kk++) wgmma_ss_n64<1, 0>(accB, da + kk * 128, db + kk * 2, (kb | kk) != 0);
    wg_commit();
    if (kb == GL1) gload(pv1, 1);
    if (kb == 1) { wg_wait<2>(); fence_regs(accA); TL(15); }
    if (kb == GS0) gsum(pv0, 0);
    if (kb == GL2) gload(pv2, 2);
    if (kb == GS1) gsum(pv1, 1);
  }
  TL(11);
  for (uint32_t n = 0; (((gt0 ^ epoch) | (gt1 ^ epoch)) & 0xffffu) && n < SPIN_LIMIT; n++) {
    gt0 = ld_relaxed(&p.s->gate[row]); gt1 = ld_relaxed(&p.s->gate[row + 8]);
  }
  gsum(pv2, 2);
  const float ga0 = bf_hi(gt0), ga1 = bf_hi(gt1);
  TL(12);
  wg_wait<0>();
  fence_regs(accB);
  TL(13);
  const float gb0 = bf_round(1.f - ga0), gb1 = bf_round(1.f - ga1);
  const float gs0 = ga0 * (2.f / (float)(S_ * D_)), gs1 = ga1 * (2.f / (float)(S_ * D_));
  uint4* const o = reinterpret_cast<uint4*>(p.out + (size_t)row * D_ + 64 * jj + 8 * q);
#pragma unroll
  for (int h = 0; h < 2; h++) {
    const float gs = h ? gs1 : gs0, gb = h ? gb1 : gb0;
#pragma unroll
    for (int k = 0; k < 2; k++) {
      uint32_t w[4];
#pragma unroll
      for (int j = 0; j < 4; j++) {
        const int i = 16 * k + 4 * j + 2 * h;
        w[j] = pack2(fmaf(gs, accB[i], gb * accA[i]), fmaf(gs, accB[i + 1], gb * accA[i + 1]));
      }
      const bool o1 = q & 1, o2 = q & 2;
      uint32_t a = __shfl_xor_sync(0xffffffffu, o1 ? w[0] : w[1], 1), b = __shfl_xor_sync(0xffffffffu, o1 ? w[2] : w[3], 1);
      if (o1) { w[0] = a; w[2] = b; } else { w[1] = a; w[3] = b; }
      a = __shfl_xor_sync(0xffffffffu, o2 ? w[0] : w[2], 2); b = __shfl_xor_sync(0xffffffffu, o2 ? w[1] : w[3], 2);
      if (o2) { w[0] = a; w[1] = b; } else { w[2] = a; w[3] = b; }
      o[h * D_ + 4 * k] = make_uint4(w[0], w[1], w[2], w[3]);
    }
  }
  if (lane == 0) *my_epoch = epoch;
  TL(14);
}

__device__ __forceinline__ void ring_issue(uint32_t sb, const Params& p, int qi, uint32_t slot, bool wait, uint32_t phase, int jj, uint32_t rank) {
  const CUtensorMap* m;
  int c0, c1, c2 = 0;
  bool half = false, is3d = false;
  if (qi < Q_G2) {
    const int nc = __popc(CMASK & ((1u << qi) - 1));
    if ((CMASK >> qi) & 1) {
      m = &p.ct; c0 = 64 * jj; c1 = 128 * nc + 64 * rank; half = nc == 3;
    } else {
      const int pass = qi >= Q_G1B;
      m = rank ? &p.wu : &p.wg; c0 = 0; c1 = 32 * (qi - nc - 14 * pass); c2 = 4 * jj + 2 * pass; is3d = true;
    }
  } else if (qi < Q_P3) {
    int o = jj + 1 + ((qi - Q_G2) >> 1);
    if (o >= 7) o -= 7;
    m = &p.wd; c0 = 64 * o; c1 = 256 * jj + 128 * (qi & 1) + 64 * rank;
  } else {
    m = &p.ct; c0 = 128 * (qi - Q_P3) + 64 * rank; c1 = 64 * jj; half = qi == Q_END - 1;
  }
  uint32_t bar = BAR_FULL(sb, slot), dst = sb + SM_RING + slot * STAGE_BYTES + rank * 8192;
  if (qi >= Q_XR && qi < Q_P3) {
    bar = BAR_X(sb, qi - Q_XR); dst = sb + SM_X + (qi - Q_XR) * 16384 + rank * 8192;
    if (qi < Q_XR + 2) mbar_wait_cluster(BAR_XFREE(sb), 0);
  } else {
    if (wait) mbar_wait_cluster(BAR_EMPTY(sb, slot), phase ^ (qi >= Q_P3));
    mbar_expect_tx(bar, half ? 8192 : 16384);
  }
  if (is3d) tma3d_mc(dst, m, c0, c1, c2, bar);
  else if (!(half && rank)) tma2d_mc(dst, m, c0, c1, bar);
}

__device__ __forceinline__ void ffn_producer(uint32_t sb, const uint8_t* smem, int bid, const Params& p, int warp, int lane, int mt, int jj, uint32_t rank) {
  if (warp < 2) {
    if (lane == 0) {
      uint32_t slot = warp, phase = 0;
#pragma unroll 1
      for (int qi = NSTAGE + warp; qi < Q_END; qi += 2) {
        ring_issue(sb, p, qi, slot, true, phase, jj, rank);
        TL(10 + qi);
        slot += 2;
        if (slot >= NSTAGE) { slot -= NSTAGE; phase ^= 1; }
      }
    }
  } else {
    const int wg = warp - 2;
    uint32_t* const my_epoch = &p.s->epoch[blockIdx.x * 12 + 8 + warp];
    const uint32_t epoch = ld_relaxed(my_epoch) + 1;
    if (wg == 0) {
      if (lane == 0) { prefetch_tmap(&p.wd); prefetch_tmap(&p.yt); }
      {
        const uint4* gw4 = reinterpret_cast<const uint4*>(p.gate_w);
        const uint4 ga = __ldg(gw4 + lane), gb = lane < 24 ? __ldg(gw4 + 32 + lane) : make_uint4(0, 0, 0, 0);
        if (lane < 7) { mbar_wait(BAR_X(sb, lane), 0); mbar_expect_tx(BAR_X(sb, lane), 16384); mbar_expect_tx(BAR_Y(sb, lane), 16384); }
        __syncwarp();
        float mine = 0.f;
#pragma unroll 1
        for (int u = 0; u < 19; u++) {
          const int r = min(19 * jj + u, 127);
          const uint8_t* xr = smem + SM_X + (lane >> 3) * 16384 + r * 128 + (((lane ^ r) & 7) << 4);
          const uint4 xa = *reinterpret_cast<const uint4*>(xr);
          const uint4 xb = lane < 24 ? *reinterpret_cast<const uint4*>(xr + 65536) : make_uint4(0, 0, 0, 0);
          float s = 0.f;
          auto dot2 = [&](uint32_t a, uint32_t b) {
            const uint32_t pr = mul2(a, b);
            s += bf_lo(pr) + bf_hi(pr);
          };
          dot2(xa.x, ga.x); dot2(xa.y, ga.y); dot2(xa.z, ga.z); dot2(xa.w, ga.w);
          dot2(xb.x, gb.x); dot2(xb.y, gb.y); dot2(xb.z, gb.z); dot2(xb.w, gb.w);
#pragma unroll
          for (int o = 16; o > 0; o >>= 1) s += __shfl_xor_sync(0xffffffffu, s, o);
          if (lane == u) mine = s;
        }
        if (lane < 19 && 19 * jj + lane < 128)
          st_relaxed(&p.s->gate[128 * mt + 19 * jj + lane], pack2(0.f, 1.f / (1.f + __expf(-bf_round(mine)))) | (epoch & 0xffffu));
      }
      TL(9);
      if (lane < 2) mbar_arrive_cluster(BAR_XFREE(sb), lane);
    } else {
      mbar_wait(BAR_X(sb, PFAT), 0);
      if (lane < 6) {
        int row = 176 + 3 * bid + (lane >> 1);
        if (row >= D_) row -= D_;
        l2_prefetch(((lane & 1) ? p.pwu : p.pwg) + row * F_, F_ * 2);
      }
      TL(2);
      bar_sync(7, 160);
      if (lane == 0) { fence_gpu(); red_add(&p.s->cnt_x1[jj * 32], 1); l2_prefetch(p.pwd + bid * 16 * D_, 32 * D_); }
      TL(5);
    }
    mbar_wait(BAR_XFREE(sb), 0);
    TL(3);
    const int kb = 2 * lane + wg;
    bool todo = kb < 7;
    uint32_t n = 0;
    while (__any_sync(0xffffffffu, todo)) {
      if (todo) {
        uint32_t v, ok;
        asm volatile("ld.acquire.gpu.global.u32 %0, [%1];" : "=r"(v) : "l"(&p.s->cnt_y[kb * 32]) : "memory");
        asm volatile("{\n.reg .pred p;\nmbarrier.test_wait.parity.shared::cta.b64 p, [%1], 0;\nselp.u32 %0, 1, 0, p;\n}"
                     : "=r"(ok) : "r"(BAR_E2(sb, kb)) : "memory");
        if ((ok && (int32_t)(v - epoch * (kb ? 16 : 17)) >= 0) || ++n > SPIN_LIMIT) {
          tma3d(sb + y_addr(kb), &p.yt, 0, 64 * kb, 2 * mt, BAR_Y(sb, kb));
          todo = false;
        }
      }
    }
    TL(4);
    if (lane == 0) *my_epoch = epoch;
  }
}

__device__ __forceinline__ void spectral_cta(uint32_t sb, uint8_t* smem, const Params& p, int sc, int wg) {
  const int t384 = threadIdx.x, lane = t384 & 31, warp12 = t384 >> 5, tid = t384 & 127;
  const int warp = tid >> 5, q = lane & 3;
  const int sl0 = 6 * sc + min(sc, 8), nsl = sc < 8 ? 7 : 6;
  if (t384 == 320) {
#pragma unroll 1
    for (int i = 0; i < nsl; i++) {
      mbar_expect_tx(BAR_X(sb, i), 2 * SLAB_BYTES);
      const int row = 128 * ((sl0 + i) >> 3) + 8 * ((sl0 + i) & 7);
      const uint32_t dst = sb + SP_Z + 2 * i * SLAB_BYTES;
      bulk_g2s(dst, p.w_r + row * DF_, SLAB_BYTES / 2, BAR_X(sb, i));
      bulk_g2s(dst + SLAB_BYTES / 2, p.w_r + (row + 64) * DF_, SLAB_BYTES / 2, BAR_X(sb, i));
      bulk_g2s(dst + SLAB_BYTES, p.w_i + row * DF_, SLAB_BYTES / 2, BAR_X(sb, i));
      bulk_g2s(dst + 3 * SLAB_BYTES / 2, p.w_i + (row + 64) * DF_, SLAB_BYTES / 2, BAR_X(sb, i));
    }
    if (sc < 19) {
      mbar_expect_tx(BAR_Y(sb, 6), 24576);
      bulk_g2s(sb + SP_TW, p.spec, 24576, BAR_Y(sb, 6));
    }
  }
  uint32_t* const my_epoch = &p.s->epoch[blockIdx.x * 12 + warp12];
  const uint32_t epoch = ld_relaxed(my_epoch) + 1;
  uint32_t fe[16], tw[16];
#pragma unroll
  for (int i = 0; i < 4; i++) {
    const uint4 a = __ldg(reinterpret_cast<const uint4*>(p.spec->fe) + i * 128 + tid);
    const uint4 b = __ldg(reinterpret_cast<const uint4*>(p.spec->tw) + i * 128 + tid);
    fe[4 * i] = a.x; fe[4 * i + 1] = a.y; fe[4 * i + 2] = a.z; fe[4 * i + 3] = a.w;
    tw[4 * i] = b.x; tw[4 * i + 1] = b.y; tw[4 * i + 2] = b.z; tw[4 * i + 3] = b.w;
  }
  __syncwarp();
  asm volatile("barrier.cluster.wait.acquire.aligned;" ::: "memory");
#pragma unroll 2
  for (int un = wg; un < 8 * nsl; un += 3) {
    const int i = un >> 3, sl = sl0 + i, pr = 16 * (un & 7) + 4 * (lane >> 3) + warp, r = lane & 7;
    mbar_wait(BAR_X(sb, i), 0);
    if (pr < 113) {
      const uint16_t* w = reinterpret_cast<const uint16_t*>(smem + SP_Z + 2 * i * SLAB_BYTES) + r * DF_ + 2 * pr;
      const uint32_t m = pr < 112 ? 0xffffffffu : 0u;
      p.s->wt[pr * 1024 + sl * 8 + (r ^ ((sl >> 2) & 6))] =
          make_uint4(w[0] | ((uint32_t)w[8 * DF_] << 16), w[16 * DF_] | ((uint32_t)w[24 * DF_] << 16),
                     (w[1] | ((uint32_t)w[8 * DF_ + 1] << 16)) & m, (w[16 * DF_ + 1] | ((uint32_t)w[24 * DF_ + 1] << 16)) & m);
    }
  }
  __syncthreads();
  if (t384 == 352) { fence_gpu(); red_add(&p.s->cnt_w[0], 1); }
  TL(1);
  if (sc == 19) return;
  const int nrnd = (sc == 18 && wg == 2) ? 1 : 2;
  if (tid == 32) {
    wait_counter(&p.s->cnt_w[0], epoch * NSPEC);
    fence_async();
    for (int rnd = 0; rnd < nrnd; rnd++) {
      const int item = wg + 3 * rnd;
      mbar_expect_tx(BAR_Y(sb, item), 16384);
      bulk_g2s(sb + SP_W + item * 16384, p.s->wt + (6 * sc + item) * 1024, 16384, BAR_Y(sb, item));
    }
  } else if (tid == 0) {
#pragma unroll 1
    for (int rnd = 0; rnd < nrnd; rnd++) {
      const int item = wg + 3 * rnd, pr = 6 * sc + item;
      wait_counter(&p.s->cnt_x1[(pr < 112 ? pr >> 4 : 0) * 32], epoch * 16);
      fence_async();
      const uint32_t bar = BAR_FULL(sb, item), z = sb + SP_Z + item * 16384;
      mbar_expect_tx(bar, 16384);
      bulk_g2s(z, p.s->x1t + pr * 1024, 16384, bar);
    }
  }
  __syncwarp();
  fence_regs(fe); fence_regs(tw);
  mbar_wait(BAR_Y(sb, 6), 0);
  TL(3);
  const uint64_t dT_n = mk_desc(sb + SP_T, 8192, 1024, 1);
#pragma unroll 1
  for (int rnd = 0; rnd < nrnd; rnd++) {
    const int item = wg + 3 * rnd, pr = 6 * sc + item;
    const uint32_t z = sb + SP_Z + item * 16384;
    uint32_t fa[16], fb[16];
    auto load_frag = [&](int off) {
#pragma unroll
      for (int i = 0; i < 4; i++) {
        const uint4 a = *reinterpret_cast<const uint4*>(smem + SP_TW + off + i * 2048 + tid * 16);
        fa[4 * i] = a.x; fa[4 * i + 1] = a.y; fa[4 * i + 2] = a.z; fa[4 * i + 3] = a.w;
      }
      fence_regs(fa);
    };
    load_frag(0);
    mbar_wait(BAR_FULL(sb, item), 0);
    TL(4 + 8 * rnd);
    if (rnd == 0 && wg > 0) bar_sync(3 + wg, 256);
    float aR[32], aI[32];
    {
      const uint64_t de = mk_desc(z, 4096, 512, 2);
      wg_fence();
#pragma unroll
      for (int kk = 0; kk < 4; kk++) {
        wgmma_rs_n64<1, 1>(aR, fe[4 * kk], fe[4 * kk + 1], fe[4 * kk + 2], fe[4 * kk + 3], de + kk * 64, kk != 0);
        wgmma_rs_n64<1, 1>(aI, fa[4 * kk], fa[4 * kk + 1], fa[4 * kk + 2], fa[4 * kk + 3], de + 512 + kk * 64, kk != 0);
      }
      wg_commit();
      if (rnd == 0 && wg < 2) bar_arrive(4 + wg, 256);
      wg_wait<0>();
      fence_regs(aR); fence_regs(aI);
    }
    TL(5 + 8 * rnd);
#pragma unroll
    for (int v = 0; v < 8; v++) {
      uint32_t* f = (v < 4 ? fa : fb) + 2 * (v & 3);
      const uint32_t* t = tw + 2 * (v & 3);
      const float *e = aR + 4 * v, *o = aI + 4 * v;
      const uint32_t er = pack2(e[0], e[1]), ei = pack2(e[2], e[3]), qr = pack2(o[0], o[1]), qi = pack2(o[2], o[3]);
      const uint32_t u0r = add2(er, qr), u0i = add2(ei, qi), u1r = sub2(er, qr), u1i = sub2(ei, qi);
      f[0] = fma2(u0r, t[0], mul2(u0i, t[8]));
      f[8] = fms2(u0i, t[0], mul2(u0r, t[8]));
      f[1] = fma2(u1r, t[1], mul2(u1i, t[9]));
      f[9] = fms2(u1i, t[1], mul2(u1r, t[9]));
    }
    fence_regs(fa); fence_regs(fb);
    wg_fence();
#pragma unroll
    for (int kk = 0; kk < 4; kk++) {
      wgmma_rs_n64<1, 1>(aR, fa[4 * kk], fa[4 * kk + 1], fa[4 * kk + 2], fa[4 * kk + 3], dT_n + kk * 128, kk != 0);
      wgmma_rs_n64<1, 1>(aI, fb[4 * kk], fb[4 * kk + 1], fb[4 * kk + 2], fb[4 * kk + 3], dT_n + kk * 128, kk != 0);
    }
    wg_commit();
    mbar_wait(BAR_Y(sb, item), 0);
    wg_wait<0>();
    fence_regs(aR); fence_regs(aI);
    TL(6 + 8 * rnd);
    {
      const uint8_t* wp = smem + SP_W + item * 16384 + q * 1024 + warp * 128 + (((lane >> 2) ^ (2 * q)) << 4);
#pragma unroll
      for (int jb = 0; jb < 4; jb++) {
#pragma unroll
        for (int h = 0; h < 2; h++) {
          const uint4 w = *reinterpret_cast<const uint4*>(wp + jb * 4096 + h * 512);
          const int i = 4 * jb + 2 * h;
          const uint32_t ar = pack2(aR[i], aR[i + 1]), ai = pack2(aR[16 + i], aR[17 + i]);
          const uint32_t br = pack2(aI[i], aI[i + 1]), bi = pack2(aI[16 + i], aI[17 + i]);
          fa[2 * jb + h] = fms2(ar, w.x, mul2(ai, w.y));
          fa[8 + 2 * jb + h] = fma2(ar, w.y, mul2(ai, w.x));
          fb[2 * jb + h] = fms2(br, w.z, mul2(bi, w.w));
          fb[8 + 2 * jb + h] = fma2(br, w.w, mul2(bi, w.z));
        }
      }
    }
    fence_regs(fa); fence_regs(fb);
    wg_fence();
#pragma unroll
    for (int kk = 0; kk < 4; kk++) {
      wgmma_rs_n64<1, 0>(aR, fa[4 * kk], fa[4 * kk + 1], fa[4 * kk + 2], fa[4 * kk + 3], dT_n + kk * 2, kk != 0);
      wgmma_rs_n64<1, 0>(aI, fb[4 * kk], fb[4 * kk + 1], fb[4 * kk + 2], fb[4 * kk + 3], dT_n + kk * 2, kk != 0);
    }
    wg_commit();
    wg_wait<0>();
    fence_regs(aR); fence_regs(aI);
    TL(7 + 8 * rnd);
#pragma unroll
    for (int v = 0; v < 8; v++) {
      const float* a = (v < 4 ? aR : aI) + 4 * (v & 3);
      const uint32_t* t = tw + 2 * (v & 3);
      const uint32_t u0r = pack2(a[0], a[1]), u1r = pack2(a[2], a[3]), u0i = pack2(a[16], a[17]), u1i = pack2(a[18], a[19]);
      const uint32_t t0r = fms2(u0r, t[0], mul2(u0i, t[8])), t0i = fma2(u0i, t[0], mul2(u0r, t[8]));
      const uint32_t t1r = fms2(u1r, t[1], mul2(u1i, t[9])), t1i = fma2(u1i, t[1], mul2(u1r, t[9]));
      fa[v] = add2(t0i, t1i); fa[8 + v] = add2(t0r, t1r);
      fb[v] = sub2(t0i, t1i); fb[8 + v] = sub2(t0r, t1r);
    }
    bar_sync(1 + wg, 128);
#pragma unroll
    for (int u = 0; u < 4; u++) {
      const uint32_t a = z + (32 * (u >> 1) + 8 * warp + (lane & 7)) * 128 + (((4 * (u & 1) + (lane >> 3)) ^ (lane & 7)) << 4);
      stmatrix_x4(a, fa[4 * u], fa[4 * u + 1], fa[4 * u + 2], fa[4 * u + 3]);
      stmatrix_x4(a + 8192, fb[4 * u], fb[4 * u + 1], fb[4 * u + 2], fb[4 * u + 3]);
    }
    load_frag(8192);
    fence_async_smem();
    bar_sync(1 + wg, 128);
    TL(8 + 8 * rnd);
    {
      const uint64_t de = mk_desc(z, 8192, 1024, 1);
      wg_fence();
#pragma unroll
      for (int kk = 0; kk < 4; kk++) {
        wgmma_rs_n64<1, 1>(aR, fe[4 * kk], fe[4 * kk + 1], fe[4 * kk + 2], fe[4 * kk + 3], de + kk * 128, kk != 0);
        wgmma_rs_n64<1, 1>(aI, fa[4 * kk], fa[4 * kk + 1], fa[4 * kk + 2], fa[4 * kk + 3], de + 512 + kk * 128, kk != 0);
      }
      wg_commit();
      wg_wait<0>();
      fence_regs(aR); fence_regs(aI);
    }
    TL(9 + 8 * rnd);
    const bool edge = pr == 0 || pr == 112;
    if (edge) {
#pragma unroll
      for (int i = 0; i < 16; i++) { aR[i] *= 0.5f; aI[i] *= 0.5f; }
    }
#pragma unroll
    for (int i = 0; i < 8; i++) {
      const float* a = ((i & 1) ? aI : aR) + 16 * (i >> 2) + 2 - (i & 2);
      *reinterpret_cast<uint4*>(smem + SP_W + item * 16384 + (i >> 1) * 4096 + (i & 1) * 64 + (tid >> 2) * 128 + q * 16) =
          make_uint4(pack2(a[0], a[1]), pack2(a[4], a[5]), pack2(a[8], a[9]), pack2(a[12], a[13]));
    }
    fence_async_smem();
    bar_sync(1 + wg, 128);
    if (tid == 0) {
      const uint32_t src = sb + SP_W + item * 16384;
      __nv_bfloat16* dst = p.s->yt + (size_t)(pr < 112 ? 4 * pr : 1) * S_;
      bulk_s2g(dst, src, edge ? 4096 : 16384);
      if (pr == 0) bulk_s2g(dst + 2 * S_, src + 8192, 8192);
      asm volatile("cp.async.bulk.commit_group;" ::: "memory");
      if (rnd == nrnd - 1) {
        asm volatile("cp.async.bulk.wait_group 0;" ::: "memory");
        TL(11);
        red_add(&p.s->cnt_y[(pr < 112 ? pr >> 4 : 0) * 32], 1);
        if (rnd) red_add(&p.s->cnt_y[((pr - 3) >> 4) * 32], 1);
      }
    }
    __syncwarp();
    TL(10 + 8 * rnd);
  }
  if (lane == 0) *my_epoch = epoch;
}

__global__ void __cluster_dims__(2, 1, 1) __launch_bounds__(384, 1)
fused_kernel(const __grid_constant__ Params p) {
  extern __shared__ __align__(1024) uint8_t smem[];
  const uint32_t sb = smem_u32(smem);
  TL(0);
  const uint32_t rank = blockIdx.x & 1;
  const int hc = blockIdx.x >> 1;
  int grp, jj;
  if (hc < 4) { grp = 8; jj = hc; }
  else if (hc < 36) { grp = (hc - 4) & 7; jj = (hc - 4) >> 3; }
  else if (hc < 57) { jj = (hc - 36) / 7; grp = 1 + (hc - 36) - 7 * jj; jj += 4; }
  else if (hc < 60) { grp = 0; jj = hc - 53; }
  else { grp = 8; jj = hc - 56; }
  const int mt = 2 * grp + rank, bid = 2 * (7 * grp + jj) + rank;
  if (threadIdx.x == 256) {
#pragma unroll
    for (int i = 0; i < NSTAGE; i++) { mbar_init(BAR_FULL(sb, i), 1); mbar_init(BAR_EMPTY(sb, i), 4); }
    asm volatile("fence.mbarrier_init.release.cluster;" ::: "memory");
  } else if (threadIdx.x == 320) {
#pragma unroll
    for (int i = 0; i < NSTAGE; i++) { mbar_init(BAR_X(sb, i), 1); mbar_init(BAR_Y(sb, i), 1); }
    mbar_init(BAR_XFREE(sb), 6);
#pragma unroll
    for (int i = 0; i < 7; i++) mbar_init(BAR_E2(sb, i), 2);
    asm volatile("fence.mbarrier_init.release.cluster;" ::: "memory");
  } else if (threadIdx.x == 288) {
    prefetch_tmap(rank ? &p.wu : &p.wg); prefetch_tmap(&p.ct);
  }
  __syncwarp();
  asm volatile("barrier.cluster.arrive.relaxed.aligned;" ::: "memory");
  const int wg = __shfl_sync(0xffffffffu, threadIdx.x >> 7, 0);
  if (bid >= NFFN) {
    spectral_cta(sb, smem, p, bid - NFFN, wg);
  } else if (wg < 2) {
    asm volatile("setmaxnreg.inc.sync.aligned.u32 232;");
    asm volatile("barrier.cluster.wait.acquire.aligned;" ::: "memory");
    TL(1);
    ffn_consumer(sb, smem, p, bid, wg, threadIdx.x & 127, mt, jj);
  } else {
    asm volatile("setmaxnreg.dec.sync.aligned.u32 40;");
    if (threadIdx.x == 320) {
      mbar_expect_tx(BAR_X(sb, 0), 16384);
      tma2d(sb + SM_X, &p.x, 0, 128 * mt, BAR_X(sb, 0));
    }
    __syncwarp();
    asm volatile("barrier.cluster.wait.acquire.aligned;" ::: "memory");
    TL(1);
    if (threadIdx.x == 320) {
      constexpr int order[13] = {XORDER};
#pragma unroll
      for (int i = 0; i < 13; i++) {
        if (order[i] < 8) {
          ring_issue(sb, p, order[i], order[i], false, 0, jj, rank);
        } else {
          const int kb = order[i] - 10;
          mbar_expect_tx(BAR_X(sb, kb), 16384);
          tma2d(sb + SM_X + kb * 16384, &p.x, 64 * kb, 128 * mt, BAR_X(sb, kb));
        }
      }
      TL(2);
    } else if (threadIdx.x == 352) {
    }
    __syncwarp();
    ffn_producer(sb, smem, bid, p, (threadIdx.x >> 5) & 3, threadIdx.x & 31, mt, jj, rank);
  }
}

typedef CUresult (*EncodeFn)(CUtensorMap*, CUtensorMapDataType, cuuint32_t, void*, const cuuint64_t*, const cuuint64_t*,
                             const cuuint32_t*, const cuuint32_t*, CUtensorMapInterleave, CUtensorMapSwizzle,
                             CUtensorMapL2promotion, CUtensorMapFloatOOBfill);

void make_map(EncodeFn fn, CUtensorMap* m, const void* base, int rank, const cuuint64_t* dims, const cuuint64_t* strides,
              const cuuint32_t* box, CUtensorMapSwizzle sw) {
  const cuuint32_t es[4] = {1, 1, 1, 1};
  fn(m, CU_TENSOR_MAP_DATA_TYPE_BFLOAT16, rank, const_cast<void*>(base), dims, strides, box, es,
     CU_TENSOR_MAP_INTERLEAVE_NONE, sw, CU_TENSOR_MAP_L2_PROMOTION_L2_256B, CU_TENSOR_MAP_FLOAT_OOB_FILL_NONE);
}

}

extern "C" void kernel_launch(void* const* d_in, const int* in_sizes, int n_in, void* d_out, int out_size) {
  const __nv_bfloat16* x = (const __nv_bfloat16*)d_in[0];
  const __nv_bfloat16* w_r = (const __nv_bfloat16*)d_in[1];
  const __nv_bfloat16* w_i = (const __nv_bfloat16*)d_in[2];
  const __nv_bfloat16* wg = (const __nv_bfloat16*)d_in[4];
  const __nv_bfloat16* wu = (const __nv_bfloat16*)d_in[5];
  const __nv_bfloat16* wd = (const __nv_bfloat16*)d_in[6];
  const __nv_bfloat16* gate_w = (const __nv_bfloat16*)d_in[7];

  void* fnp = nullptr;
  cudaDriverEntryPointQueryResult qr;
  cudaGetDriverEntryPoint("cuTensorMapEncodeTiled", &fnp, cudaEnableDefault, &qr);
  EncodeFn fn = (EncodeFn)fnp;
  void *ctab, *spec, *scr;
  cudaGetSymbolAddress(&ctab, g_ctab);
  cudaGetSymbolAddress(&spec, g_spec);
  cudaGetSymbolAddress(&scr, g_scratch);
  const void* yt = (const char*)scr + offsetof(Scratch, yt);
  Params p;
  p.s = (Scratch*)scr; p.out = (__nv_bfloat16*)d_out;
  p.px = x; p.w_r = w_r; p.w_i = w_i; p.gate_w = gate_w; p.pwg = wg; p.pwu = wu; p.pwd = wd;
  p.ctab = (const tab::Table*)ctab; p.spec = (const tab::Spec*)spec;
  {
    const cuuint64_t d[2] = {D_, S_}, s[1] = {D_ * 2};
    const cuuint32_t b[2] = {64, 128};
    make_map(fn, &p.x, x, 2, d, s, b, CU_TENSOR_MAP_SWIZZLE_128B);
  }
  {
    const cuuint64_t d[3] = {64, D_, F_ / 64}, s[2] = {F_ * 2, 128};
    const cuuint32_t b[3] = {64, 32, 2};
    make_map(fn, &p.wg, wg, 3, d, s, b, CU_TENSOR_MAP_SWIZZLE_128B);
    make_map(fn, &p.wu, wu, 3, d, s, b, CU_TENSOR_MAP_SWIZZLE_128B);
  }
  {
    const cuuint64_t d[2] = {D_, F_}, s[1] = {D_ * 2};
    const cuuint32_t b[2] = {64, 64};
    make_map(fn, &p.wd, wd, 2, d, s, b, CU_TENSOR_MAP_SWIZZLE_128B);
  }
  {
    const cuuint64_t d[2] = {D_, D_}, s[1] = {D_ * 2};
    const cuuint32_t b[2] = {64, 64};
    make_map(fn, &p.ct, ctab, 2, d, s, b, CU_TENSOR_MAP_SWIZZLE_128B);
  }
  {
    const cuuint64_t d[3] = {64, D_, S_ / 64}, s[2] = {S_ * 2, 128};
    const cuuint32_t b[3] = {64, 64, 2};
    make_map(fn, &p.yt, yt, 3, d, s, b, CU_TENSOR_MAP_SWIZZLE_128B);
  }
  cudaFuncSetAttribute(fused_kernel, cudaFuncAttributeMaxDynamicSharedMemorySize, SM_TOTAL);
  fused_kernel<<<NCTA, 384, SM_TOTAL, cudaStreamPerThread>>>(p, x, w_r, w_i, gate_w, wd, (__nv_bfloat16*)d_out);
}
```

```cpp
#include <cuda_runtime.h>
#include <cuda_bf16.h>
#include <cuda.h>
#include <stdint.h>
#include <stddef.h>

namespace {

constexpr int S_ = 2048, D_ = 448, F_ = 1792, DF_ = 225;
constexpr int NFFN = 112, NSPEC = 20, NCTA = NFFN + NSPEC;
constexpr int NSTAGE = 7, STAGE_BYTES = 16384;
constexpr int SM_X = 0, SM_RING = 114688, SM_BAR = 229376, SM_TOTAL = SM_BAR + 512;
constexpr int SP_Z = 0, SP_W = 98304, SP_TW = 198656, SP_T = 215040, SLAB_BYTES = 16 * DF_ * 2;
constexpr uint32_t SPIN_LIMIT = 1u << 20;

namespace tab {
constexpr double PI = 3.14159265358979323846264338327950288;
constexpr double csin(double x) {
  double t = x, s = x;
  for (int i = 1; i < 20; i++) { t = -t * x * x / ((2 * i) * (2 * i + 1)); s += t; }
  return s;
}
constexpr double ccos(double x) {
  double t = 1, s = 1;
  for (int i = 1; i < 20; i++) { t = -t * x * x / ((2 * i - 1) * (2 * i)); s += t; }
  return s;
}
constexpr uint32_t to_bf16(double v) {
  uint32_t sign = v < 0 ? 0x8000u : 0u;
  double a = v < 0 ? -v : v;
  if (a < 1e-12) return 0;
  int e = 0;
  while (a >= 2.0) { a /= 2; e++; }
  while (a < 1.0) { a *= 2; e--; }
  double m = a * 128.0;
  int mi = (int)m;
  double fr = m - mi;
  if (fr > 0.5 || (fr == 0.5 && (mi & 1))) mi++;
  if (mi == 256) { mi = 128; e++; }
  return sign | (uint32_t)((e + 127) << 7) | (uint32_t)(mi - 128);
}
struct Base { uint32_t v[448]; };
constexpr Base make_base() {
  Base b{};
  for (int m = 0; m < 448; m++) {
    int mm = m > 224 ? m - 448 : m;
    double ang = 2 * PI * mm / 448.0;
    b.v[m] = to_bf16(ccos(ang)) | (to_bf16(-csin(ang)) << 16);
  }
  return b;
}
constexpr Base base = make_base();
struct Row { uint32_t v[224]; };
constexpr Row make_row(int d) {
  Row r{};
  r.v[0] = 0x3f80u | ((d & 1) ? 0xbf800000u : 0x3f800000u);
  int m = 0;
  for (int c = 1; c < 224; c++) { m += d; if (m >= 448) m -= 448; r.v[c] = base.v[m]; }
  return r;
}
struct Table { Row r[448]; };
constexpr Table make_table() {
  Table t{};
  for (int d = 0; d < 448; d++) t.r[d] = make_row(d);
  return t;
}
struct Cs { double c[2048], s[2048]; };
constexpr Cs make_cs() {
  Cs t{};
  for (int m = 0; m <= 256; m++) {
    const double a = 2 * PI * m / 2048.0, c = ccos(a), s = csin(a);
    t.c[m] = c; t.s[m] = s;
    t.c[512 - m] = s; t.s[512 - m] = c;
  }
  for (int m = 513; m < 2048; m++) { t.c[m] = -t.s[m - 512]; t.s[m] = t.c[m - 512]; }
  return t;
}
constexpr Cs cs = make_cs();
struct Spec {
  uint32_t fo[2048], fot[2048];
  uint16_t t32[4096];
  uint32_t fe[2048];
  uint32_t tw[2048];
};
constexpr uint32_t blk(int h, int c, int a) { return to_bf16(h == c ? cs.c[a & 2047] : (h ? -cs.s[a & 2047] : cs.s[a & 2047])); }
constexpr Spec make_spec() {
  Spec t{};
  for (int row = 0; row < 64; row++)
    for (int col = 0; col < 64; col++) {
      const int c = row & 31, k2 = col & 31, n2 = 8 * ((c >> 1) & 3) + 2 * (c >> 3) + (c & 1), m = 64 * ((n2 * k2) & 31);
      const double v = (row >> 5) == (col >> 5) ? cs.c[m] : (row < 32 ? -cs.s[m] : cs.s[m]);
      t.t32[row * 64 + (((col >> 3) ^ (row & 7)) << 3) + (col & 7)] = (uint16_t)to_bf16(v);
    }
  for (int th = 0; th < 128; th++)
    for (int i = 0; i < 16; i++) {
      const int r = 8 * (th >> 5) + ((th & 31) >> 2), h = i & 1, c = i >> 3, m = 8 * ((i >> 1) & 3) + 2 * (th & 3);
      const int o = ((i >> 2) * 128 + th) * 4 + (i & 3);
      t.fe[o] = blk(h, c, 64 * m * r) | (blk(h, c, 64 * (m + 1) * r) << 16);
      t.fo[o] = blk(h, c, 32 * (2 * m + 1) * r) | (blk(h, c, 32 * (2 * m + 3) * r) << 16);
      t.fot[o] = blk(h, c, 32 * (2 * r + 1) * m) | (blk(h, c, 32 * (2 * r + 1) * (m + 1)) << 16);
      const int k1 = r + 32 * h, n2 = 8 * (th & 3) + 2 * ((i >> 1) & 3);
      t.tw[o] = blk(0, c, n2 * k1) | (blk(0, c, (n2 + 1) * k1) << 16);
    }
  return t;
}
}
}

__device__ __align__(1024) const tab::Table g_ctab = tab::make_table();
__device__ __align__(1024) const tab::Spec g_spec = tab::make_spec();

struct Scratch {
  uint32_t cnt_w[32];
  uint32_t cnt_x1[7 * 32];
  uint32_t cnt_y[7 * 32];
  uint32_t epoch[NCTA * 12 + 240 + 256];
  uint32_t gate[S_];
  uint4 x1t[113 * 1024];
  __nv_bfloat16 yt[D_ * S_];
  uint4 wt[114 * 1024];
  uint4 part[16 * 7 * 6 * 2 * 4 * 128];
};
static_assert(offsetof(Scratch, x1t) % 1024 == 0, "alignment");
__device__ __align__(1024) Scratch g_scratch;
#define TL(i)

namespace {

struct Params {
  Scratch* s;
  __nv_bfloat16* out;
  const __nv_bfloat16 *px, *w_r, *w_i, *gate_w, *pwg, *pwu, *pwd;
  const tab::Table* ctab;
  const tab::Spec* spec;
  CUtensorMap x, wg, wu, wd, ct, yt;
};

__device__ __forceinline__ uint32_t smem_u32(const void* p) { return (uint32_t)__cvta_generic_to_shared(p); }
__device__ __forceinline__ void mbar_init(uint32_t bar, uint32_t cnt) {
  asm volatile("mbarrier.init.shared::cta.b64 [%0], %1;" ::"r"(bar), "r"(cnt) : "memory");
}
__device__ __forceinline__ void mbar_expect_tx(uint32_t bar, uint32_t bytes) {
  asm volatile("mbarrier.arrive.expect_tx.shared::cta.b64 _, [%0], %1;" ::"r"(bar), "r"(bytes) : "memory");
}
__device__ __forceinline__ void mbar_arrive(uint32_t bar) {
  asm volatile("mbarrier.arrive.shared::cta.b64 _, [%0];" ::"r"(bar) : "memory");
}
__device__ __forceinline__ void mbar_arrive_cluster(uint32_t bar, uint32_t cta) {
  asm volatile("{\n.reg .b32 ra;\nmapa.shared::cluster.u32 ra, %0, %1;\n"
               "mbarrier.arrive.shared::cluster.b64 _, [ra];\n}" ::"r"(bar), "r"(cta) : "memory");
}
__device__ __forceinline__ void mbar_wait(uint32_t bar, uint32_t parity) {
  uint32_t ok, n = 0;
  do {
    asm volatile("{\n.reg .pred p;\nmbarrier.try_wait.parity.shared::cta.b64 p, [%1], %2;\nselp.u32 %0, 1, 0, p;\n}"
                 : "=r"(ok) : "r"(bar), "r"(parity) : "memory");
  } while (!ok && ++n < SPIN_LIMIT);
}
__device__ __forceinline__ void mbar_wait_cluster(uint32_t bar, uint32_t parity) {
  uint32_t ok, n = 0;
  do {
    asm volatile("{\n.reg .pred p;\nmbarrier.try_wait.parity.acquire.cluster.shared::cta.b64 p, [%1], %2;\nselp.u32 %0, 1, 0, p;\n}"
                 : "=r"(ok) : "r"(bar), "r"(parity) : "memory");
  } while (!ok && ++n < SPIN_LIMIT);
}
__device__ __forceinline__ void tma2d(uint32_t dst, const CUtensorMap* m, int c0, int c1, uint32_t bar) {
  asm volatile("cp.async.bulk.tensor.2d.shared::cluster.global.mbarrier::complete_tx::bytes [%0], [%1, {%3, %4}], [%2];"
               ::"r"(dst), "l"(m), "r"(bar), "r"(c0), "r"(c1) : "memory");
}
__device__ __forceinline__ void tma3d(uint32_t dst, const CUtensorMap* m, int c0, int c1, int c2, uint32_t bar) {
  asm volatile("cp.async.bulk.tensor.3d.shared::cluster.global.mbarrier::complete_tx::bytes [%0], [%1, {%3, %4, %5}], [%2];"
               ::"r"(dst), "l"(m), "r"(bar), "r"(c0), "r"(c1), "r"(c2) : "memory");
}
__device__ __forceinline__ void tma2d_mc(uint32_t dst, const CUtensorMap* m, int c0, int c1, uint32_t bar) {
  asm volatile("cp.async.bulk.tensor.2d.shared::cluster.global.mbarrier::complete_tx::bytes.multicast::cluster [%0], [%1, {%3, %4}], [%2], %5;"
               ::"r"(dst), "l"(m), "r"(bar), "r"(c0), "r"(c1), "h"((uint16_t)3) : "memory");
}
__device__ __forceinline__ void tma3d_mc(uint32_t dst, const CUtensorMap* m, int c0, int c1, int c2, uint32_t bar) {
  asm volatile("cp.async.bulk.tensor.3d.shared::cluster.global.mbarrier::complete_tx::bytes.multicast::cluster [%0], [%1, {%3, %4, %5}], [%2], %6;"
               ::"r"(dst), "l"(m), "r"(bar), "r"(c0), "r"(c1), "r"(c2), "h"((uint16_t)3) : "memory");
}
__device__ __forceinline__ void bulk_g2s(uint32_t dst, const void* src, uint32_t bytes, uint32_t bar) {
  asm volatile("cp.async.bulk.shared::cluster.global.mbarrier::complete_tx::bytes [%0], [%1], %2, [%3];"
               ::"r"(dst), "l"(src), "r"(bytes), "r"(bar) : "memory");
}
__device__ __forceinline__ void bulk_s2g(void* dst, uint32_t src, uint32_t bytes) {
  asm volatile("cp.async.bulk.global.shared::cta.bulk_group [%0], [%1], %2;" ::"l"(dst), "r"(src), "r"(bytes) : "memory");
}
__device__ __forceinline__ void prefetch_tmap(const CUtensorMap* m) {
  asm volatile("prefetch.tensormap [%0];" ::"l"(m) : "memory");
}
__device__ __forceinline__ void l2_prefetch(const void* p, uint32_t bytes) {
  asm volatile("cp.async.bulk.prefetch.L2.global [%0], %1;" ::"l"(p), "r"(bytes) : "memory");
}
__device__ __forceinline__ void wg_fence() { asm volatile("wgmma.fence.sync.aligned;" ::: "memory"); }
__device__ __forceinline__ void wg_commit() { asm volatile("wgmma.commit_group.sync.aligned;" ::: "memory"); }
template <int N> __device__ __forceinline__ void wg_wait() { asm volatile("wgmma.wait_group.sync.aligned %0;" ::"n"(N) : "memory"); }
template <int N> __device__ __forceinline__ void fence_regs(float (&d)[N]) {
#pragma unroll
  for (int i = 0; i < N; i++) asm volatile("" : "+f"(d[i])::"memory");
}
template <int N> __device__ __forceinline__ void fence_regs(uint32_t (&d)[N]) {
#pragma unroll
  for (int i = 0; i < N; i++) asm volatile("" : "+r"(d[i])::"memory");
}
__device__ __forceinline__ void bar_sync(int id, int n) { asm volatile("bar.sync %0, %1;" ::"r"(id), "r"(n) : "memory"); }
__device__ __forceinline__ void bar_arrive(int id, int n) { asm volatile("bar.arrive %0, %1;" ::"r"(id), "r"(n) : "memory"); }
__device__ __forceinline__ void fence_gpu() { asm volatile("fence.acq_rel.gpu;" ::: "memory"); }
__device__ __forceinline__ void fence_async() { asm volatile("fence.proxy.async;" ::: "memory"); }
__device__ __forceinline__ void fence_async_smem() { asm volatile("fence.proxy.async.shared::cta;" ::: "memory"); }
__device__ __forceinline__ void red_add(uint32_t* p, uint32_t v) {
  asm volatile("red.relaxed.gpu.global.add.u32 [%0], %1;" ::"l"(p), "r"(v) : "memory");
}
__device__ __forceinline__ uint32_t ld_relaxed(const uint32_t* p) {
  uint32_t v;
  asm volatile("ld.relaxed.gpu.global.u32 %0, [%1];" : "=r"(v) : "l"(p) : "memory");
  return v;
}
__device__ __forceinline__ void wait_counter(const uint32_t* p, uint32_t target) {
  uint32_t v, n = 0;
  while (true) {
    asm volatile("ld.acquire.gpu.global.u32 %0, [%1];" : "=r"(v) : "l"(p) : "memory");
    if ((int32_t)(v - target) >= 0 || ++n > SPIN_LIMIT) break;
  }
}
__device__ __forceinline__ uint4 ld_relaxed(const uint4* p) {
  uint4 v;
  asm volatile("ld.relaxed.gpu.global.v4.u32 {%0, %1, %2, %3}, [%4];" : "=r"(v.x), "=r"(v.y), "=r"(v.z), "=r"(v.w) : "l"(p) : "memory");
  return v;
}
__device__ __forceinline__ void st_relaxed(uint4* p, uint4 v) {
  asm volatile("st.relaxed.gpu.global.v4.u32 [%0], {%1, %2, %3, %4};" ::"l"(p), "r"(v.x), "r"(v.y), "r"(v.z), "r"(v.w) : "memory");
}
__device__ __forceinline__ void st_relaxed(uint32_t* p, uint32_t v) {
  asm volatile("st.relaxed.gpu.global.u32 [%0], %1;" ::"l"(p), "r"(v) : "memory");
}
__device__ __forceinline__ uint32_t pack2(float lo, float hi) {
  uint32_t r;
  asm("cvt.rn.bf16x2.f32 %0, %1, %2;" : "=r"(r) : "f"(hi), "f"(lo));
  return r;
}
__device__ __forceinline__ uint32_t mul2(uint32_t a, uint32_t b) {
  uint32_t r;
  asm("mul.rn.bf16x2 %0, %1, %2;" : "=r"(r) : "r"(a), "r"(b));
  return r;
}
__device__ __forceinline__ uint32_t fma2(uint32_t a, uint32_t b, uint32_t c) {
  uint32_t r;
  asm("fma.rn.bf16x2 %0, %1, %2, %3;" : "=r"(r) : "r"(a), "r"(b), "r"(c));
  return r;
}
__device__ __forceinline__ uint32_t add2(uint32_t a, uint32_t b) {
  uint32_t r;
  asm("add.rn.bf16x2 %0, %1, %2;" : "=r"(r) : "r"(a), "r"(b));
  return r;
}
__device__ __forceinline__ uint32_t sub2(uint32_t a, uint32_t b) {
  uint32_t r;
  asm("sub.rn.bf16x2 %0, %1, %2;" : "=r"(r) : "r"(a), "r"(b));
  return r;
}
__device__ __forceinline__ uint32_t fms2(uint32_t a, uint32_t b, uint32_t c) {
  uint32_t r;
  asm("{\n.reg .b32 n;\nneg.bf16x2 n, %3;\nfma.rn.bf16x2 %0, %1, %2, n;\n}" : "=r"(r) : "r"(a), "r"(b), "r"(c));
  return r;
}
__device__ __forceinline__ float bf_lo(uint32_t v) { return __uint_as_float(v << 16); }
__device__ __forceinline__ float bf_hi(uint32_t v) { return __uint_as_float(v & 0xffff0000u); }
__device__ __forceinline__ float bf_round(float v) { return bf_lo(pack2(v, 0.f)); }
__device__ __forceinline__ float tanh_fast(float v) {
  float r;
  asm("tanh.approx.f32 %0, %1;" : "=f"(r) : "f"(v));
  return r;
}
__device__ __forceinline__ uint64_t mk_desc(uint32_t addr, uint32_t lbo, uint32_t sbo, uint32_t mode) {
  return (uint64_t)((addr & 0x3FFFF) >> 4) | ((uint64_t)(lbo >> 4) << 16) | ((uint64_t)(sbo >> 4) << 32) | ((uint64_t)mode << 62);
}
__device__ __forceinline__ void stmatrix_x4(uint32_t addr, uint32_t r0, uint32_t r1, uint32_t r2, uint32_t r3) {
  asm volatile("stmatrix.sync.aligned.m8n8.x4.shared.b16 [%0], {%1, %2, %3, %4};" ::"r"(addr), "r"(r0), "r"(r1), "r"(r2), "r"(r3) : "memory");
}

template <int TA, int TB>
__device__ __forceinline__ void wgmma_ss_n256(float (&d)[128], uint64_t da, uint64_t db, int sd) {
  asm volatile("{\n.reg .pred p;\nsetp.ne.b32 p, %130, 0;\n"
      "wgmma.mma_async.sync.aligned.m64n256k16.f32.bf16.bf16 {"
      "%0, %1, %2, %3, %4, %5, %6, %7, %8, %9, %10, %11, %12, %13, %14, %15, %16, %17, %18, %19, %20, %21, %22, %23, "
      "%24, %25, %26, %27, %28, %29, %30, %31, %32, %33, %34, %35, %36, %37, %38, %39, %40, %41, %42, %43, %44, %45, "
      "%46, %47, %48, %49, %50, %51, %52, %53, %54, %55, %56, %57, %58, %59, %60, %61, %62, %63, %64, %65, %66, %67, "
      "%68, %69, %70, %71, %72, %73, %74, %75, %76, %77, %78, %79, %80, %81, %82, %83, %84, %85, %86, %87, %88, %89, "
      "%90, %91, %92, %93, %94, %95, %96, %97, %98, %99, %100, %101, %102, %103, %104, %105, %106, %107, %108, %109, "
      "%110, %111, %112, %113, %114, %115, %116, %117, %118, %119, %120, %121, %122, %123, %124, %125, %126, %127"
      "}, %128, %129, p, 1, 1, %131, %132;\n}\n"
      : "+f"(d[0]), "+f"(d[1]), "+f"(d[2]), "+f"(d[3]), "+f"(d[4]), "+f"(d[5]), "+f"(d[6]), "+f"(d[7]), "+f"(d[8]),
        "+f"(d[9]), "+f"(d[10]), "+f"(d[11]), "+f"(d[12]), "+f"(d[13]), "+f"(d[14]), "+f"(d[15]), "+f"(d[16]),
        "+f"(d[17]), "+f"(d[18]), "+f"(d[19]), "+f"(d[20]), "+f"(d[21]), "+f"(d[22]), "+f"(d[23]), "+f"(d[24]),
        "+f"(d[25]), "+f"(d[26]), "+f"(d[27]), "+f"(d[28]), "+f"(d[29]), "+f"(d[30]), "+f"(d[31]), "+f"(d[32]),
        "+f"(d[33]), "+f"(d[34]), "+f"(d[35]), "+f"(d[36]), "+f"(d[37]), "+f"(d[38]), "+f"(d[39]), "+f"(d[40]),
        "+f"(d[41]), "+f"(d[42]), "+f"(d[43]), "+f"(d[44]), "+f"(d[45]), "+f"(d[46]), "+f"(d[47]), "+f"(d[48]),
        "+f"(d[49]), "+f"(d[50]), "+f"(d[51]), "+f"(d[52]), "+f"(d[53]), "+f"(d[54]), "+f"(d[55]), "+f"(d[56]),
        "+f"(d[57]), "+f"(d[58]), "+f"(d[59]), "+f"(d[60]), "+f"(d[61]), "+f"(d[62]), "+f"(d[63]), "+f"(d[64]),
        "+f"(d[65]), "+f"(d[66]), "+f"(d[67]), "+f"(d[68]), "+f"(d[69]), "+f"(d[70]), "+f"(d[71]), "+f"(d[72]),
        "+f"(d[73]), "+f"(d[74]), "+f"(d[75]), "+f"(d[76]), "+f"(d[77]), "+f"(d[78]), "+f"(d[79]), "+f"(d[80]),
        "+f"(d[81]), "+f"(d[82]), "+f"(d[83]), "+f"(d[84]), "+f"(d[85]), "+f"(d[86]), "+f"(d[87]), "+f"(d[88]),
        "+f"(d[89]), "+f"(d[90]), "+f"(d[91]), "+f"(d[92]), "+f"(d[93]), "+f"(d[94]), "+f"(d[95]), "+f"(d[96]),
        "+f"(d[97]), "+f"(d[98]), "+f"(d[99]), "+f"(d[100]), "+f"(d[101]), "+f"(d[102]), "+f"(d[103]), "+f"(d[104]),
        "+f"(d[105]), "+f"(d[106]), "+f"(d[107]), "+f"(d[108]), "+f"(d[109]), "+f"(d[110]), "+f"(d[111]),
        "+f"(d[112]), "+f"(d[113]), "+f"(d[114]), "+f"(d[115]), "+f"(d[116]), "+f"(d[117]), "+f"(d[118]),
        "+f"(d[119]), "+f"(d[120]), "+f"(d[121]), "+f"(d[122]), "+f"(d[123]), "+f"(d[124]), "+f"(d[125]),
        "+f"(d[126]), "+f"(d[127])
      : "l"(da), "l"(db), "r"(sd), "n"(TA), "n"(TB));
}
template <int TA, int TB>
__device__ __forceinline__ void wgmma_ss_n128(float (&d)[64], uint64_t da, uint64_t db, int sd) {
  asm volatile("{\n.reg .pred p;\nsetp.ne.b32 p, %66, 0;\n"
      "wgmma.mma_async.sync.aligned.m64n128k16.f32.bf16.bf16 {"
      "%0, %1, %2, %3, %4, %5, %6, %7, %8, %9, %10, %11, %12, %13, %14, %15, %16, %17, %18, %19, %20, %21, %22, %23, "
      "%24, %25, %26, %27, %28, %29, %30, %31, %32, %33, %34, %35, %36, %37, %38, %39, %40, %41, %42, %43, %44, %45, "
      "%46, %47, %48, %49, %50, %51, %52, %53, %54, %55, %56, %57, %58, %59, %60, %61, %62, %63"
      "}, %64, %65, p, 1, 1, %67, %68;\n}\n"
      : "+f"(d[0]), "+f"(d[1]), "+f"(d[2]), "+f"(d[3]), "+f"(d[4]), "+f"(d[5]), "+f"(d[6]), "+f"(d[7]), "+f"(d[8]),
        "+f"(d[9]), "+f"(d[10]), "+f"(d[11]), "+f"(d[12]), "+f"(d[13]), "+f"(d[14]), "+f"(d[15]), "+f"(d[16]),
        "+f"(d[17]), "+f"(d[18]), "+f"(d[19]), "+f"(d[20]), "+f"(d[21]), "+f"(d[22]), "+f"(d[23]), "+f"(d[24]),
        "+f"(d[25]), "+f"(d[26]), "+f"(d[27]), "+f"(d[28]), "+f"(d[29]), "+f"(d[30]), "+f"(d[31]), "+f"(d[32]),
        "+f"(d[33]), "+f"(d[34]), "+f"(d[35]), "+f"(d[36]), "+f"(d[37]), "+f"(d[38]), "+f"(d[39]), "+f"(d[40]),
        "+f"(d[41]), "+f"(d[42]), "+f"(d[43]), "+f"(d[44]), "+f"(d[45]), "+f"(d[46]), "+f"(d[47]), "+f"(d[48]),
        "+f"(d[49]), "+f"(d[50]), "+f"(d[51]), "+f"(d[52]), "+f"(d[53]), "+f"(d[54]), "+f"(d[55]), "+f"(d[56]),
        "+f"(d[57]), "+f"(d[58]), "+f"(d[59]), "+f"(d[60]), "+f"(d[61]), "+f"(d[62]), "+f"(d[63])
      : "l"(da), "l"(db), "r"(sd), "n"(TA), "n"(TB));
}
template <int TA, int TB>
__device__ __forceinline__ void wgmma_ss_n64(float (&d)[32], uint64_t da, uint64_t db, int sd) {
  asm volatile("{\n.reg .pred p;\nsetp.ne.b32 p, %34, 0;\n"
      "wgmma.mma_async.sync.aligned.m64n64k16.f32.bf16.bf16 {"
      "%0, %1, %2, %3, %4, %5, %6, %7, %8, %9, %10, %11, %12, %13, %14, %15, %16, %17, %18, %19, %20, %21, %22, %23, "
      "%24, %25, %26, %27, %28, %29, %30, %31"
      "}, %32, %33, p, 1, 1, %35, %36;\n}\n"
      : "+f"(d[0]), "+f"(d[1]), "+f"(d[2]), "+f"(d[3]), "+f"(d[4]), "+f"(d[5]), "+f"(d[6]), "+f"(d[7]), "+f"(d[8]),
        "+f"(d[9]), "+f"(d[10]), "+f"(d[11]), "+f"(d[12]), "+f"(d[13]), "+f"(d[14]), "+f"(d[15]), "+f"(d[16]),
        "+f"(d[17]), "+f"(d[18]), "+f"(d[19]), "+f"(d[20]), "+f"(d[21]), "+f"(d[22]), "+f"(d[23]), "+f"(d[24]),
        "+f"(d[25]), "+f"(d[26]), "+f"(d[27]), "+f"(d[28]), "+f"(d[29]), "+f"(d[30]), "+f"(d[31])
      : "l"(da), "l"(db), "r"(sd), "n"(TA), "n"(TB));
}
template <int SA, int TB>
__device__ __forceinline__ void wgmma_rs_n64(float (&d)[32], uint32_t a0, uint32_t a1, uint32_t a2, uint32_t a3, uint64_t db, int sd) {
  asm volatile("{\n.reg .pred p;\nsetp.ne.b32 p, %37, 0;\n"
      "wgmma.mma_async.sync.aligned.m64n64k16.f32.bf16.bf16 {"
      "%0, %1, %2, %3, %4, %5, %6, %7, %8, %9, %10, %11, %12, %13, %14, %15, %16, %17, %18, %19, %20, %21, %22, %23, "
      "%24, %25, %26, %27, %28, %29, %30, %31"
      "}, {%32, %33, %34, %35}, %36, p, %38, 1, %39;\n}\n"
      : "+f"(d[0]), "+f"(d[1]), "+f"(d[2]), "+f"(d[3]), "+f"(d[4]), "+f"(d[5]), "+f"(d[6]), "+f"(d[7]), "+f"(d[8]),
        "+f"(d[9]), "+f"(d[10]), "+f"(d[11]), "+f"(d[12]), "+f"(d[13]), "+f"(d[14]), "+f"(d[15]), "+f"(d[16]),
        "+f"(d[17]), "+f"(d[18]), "+f"(d[19]), "+f"(d[20]), "+f"(d[21]), "+f"(d[22]), "+f"(d[23]), "+f"(d[24]),
        "+f"(d[25]), "+f"(d[26]), "+f"(d[27]), "+f"(d[28]), "+f"(d[29]), "+f"(d[30]), "+f"(d[31])
      : "r"(a0), "r"(a1), "r"(a2), "r"(a3), "l"(db), "r"(sd), "n"(SA), "n"(TB));
}

__device__ __forceinline__ uint32_t BAR_FULL(uint32_t sb, int i) { return sb + SM_BAR + 8 * i; }
__device__ __forceinline__ uint32_t BAR_EMPTY(uint32_t sb, int i) { return sb + SM_BAR + 64 + 8 * i; }
__device__ __forceinline__ uint32_t BAR_X(uint32_t sb, int i) { return sb + SM_BAR + 128 + 8 * i; }
__device__ __forceinline__ uint32_t BAR_Y(uint32_t sb, int i) { return sb + SM_BAR + 192 + 8 * i; }
__device__ __forceinline__ uint32_t BAR_XFREE(uint32_t sb) { return sb + SM_BAR + 256; }

__device__ __forceinline__ uint32_t BAR_E2(uint32_t sb, int i) { return sb + SM_BAR + 264 + 8 * i; }
#define CMASK 0x194u
#define XORDER 0, 1, 11, 2, 3, 12, 13, 4, 5, 14, 6, 15, 16
#define XSPREAD 2
#define PFAT 3
#define SKEW 3
#define EQW 38
#define EQA 37
#define SPREAD 1
#define GL1 0
#define GS0 2
#define GL2 6
#define GS1 4
constexpr int Q_G1B = 18, Q_G2 = 32, Q_XR = 39, Q_P3 = 46, Q_END = 50;

__device__ __forceinline__ uint32_t y_addr(int kb) { return kb < 3 ? SM_RING + (kb + (Q_G2 + 4) % NSTAGE) * STAGE_BYTES : SM_X + (kb - 3) * 16384; }
static_assert((Q_G2 + 4) % NSTAGE + 2 < NSTAGE, "");

struct Ring {
  uint32_t slot, phase;
  __device__ __forceinline__ void next() { if (++slot == NSTAGE) { slot = 0; phase ^= 1; } }
};

__device__ __forceinline__ void release_slot(uint32_t sb, uint32_t slot, int tid, int times) {
  if (tid < 2 * times) mbar_arrive_cluster(BAR_EMPTY(sb, slot), tid & 1);
}

__device__ __forceinline__ void ffn_consumer(uint32_t sb, const uint8_t* smem, const Params& p, int bid, int wg, int tid, int mt, int jj) {
  const int lane = tid & 31, warp = tid >> 5, q = lane & 3, r0 = 16 * warp + (lane >> 2);
  uint32_t* const my_epoch = &p.s->epoch[blockIdx.x * 12 + (threadIdx.x >> 5)];
  const uint32_t epoch = ld_relaxed(my_epoch) + 1;
  Ring rg{0, 0};
  uint32_t u[64];
  float acc[128];
  uint32_t prev = 0, cmask = CMASK;
  int st = 0;
  auto g1_stage = [&](uint32_t slot, int s) {
    const uint64_t da = mk_desc(sb + SM_X + (s >> 1) * 16384 + wg * 8192 + (s & 1) * 64, 16, 1024, 1);
    const uint64_t db = mk_desc(sb + SM_RING + slot * STAGE_BYTES, 4096, 1024, 1);
    wg_fence();
    wgmma_ss_n256<0, 1>(acc, da, db, s != 0);
    wgmma_ss_n256<0, 1>(acc, da + 2, db + 128, 1);
    wg_commit();
  };
  if (wg == 1) {
    float ap[64];
    constexpr int QX = 32 - __builtin_clz(CMASK);
    constexpr int NPRE = QX + XSPREAD;
    uint4* const x1dst = p.s->x1t + ((64 * jj + r0 + 8) >> 2) * 1024 + (r0 & 3) * 128 + 8 * mt + (q ^ (mt & 3));
    const int x1lo = 64 * jj + r0 == 1 ? 110 * 1024 - 128 : -2048;
#pragma unroll
    for (int qi = 0; qi < NPRE; qi++) {
      const int slot = qi % NSTAGE, nc = __builtin_popcount(CMASK & ((1u << qi) - 1));
      if (qi == 0) TL(60);
      mbar_wait(BAR_FULL(sb, slot), (qi / NSTAGE) & 1);
      if (qi == 0) TL(61);
      if ((CMASK >> qi) & 1) {
#pragma unroll
        for (int kb = 2 * nc; kb < 2 * nc + 2 && kb < 7; kb++) {
          const uint64_t da = mk_desc(sb + SM_RING + slot * STAGE_BYTES + (kb & 1) * 8192, 8192, 1024, 1);
          const uint64_t db = mk_desc(sb + SM_X + kb * 16384, 16, 1024, 1);
          mbar_wait(BAR_X(sb, kb), 0);
          TL(16 + kb);
          wg_fence();
#pragma unroll
          for (int kk = 0; kk < 4; kk++) wgmma_ss_n128<1, 0>(ap, da + kk * 128, db + kk * 2, (kb | kk) != 0);
          wg_commit();
        }
      } else {
        if (((qi - nc) & 1) == 0 && qi - nc >= 4 * nc) mbar_wait(BAR_X(sb, (qi - nc) >> 1), 0);
        TL(32 + qi - nc);
        g1_stage(slot, qi - nc);
      }
      if (qi > 0) {
        wg_wait<1>();
        release_slot(sb, (qi - 1) % NSTAGE, tid, ((CMASK >> (qi - 1)) & 1) ? 2 : 1);
      }
      if (qi >= QX) {
        if (qi == QX) { fence_regs(ap); TL(2); }
#pragma unroll
        for (int t = (qi - QX) * (4 / XSPREAD); t < (qi - QX + 1) * (4 / XSPREAD); t++)
#pragma unroll
        for (int h = 0; h < 2; h++)
          x1dst[(h ? 0 : x1lo) + 512 * (t & 1) + 4 * (t >> 1)] = make_uint4((pack2(ap[16 * t + 2 * h], ap[16 * t + 2 * h + 1]) & ~1u) | (epoch & 1), pack2(ap[16 * t + 4 + 2 * h], ap[16 * t + 5 + 2 * h]),
                                             pack2(ap[16 * t + 8 + 2 * h], ap[16 * t + 9 + 2 * h]), pack2(ap[16 * t + 12 + 2 * h], ap[16 * t + 13 + 2 * h]));
      }
    }
    bar_arrive(7, 160);
    st = NPRE - 4; cmask = 0; prev = (NPRE - 1) % NSTAGE;
    rg.slot = NPRE % NSTAGE; rg.phase = (NPRE / NSTAGE) & 1;
  }
#pragma unroll 1
  for (int pass = 0; pass < 2; pass++) {
#pragma unroll 1
    for (; st < 14; st++) {
      while (cmask & 1) { cmask >>= 1; rg.next(); }
      cmask >>= 1;
      if (pass == 0 && (st & 1) == 0) mbar_wait(BAR_X(sb, st >> 1), 0);
      if (st == 14 - SKEW && wg == 1) bar_sync(9 + pass, 256);
      mbar_wait(BAR_FULL(sb, rg.slot), rg.phase);
      TL(32 + 14 * pass + st);
      g1_stage(rg.slot, st);
      wg_wait<1>();
      if (st > 0) release_slot(sb, prev, tid, 1);
      prev = rg.slot;
      rg.next();
    }
    st = 0;
    if (wg == 0) bar_arrive(9 + pass, 256);
    wg_wait<0>();
    fence_regs(acc);
    release_slot(sb, prev, tid, 1);
    if (pass == 1 && tid < 2) mbar_arrive_cluster(BAR_XFREE(sb), tid);
    TL(3 + 2 * pass);
#pragma unroll
    for (int i = 0; i < 32; i++) {
      const float g0 = 0.5f * acc[2 * i], g1 = 0.5f * acc[2 * i + 1];
      const float s0 = fmaf(g0, tanh_fast(g0), g0), s1 = fmaf(g1, tanh_fast(g1), g1);
      u[32 + i] = pack2(s0 * acc[64 + 2 * i], s1 * acc[64 + 2 * i + 1]);
    }
    if (pass == 0) {
#pragma unroll
      for (int i = 0; i < 32; i++) u[i] = u[32 + i];
    }
    TL(4 + 2 * pass);
  }
  fence_regs(u);
  float accA[32], accB[32];
  auto stage = [&](float (&acc)[32], int qi) {
    const int st = qi & 1;
    if (qi == EQW && wg == 0) bar_sync(1, 256);
    if (qi < Q_XR) mbar_wait(BAR_FULL(sb, qi % NSTAGE), (qi / NSTAGE) & 1);
    else mbar_wait(BAR_X(sb, qi - Q_XR), 1);
    const uint64_t db = mk_desc(sb + (qi < Q_XR ? SM_RING + (qi % NSTAGE) * STAGE_BYTES : SM_X + (qi - Q_XR) * 16384), 8192, 1024, 1);
    wg_fence();
#pragma unroll
    for (int kk = 0; kk < 8; kk++) {
      const uint32_t* a = u + 32 * st + 4 * kk;
      wgmma_rs_n64<1, 1>(acc, a[0], a[1], a[2], a[3], db + kk * 128, (st | kk) != 0);
    }
    wg_commit();
    if (qi == EQA && wg == 1) bar_arrive(1, 256);
  };
  auto retire = [&](int qi) {
    wg_wait<1>();
    if (qi >= Q_G2 && qi < Q_G2 + 4) release_slot(sb, qi % NSTAGE, tid, 1);
    else if (qi >= Q_G2 + 4 && qi < Q_G2 + 11 && tid == 0) mbar_arrive(BAR_E2(sb, qi - Q_G2 - 4));
  };
  const uint32_t par = epoch & 1;
  auto put = [&](float (&acc)[32], int c) {
    fence_regs(acc);
    int o = jj + 1 + c;
    if (o >= 7) o -= 7;
    uint4* dst = p.s->part + ((((mt * 7 + o) * 6 + c) * 2 + wg) * 4) * 128 + tid;
#pragma unroll
    for (int v = 0; v < 4; v++) {
      const float* a = acc + 8 * v;
      st_relaxed(dst + v * 128, make_uint4((pack2(a[0], a[1]) & ~1u) | par, pack2(a[2], a[3]), pack2(a[4], a[5]), pack2(a[6], a[7])));
    }
  };
  const uint4* const src = p.s->part + (((mt * 7 + jj) * 6 * 2 + wg) * 4) * 128 + tid;
  auto gload = [&](uint4 (&pv)[8], int c) {
#pragma unroll
    for (int i = 0; i < 8; i++) pv[i] = ld_relaxed(src + ((2 * c + (i >> 2)) * 8 + (i & 3)) * 128);
  };
  auto gload1 = [&](uint4 (&pv)[8], int c) {
#pragma unroll
    for (int i = 0; i < 4; i++) pv[4 * (c & 1) + i] = ld_relaxed(src + (c * 8 + i) * 128);
  };
  auto gsum = [&](uint4 (&pv)[8], int c) {
#pragma unroll 1
    for (uint32_t n = 0; n < SPIN_LIMIT; n++) {
      uint32_t bad = 0;
#pragma unroll
      for (int i = 0; i < 8; i++) bad |= pv[i].x ^ par;
      if (!__any_sync(0xffffffffu, bad & 1)) break;
      gload(pv, c);
    }
    TL(24 + c);
#pragma unroll
    for (int i = 0; i < 8; i++) {
      const float t[8] = {bf_lo(pv[i].x), bf_hi(pv[i].x), bf_lo(pv[i].y), bf_hi(pv[i].y), bf_lo(pv[i].z), bf_hi(pv[i].z), bf_lo(pv[i].w), bf_hi(pv[i].w)};
#pragma unroll
      for (int k = 0; k < 8; k++) accA[8 * (i & 3) + k] += t[k];
    }
  };
  uint4 pv0[8], pv1[8], pv2[8];
  const int row = 128 * mt + 64 * wg + r0;
  uint32_t gt0, gt1;
#pragma unroll
  for (int c2 = 0; c2 < 4; c2++) {
    const int qi = Q_G2 + 4 * c2;
    stage(accA, qi);
    retire(qi - 1);
    stage(accA, qi + 1);
    if (c2 == 3) TL(27);
    if (c2 > 0) put(accB, 2 * c2 - 1);
    if (c2 == 2) gload1(pv0, 1);
    if (c2 == 3) gload1(pv1, 3);
    TL(7 + c2);
    if (c2 == 3) break;
    retire(qi);
    stage(accB, qi + 2);
    retire(qi + 1);
    stage(accB, qi + 3);
    put(accA, 2 * c2);
    if (c2 == 1) gload1(pv0, 0);
    if (c2 == 2) gload1(pv1, 2);
    if (c2 == 0) { gt0 = ld_relaxed(&p.s->gate[row]); gt1 = ld_relaxed(&p.s->gate[row + 8]); }
    retire(qi + 2);
  }
#pragma unroll
  for (int kb = 0; kb < 7; kb++) {
    const int qt = Q_XR + (kb >> 1);
    if ((kb & 1) == 0) mbar_wait(BAR_FULL(sb, qt % NSTAGE), (qt / NSTAGE) & 1);
    mbar_wait(BAR_Y(sb, kb), 0);
    const uint64_t da = mk_desc(sb + y_addr(kb) + wg * 8192, 8192, 1024, 1);
    const uint64_t db = mk_desc(sb + SM_RING + (qt % NSTAGE) * STAGE_BYTES + (kb & 1) * 8192, 16, 1024, 1);
    wg_fence();
#pragma unroll
    for (int kk = 0; kk < 4; kk++) wgmma_ss_n64<1, 0>(accB, da + kk * 128, db + kk * 2, (kb | kk) != 0);
    wg_commit();
    if (kb == 1) { wg_wait<2>(); fence_regs(accA); TL(15); }
    if (kb == GS0) gsum(pv0, 0);
    if (kb == GL2) gload(pv2, 2);
    if (kb == GS1) gsum(pv1, 1);
  }
  TL(11);
  for (uint32_t n = 0; (((gt0 ^ epoch) | (gt1 ^ epoch)) & 0xffffu) && n < SPIN_LIMIT; n++) {
    gt0 = ld_relaxed(&p.s->gate[row]); gt1 = ld_relaxed(&p.s->gate[row + 8]);
  }
  gsum(pv2, 2);
  const float ga0 = bf_hi(gt0), ga1 = bf_hi(gt1);
  TL(12);
  wg_wait<0>();
  fence_regs(accB);
  TL(13);
  const float gb0 = bf_round(1.f - ga0), gb1 = bf_round(1.f - ga1);
  const float gs0 = ga0 * (2.f / (float)(S_ * D_)), gs1 = ga1 * (2.f / (float)(S_ * D_));
  uint4* const o = reinterpret_cast<uint4*>(p.out + (size_t)row * D_ + 64 * jj + 8 * q);
#pragma unroll
  for (int h = 0; h < 2; h++) {
    const float gs = h ? gs1 : gs0, gb = h ? gb1 : gb0;
#pragma unroll
    for (int k = 0; k < 2; k++) {
      uint32_t w[4];
#pragma unroll
      for (int j = 0; j < 4; j++) {
        const int i = 16 * k + 4 * j + 2 * h;
        w[j] = pack2(fmaf(gs, accB[i], gb * accA[i]), fmaf(gs, accB[i + 1], gb * accA[i + 1]));
      }
      const bool o1 = q & 1, o2 = q & 2;
      uint32_t a = __shfl_xor_sync(0xffffffffu, o1 ? w[0] : w[1], 1), b = __shfl_xor_sync(0xffffffffu, o1 ? w[2] : w[3], 1);
      if (o1) { w[0] = a; w[2] = b; } else { w[1] = a; w[3] = b; }
      a = __shfl_xor_sync(0xffffffffu, o2 ? w[0] : w[2], 2); b = __shfl_xor_sync(0xffffffffu, o2 ? w[1] : w[3], 2);
      if (o2) { w[0] = a; w[1] = b; } else { w[2] = a; w[3] = b; }
      o[h * D_ + 4 * k] = make_uint4(w[0], w[1], w[2], w[3]);
    }
  }
  if (lane == 0) *my_epoch = epoch;
  TL(14);
}

__device__ __forceinline__ void ring_issue(uint32_t sb, const Params& p, int qi, uint32_t slot, bool wait, uint32_t phase, int jj, uint32_t rank) {
  const CUtensorMap* m;
  int c0, c1, c2 = 0;
  bool half = false, is3d = false;
  if (qi < Q_G2) {
    const int nc = __popc(CMASK & ((1u << qi) - 1));
    if ((CMASK >> qi) & 1) {
      m = &p.ct; c0 = 64 * jj; c1 = 128 * nc + 64 * rank; half = nc == 3;
    } else {
      const int pass = qi >= Q_G1B;
      m = rank ? &p.wu : &p.wg; c0 = 0; c1 = 32 * (qi - nc - 14 * pass); c2 = 4 * jj + 2 * pass; is3d = true;
    }
  } else if (qi < Q_P3) {
    int o = jj + 1 + ((qi - Q_G2) >> 1);
    if (o >= 7) o -= 7;
    m = &p.wd; c0 = 64 * o; c1 = 256 * jj + 128 * (qi & 1) + 64 * rank;
  } else {
    m = &p.ct; c0 = 128 * (qi - Q_P3) + 64 * rank; c1 = 64 * jj; half = qi == Q_END - 1;
  }
  uint32_t bar = BAR_FULL(sb, slot), dst = sb + SM_RING + slot * STAGE_BYTES + rank * 8192;
  if (qi >= Q_XR && qi < Q_P3) {
    bar = BAR_X(sb, qi - Q_XR); dst = sb + SM_X + (qi - Q_XR) * 16384 + rank * 8192;
    if (qi < Q_XR + 2) mbar_wait_cluster(BAR_XFREE(sb), 0);
  } else {
    if (wait) mbar_wait_cluster(BAR_EMPTY(sb, slot), phase ^ (qi >= Q_P3));
    mbar_expect_tx(bar, half ? 8192 : 16384);
  }
  if (is3d) tma3d_mc(dst, m, c0, c1, c2, bar);
  else if (!(half && rank)) tma2d_mc(dst, m, c0, c1, bar);
}

__device__ __forceinline__ void ffn_producer(uint32_t sb, const uint8_t* smem, int bid, const Params& p, int warp, int lane, int mt, int jj, uint32_t rank) {
  if (warp < 2) {
    if (lane == 0) {
      uint32_t slot = warp, phase = 0;
#pragma unroll 1
      for (int qi = NSTAGE + warp; qi < Q_END; qi += 2) {
        ring_issue(sb, p, qi, slot, true, phase, jj, rank);
        TL(10 + qi);
        slot += 2;
        if (slot >= NSTAGE) { slot -= NSTAGE; phase ^= 1; }
      }
    }
  } else {
    const int wg = warp - 2;
    uint32_t* const my_epoch = &p.s->epoch[blockIdx.x * 12 + 8 + warp];
    const uint32_t epoch = ld_relaxed(my_epoch) + 1;
    if (wg == 0) {
      if (lane == 0) { prefetch_tmap(&p.wd); prefetch_tmap(&p.yt); }
      {
        const uint4* gw4 = reinterpret_cast<const uint4*>(p.gate_w);
        const uint4 ga = __ldg(gw4 + lane), gb = lane < 24 ? __ldg(gw4 + 32 + lane) : make_uint4(0, 0, 0, 0);
        if (lane < 7) { mbar_wait(BAR_X(sb, lane), 0); mbar_expect_tx(BAR_X(sb, lane), 16384); mbar_expect_tx(BAR_Y(sb, lane), 16384); }
        __syncwarp();
        float mine = 0.f;
#pragma unroll 1
        for (int u = 0; u < 19; u++) {
          const int r = min(19 * jj + u, 127);
          const uint8_t* xr = smem + SM_X + (lane >> 3) * 16384 + r * 128 + (((lane ^ r) & 7) << 4);
          const uint4 xa = *reinterpret_cast<const uint4*>(xr);
          const uint4 xb = lane < 24 ? *reinterpret_cast<const uint4*>(xr + 65536) : make_uint4(0, 0, 0, 0);
          float s = 0.f;
          auto dot2 = [&](uint32_t a, uint32_t b) {
            const uint32_t pr = mul2(a, b);
            s += bf_lo(pr) + bf_hi(pr);
          };
          dot2(xa.x, ga.x); dot2(xa.y, ga.y); dot2(xa.z, ga.z); dot2(xa.w, ga.w);
          dot2(xb.x, gb.x); dot2(xb.y, gb.y); dot2(xb.z, gb.z); dot2(xb.w, gb.w);
#pragma unroll
          for (int o = 16; o > 0; o >>= 1) s += __shfl_xor_sync(0xffffffffu, s, o);
          if (lane == u) mine = s;
        }
        if (lane < 19 && 19 * jj + lane < 128)
          st_relaxed(&p.s->gate[128 * mt + 19 * jj + lane], pack2(0.f, 1.f / (1.f + __expf(-bf_round(mine)))) | (epoch & 0xffffu));
      }
      TL(9);
      if (lane < 2) mbar_arrive_cluster(BAR_XFREE(sb), lane);
    } else {
      mbar_wait(BAR_X(sb, PFAT), 0);
      if (lane < 6) {
        int row = 176 + 3 * bid + (lane >> 1);
        if (row >= D_) row -= D_;
        l2_prefetch(((lane & 1) ? p.pwu : p.pwg) + row * F_, F_ * 2);
      }
      TL(2);
      bar_sync(7, 160);
      if (lane == 0) { red_add(&p.s->cnt_x1[jj * 32], 1);
        l2_prefetch(p.pwd + bid * 16 * D_, 32 * D_); }
      TL(5);
    }
    mbar_wait(BAR_XFREE(sb), 0);
    TL(3);
    const int kb = 2 * lane + wg;
    bool todo = kb < 7, ready = false;
    uint32_t n = 0;
    while (__any_sync(0xffffffffu, todo)) {
      if (todo) {
        uint32_t ok;
        if (!ready) {
          asm volatile("ld.acquire.gpu.global.u32 %0, [%1];" : "=r"(ok) : "l"(&p.s->cnt_y[kb * 32]) : "memory");
          ready = (int32_t)(ok - epoch * (kb ? 16 : 17)) >= 0;
        }
        asm volatile("{\n.reg .pred p;\nmbarrier.test_wait.parity.shared::cta.b64 p, [%1], 0;\nselp.u32 %0, 1, 0, p;\n}"
                     : "=r"(ok) : "r"(BAR_E2(sb, kb)) : "memory");
        if ((ok && ready) || ++n > SPIN_LIMIT) {
          tma3d(sb + y_addr(kb), &p.yt, 0, 64 * kb, 2 * mt, BAR_Y(sb, kb));
          todo = false;
        }
      }
      __nanosleep(40);
    }
    TL(4);
    if (lane == 0) *my_epoch = epoch;
  }
}

__device__ __forceinline__ void spectral_cta(uint32_t sb, uint8_t* smem, const Params& p, int sc, int wg) {
  const int t384 = threadIdx.x, lane = t384 & 31, warp12 = t384 >> 5, tid = t384 & 127;
  const int warp = tid >> 5, q = lane & 3;
  const int sl0 = 6 * sc + min(sc, 8), nsl = sc < 8 ? 7 : 6;
  if (t384 == 320) {
#pragma unroll 1
    for (int i = 0; i < nsl; i++) {
      mbar_expect_tx(BAR_X(sb, i), 2 * SLAB_BYTES);
      const int row = 128 * ((sl0 + i) >> 3) + 8 * ((sl0 + i) & 7);
      const uint32_t dst = sb + SP_Z + 2 * i * SLAB_BYTES;
      bulk_g2s(dst, p.w_r + row * DF_, SLAB_BYTES / 2, BAR_X(sb, i));
      bulk_g2s(dst + SLAB_BYTES / 2, p.w_r + (row + 64) * DF_, SLAB_BYTES / 2, BAR_X(sb, i));
      bulk_g2s(dst + SLAB_BYTES, p.w_i + row * DF_, SLAB_BYTES / 2, BAR_X(sb, i));
      bulk_g2s(dst + 3 * SLAB_BYTES / 2, p.w_i + (row + 64) * DF_, SLAB_BYTES / 2, BAR_X(sb, i));
    }
    if (sc < 19) {
      mbar_expect_tx(BAR_Y(sb, 6), 24576);
      bulk_g2s(sb + SP_TW, p.spec, 24576, BAR_Y(sb, 6));
    }
  }
  uint32_t* const my_epoch = &p.s->epoch[blockIdx.x * 12 + warp12];
  const uint32_t epoch = ld_relaxed(my_epoch) + 1;
  uint32_t fe[16], tw[16];
#pragma unroll
  for (int i = 0; i < 4; i++) {
    const uint4 a = __ldg(reinterpret_cast<const uint4*>(p.spec->fe) + i * 128 + tid);
    const uint4 b = __ldg(reinterpret_cast<const uint4*>(p.spec->tw) + i * 128 + tid);
    fe[4 * i] = a.x; fe[4 * i + 1] = a.y; fe[4 * i + 2] = a.z; fe[4 * i + 3] = a.w;
    tw[4 * i] = b.x; tw[4 * i + 1] = b.y; tw[4 * i + 2] = b.z; tw[4 * i + 3] = b.w;
  }
  __syncwarp();
  asm volatile("barrier.cluster.wait.acquire.aligned;" ::: "memory");
#pragma unroll 2
  for (int un = wg; un < 8 * nsl; un += 3) {
    const int i = un >> 3, sl = sl0 + i, pr = 16 * (un & 7) + 4 * (lane >> 3) + warp, r = lane & 7;
    mbar_wait(BAR_X(sb, i), 0);
    if (pr < 113) {
      const uint16_t* w = reinterpret_cast<const uint16_t*>(smem + SP_Z + 2 * i * SLAB_BYTES) + r * DF_ + 2 * pr;
      const uint32_t m = pr < 112 ? 0xffffffffu : 0u;
      p.s->wt[pr * 1024 + sl * 8 + (r ^ ((sl >> 2) & 6))] =
          make_uint4(w[0] | ((uint32_t)w[8 * DF_] << 16), w[16 * DF_] | ((uint32_t)w[24 * DF_] << 16),
                     (w[1] | ((uint32_t)w[8 * DF_ + 1] << 16)) & m, (w[16 * DF_ + 1] | ((uint32_t)w[24 * DF_ + 1] << 16)) & m);
    }
  }
  __syncthreads();
  if (t384 == 352) { fence_gpu(); red_add(&p.s->cnt_w[0], 1); }
  TL(1);
  if (sc == 19) return;
  const int nrnd = (sc == 18 && wg == 2) ? 1 : 2;
  if (tid == 32) {
    wait_counter(&p.s->cnt_w[0], epoch * NSPEC);
    fence_async();
    for (int rnd = 0; rnd < nrnd; rnd++) {
      const int item = wg + 3 * rnd;
      mbar_expect_tx(BAR_Y(sb, item), 16384);
      bulk_g2s(sb + SP_W + item * 16384, p.s->wt + (6 * sc + item) * 1024, 16384, BAR_Y(sb, item));
    }
  } else if (tid == 0) {
#pragma unroll 1
    for (int rnd = 0; rnd < nrnd; rnd++) {
      const int item = wg + 3 * rnd, pr = 6 * sc + item;
      wait_counter(&p.s->cnt_x1[(pr < 112 ? pr >> 4 : 0) * 32], epoch * 16);
      const uint32_t bar = BAR_FULL(sb, item), z = sb + SP_Z + item * 16384;
      mbar_expect_tx(bar, 16384);
      bulk_g2s(z, p.s->x1t + pr * 1024, 16384, bar);
    }
  }
  __syncwarp();
  fence_regs(fe); fence_regs(tw);
  mbar_wait(BAR_Y(sb, 6), 0);
  TL(3);
  const uint64_t dT_n = mk_desc(sb + SP_T, 8192, 1024, 1);
#pragma unroll 1
  for (int rnd = 0; rnd < nrnd; rnd++) {
    const int item = wg + 3 * rnd, pr = 6 * sc + item;
    const uint32_t z = sb + SP_Z + item * 16384;
    uint32_t fa[16], fb[16];
    auto load_frag = [&](int off) {
#pragma unroll
      for (int i = 0; i < 4; i++) {
        const uint4 a = *reinterpret_cast<const uint4*>(smem + SP_TW + off + i * 2048 + tid * 16);
        fa[4 * i] = a.x; fa[4 * i + 1] = a.y; fa[4 * i + 2] = a.z; fa[4 * i + 3] = a.w;
      }
      fence_regs(fa);
    };
    load_frag(0);
    {
      const uint32_t live = pr == 0 ? 0xddu : (pr == 112 ? 0x11u : 0xffu);
#pragma unroll 1
      for (uint32_t n = 0; n < 4096; n++) {
        mbar_wait(BAR_FULL(sb, item), n & 1);
        uint32_t bad = 0;
#pragma unroll
        for (int i = 0; i < 8; i++) bad |= ((*reinterpret_cast<const volatile uint32_t*>(smem + SP_Z + item * 16384 + i * 2048 + tid * 16) ^ epoch) & 1) << i;
        uint32_t again;
        asm volatile("{\n.reg .pred p, q;\nsetp.ne.u32 p, %1, 0;\nbarrier.red.or.pred q, %2, 128, p;\nselp.u32 %0, 1, 0, q;\n}"
                     : "=r"(again) : "r"(bad & live), "r"(1 + wg) : "memory");
        if (!again) break;
        TL(20);
        if (tid == 0) { mbar_expect_tx(BAR_FULL(sb, item), 16384); bulk_g2s(z, p.s->x1t + pr * 1024, 16384, BAR_FULL(sb, item)); }
      }
    }
    TL(4 + 8 * rnd);
    if (rnd == 0 && wg > 0) bar_sync(3 + wg, 256);
    float aR[32], aI[32];
    {
      const uint64_t de = mk_desc(z, 4096, 512, 2);
      wg_fence();
#pragma unroll
      for (int kk = 0; kk < 4; kk++) {
        wgmma_rs_n64<1, 1>(aR, fe[4 * kk], fe[4 * kk + 1], fe[4 * kk + 2], fe[4 * kk + 3], de + kk * 64, kk != 0);
        wgmma_rs_n64<1, 1>(aI, fa[4 * kk], fa[4 * kk + 1], fa[4 * kk + 2], fa[4 * kk + 3], de + 512 + kk * 64, kk != 0);
      }
      wg_commit();
      if (rnd == 0 && wg < 2) bar_arrive(4 + wg, 256);
      wg_wait<0>();
      fence_regs(aR); fence_regs(aI);
    }
    TL(5 + 8 * rnd);
#pragma unroll
    for (int v = 0; v < 8; v++) {
      uint32_t* f = (v < 4 ? fa : fb) + 2 * (v & 3);
      const uint32_t* t = tw + 2 * (v & 3);
      const float *e = aR + 4 * v, *o = aI + 4 * v;
      const uint32_t er = pack2(e[0], e[1]), ei = pack2(e[2], e[3]), qr = pack2(o[0], o[1]), qi = pack2(o[2], o[3]);
      const uint32_t u0r = add2(er, qr), u0i = add2(ei, qi), u1r = sub2(er, qr), u1i = sub2(ei, qi);
      f[0] = fma2(u0r, t[0], mul2(u0i, t[8]));
      f[8] = fms2(u0i, t[0], mul2(u0r, t[8]));
      f[1] = fma2(u1r, t[1], mul2(u1i, t[9]));
      f[9] = fms2(u1i, t[1], mul2(u1r, t[9]));
    }
    fence_regs(fa); fence_regs(fb);
    wg_fence();
#pragma unroll
    for (int kk = 0; kk < 4; kk++) {
      wgmma_rs_n64<1, 1>(aR, fa[4 * kk], fa[4 * kk + 1], fa[4 * kk + 2], fa[4 * kk + 3], dT_n + kk * 128, kk != 0);
      wgmma_rs_n64<1, 1>(aI, fb[4 * kk], fb[4 * kk + 1], fb[4 * kk + 2], fb[4 * kk + 3], dT_n + kk * 128, kk != 0);
    }
    wg_commit();
    mbar_wait(BAR_Y(sb, item), 0);
    wg_wait<0>();
    fence_regs(aR); fence_regs(aI);
    TL(6 + 8 * rnd);
    {
      const uint8_t* wp = smem + SP_W + item * 16384 + q * 1024 + warp * 128 + (((lane >> 2) ^ (2 * q)) << 4);
#pragma unroll
      for (int jb = 0; jb < 4; jb++) {
#pragma unroll
        for (int h = 0; h < 2; h++) {
          const uint4 w = *reinterpret_cast<const uint4*>(wp + jb * 4096 + h * 512);
          const int i = 4 * jb + 2 * h;
          const uint32_t ar = pack2(aR[i], aR[i + 1]), ai = pack2(aR[16 + i], aR[17 + i]);
          const uint32_t br = pack2(aI[i], aI[i + 1]), bi = pack2(aI[16 + i], aI[17 + i]);
          fa[2 * jb + h] = fms2(ar, w.x, mul2(ai, w.y));
          fa[8 + 2 * jb + h] = fma2(ar, w.y, mul2(ai, w.x));
          fb[2 * jb + h] = fms2(br, w.z, mul2(bi, w.w));
          fb[8 + 2 * jb + h] = fma2(br, w.w, mul2(bi, w.z));
        }
      }
    }
    fence_regs(fa); fence_regs(fb);
    wg_fence();
#pragma unroll
    for (int kk = 0; kk < 4; kk++) {
      wgmma_rs_n64<1, 0>(aR, fa[4 * kk], fa[4 * kk + 1], fa[4 * kk + 2], fa[4 * kk + 3], dT_n + kk * 2, kk != 0);
      wgmma_rs_n64<1, 0>(aI, fb[4 * kk], fb[4 * kk + 1], fb[4 * kk + 2], fb[4 * kk + 3], dT_n + kk * 2, kk != 0);
    }
    wg_commit();
    wg_wait<0>();
    fence_regs(aR); fence_regs(aI);
    TL(7 + 8 * rnd);
#pragma unroll
    for (int v = 0; v < 8; v++) {
      const float* a = (v < 4 ? aR : aI) + 4 * (v & 3);
      const uint32_t* t = tw + 2 * (v & 3);
      const uint32_t u0r = pack2(a[0], a[1]), u1r = pack2(a[2], a[3]), u0i = pack2(a[16], a[17]), u1i = pack2(a[18], a[19]);
      const uint32_t t0r = fms2(u0r, t[0], mul2(u0i, t[8])), t0i = fma2(u0i, t[0], mul2(u0r, t[8]));
      const uint32_t t1r = fms2(u1r, t[1], mul2(u1i, t[9])), t1i = fma2(u1i, t[1], mul2(u1r, t[9]));
      fa[v] = add2(t0i, t1i); fa[8 + v] = add2(t0r, t1r);
      fb[v] = sub2(t0i, t1i); fb[8 + v] = sub2(t0r, t1r);
    }
    bar_sync(1 + wg, 128);
#pragma unroll
    for (int u = 0; u < 4; u++) {
      const uint32_t a = z + (32 * (u >> 1) + 8 * warp + (lane & 7)) * 128 + (((4 * (u & 1) + (lane >> 3)) ^ (lane & 7)) << 4);
      stmatrix_x4(a, fa[4 * u], fa[4 * u + 1], fa[4 * u + 2], fa[4 * u + 3]);
      stmatrix_x4(a + 8192, fb[4 * u], fb[4 * u + 1], fb[4 * u + 2], fb[4 * u + 3]);
    }
    load_frag(8192);
    fence_async_smem();
    bar_sync(1 + wg, 128);
    TL(8 + 8 * rnd);
    {
      const uint64_t de = mk_desc(z, 8192, 1024, 1);
      wg_fence();
#pragma unroll
      for (int kk = 0; kk < 4; kk++) {
        wgmma_rs_n64<1, 1>(aR, fe[4 * kk], fe[4 * kk + 1], fe[4 * kk + 2], fe[4 * kk + 3], de + kk * 128, kk != 0);
        wgmma_rs_n64<1, 1>(aI, fa[4 * kk], fa[4 * kk + 1], fa[4 * kk + 2], fa[4 * kk + 3], de + 512 + kk * 128, kk != 0);
      }
      wg_commit();
      wg_wait<0>();
      fence_regs(aR); fence_regs(aI);
    }
    TL(9 + 8 * rnd);
    const bool edge = pr == 0 || pr == 112;
    if (edge) {
#pragma unroll
      for (int i = 0; i < 16; i++) { aR[i] *= 0.5f; aI[i] *= 0.5f; }
    }
#pragma unroll
    for (int i = 0; i < 8; i++) {
      const float* a = ((i & 1) ? aI : aR) + 16 * (i >> 2) + 2 - (i & 2);
      *reinterpret_cast<uint4*>(smem + SP_W + item * 16384 + (i >> 1) * 4096 + (i & 1) * 64 + (tid >> 2) * 128 + q * 16) =
          make_uint4(pack2(a[0], a[1]), pack2(a[4], a[5]), pack2(a[8], a[9]), pack2(a[12], a[13]));
    }
    fence_async_smem();
    bar_sync(1 + wg, 128);
    if (tid == 0) {
      const uint32_t src = sb + SP_W + item * 16384;
      __nv_bfloat16* dst = p.s->yt + (size_t)(pr < 112 ? 4 * pr : 1) * S_;
      bulk_s2g(dst, src, edge ? 4096 : 16384);
      if (pr == 0) bulk_s2g(dst + 2 * S_, src + 8192, 8192);
      asm volatile("cp.async.bulk.commit_group;" ::: "memory");
      if (rnd == nrnd - 1) {
        asm volatile("cp.async.bulk.wait_group 0;" ::: "memory");
        TL(11);
        red_add(&p.s->cnt_y[(pr < 112 ? pr >> 4 : 0) * 32], 1);
        if (rnd) red_add(&p.s->cnt_y[((pr - 3) >> 4) * 32], 1);
      }
    }
    __syncwarp();
    TL(10 + 8 * rnd);
  }
  if (lane == 0) *my_epoch = epoch;
}

__global__ void __cluster_dims__(2, 1, 1) __launch_bounds__(384, 1)
fused_kernel(const __grid_constant__ Params p) {
  extern __shared__ __align__(1024) uint8_t smem[];
  const uint32_t sb = smem_u32(smem);
  TL(0);
  const uint32_t rank = blockIdx.x & 1;
  const int hc = blockIdx.x >> 1;
  int grp, jj;
  if (hc < 4) { grp = 8; jj = hc; }
  else if (hc < 36) { grp = (hc - 4) & 7; jj = (hc - 4) >> 3; }
  else if (hc < 57) { jj = (hc - 36) / 7; grp = 1 + (hc - 36) - 7 * jj; jj += 4; }
  else if (hc < 60) { grp = 0; jj = hc - 53; }
  else { grp = 8; jj = hc - 56; }
  const int mt = 2 * grp + rank, bid = 2 * (7 * grp + jj) + rank;
  if (threadIdx.x == 256) {
#pragma unroll
    for (int i = 0; i < NSTAGE; i++) { mbar_init(BAR_FULL(sb, i), 1); mbar_init(BAR_EMPTY(sb, i), 4); }
    asm volatile("fence.mbarrier_init.release.cluster;" ::: "memory");
  } else if (threadIdx.x == 320) {
#pragma unroll
    for (int i = 0; i < NSTAGE; i++) { mbar_init(BAR_X(sb, i), 1); mbar_init(BAR_Y(sb, i), 1); }
    mbar_init(BAR_XFREE(sb), 6);
#pragma unroll
    for (int i = 0; i < 7; i++) mbar_init(BAR_E2(sb, i), 2);
    asm volatile("fence.mbarrier_init.release.cluster;" ::: "memory");
  } else if (threadIdx.x == 288) {
    prefetch_tmap(rank ? &p.wu : &p.wg); prefetch_tmap(&p.ct);
  }
  __syncwarp();
  asm volatile("barrier.cluster.arrive.relaxed.aligned;" ::: "memory");
  const int wg = __shfl_sync(0xffffffffu, threadIdx.x >> 7, 0);
  if (bid >= NFFN) {
    spectral_cta(sb, smem, p, bid - NFFN, wg);
  } else if (wg < 2) {
    asm volatile("setmaxnreg.inc.sync.aligned.u32 232;");
    asm volatile("barrier.cluster.wait.acquire.aligned;" ::: "memory");
    TL(1);
    ffn_consumer(sb, smem, p, bid, wg, threadIdx.x & 127, mt, jj);
  } else {
    asm volatile("setmaxnreg.dec.sync.aligned.u32 40;");
    if (threadIdx.x == 320) {
      mbar_expect_tx(BAR_X(sb, 0), 16384);
      tma2d(sb + SM_X, &p.x, 0, 128 * mt, BAR_X(sb, 0));
    }
    __syncwarp();
    asm volatile("barrier.cluster.wait.acquire.aligned;" ::: "memory");
    TL(1);
    if (threadIdx.x == 320) {
      constexpr int order[13] = {XORDER};
#pragma unroll
      for (int i = 0; i < 13; i++) {
        if (order[i] < 8) {
          ring_issue(sb, p, order[i], order[i], false, 0, jj, rank);
        } else {
          const int kb = order[i] - 10;
          mbar_expect_tx(BAR_X(sb, kb), 16384);
          tma2d(sb + SM_X + kb * 16384, &p.x, 64 * kb, 128 * mt, BAR_X(sb, kb));
        }
      }
      TL(2);
    } else if (threadIdx.x == 352) {
    }
    __syncwarp();
    ffn_producer(sb, smem, bid, p, (threadIdx.x >> 5) & 3, threadIdx.x & 31, mt, jj, rank);
  }
}

typedef CUresult (*EncodeFn)(CUtensorMap*, CUtensorMapDataType, cuuint32_t, void*, const cuuint64_t*, const cuuint64_t*,
                             const cuuint32_t*, const cuuint32_t*, CUtensorMapInterleave, CUtensorMapSwizzle,
                             CUtensorMapL2promotion, CUtensorMapFloatOOBfill);

void make_map(EncodeFn fn, CUtensorMap* m, const void* base, int rank, const cuuint64_t* dims, const cuuint64_t* strides,
              const cuuint32_t* box, CUtensorMapSwizzle sw) {
  const cuuint32_t es[4] = {1, 1, 1, 1};
  fn(m, CU_TENSOR_MAP_DATA_TYPE_BFLOAT16, rank, const_cast<void*>(base), dims, strides, box, es,
     CU_TENSOR_MAP_INTERLEAVE_NONE, sw, CU_TENSOR_MAP_L2_PROMOTION_L2_256B, CU_TENSOR_MAP_FLOAT_OOB_FILL_NONE);
}

}

extern "C" void kernel_launch(void* const* d_in, const int* in_sizes, int n_in, void* d_out, int out_size) {
  const __nv_bfloat16* x = (const __nv_bfloat16*)d_in[0];
  const __nv_bfloat16* w_r = (const __nv_bfloat16*)d_in[1];
  const __nv_bfloat16* w_i = (const __nv_bfloat16*)d_in[2];
  const __nv_bfloat16* wg = (const __nv_bfloat16*)d_in[4];
  const __nv_bfloat16* wu = (const __nv_bfloat16*)d_in[5];
  const __nv_bfloat16* wd = (const __nv_bfloat16*)d_in[6];
  const __nv_bfloat16* gate_w = (const __nv_bfloat16*)d_in[7];

  void* fnp = nullptr;
  cudaDriverEntryPointQueryResult qr;
  cudaGetDriverEntryPoint("cuTensorMapEncodeTiled", &fnp, cudaEnableDefault, &qr);
  EncodeFn fn = (EncodeFn)fnp;
  void *ctab, *spec, *scr;
  cudaGetSymbolAddress(&ctab, g_ctab);
  cudaGetSymbolAddress(&spec, g_spec);
  cudaGetSymbolAddress(&scr, g_scratch);
  const void* yt = (const char*)scr + offsetof(Scratch, yt);
  Params p;
  p.s = (Scratch*)scr; p.out = (__nv_bfloat16*)d_out;
  p.px = x; p.w_r = w_r; p.w_i = w_i; p.gate_w = gate_w; p.pwg = wg; p.pwu = wu; p.pwd = wd;
  p.ctab = (const tab::Table*)ctab; p.spec = (const tab::Spec*)spec;
  {
    const cuuint64_t d[2] = {D_, S_}, s[1] = {D_ * 2};
    const cuuint32_t b[2] = {64, 128};
    make_map(fn, &p.x, x, 2, d, s, b, CU_TENSOR_MAP_SWIZZLE_128B);
  }
  {
    const cuuint64_t d[3] = {64, D_, F_ / 64}, s[2] = {F_ * 2, 128};
    const cuuint32_t b[3] = {64, 32, 2};
    make_map(fn, &p.wg, wg, 3, d, s, b, CU_TENSOR_MAP_SWIZZLE_128B);
    make_map(fn, &p.wu, wu, 3, d, s, b, CU_TENSOR_MAP_SWIZZLE_128B);
  }
  {
    const cuuint64_t d[2] = {D_, F_}, s[1] = {D_ * 2};
    const cuuint32_t b[2] = {64, 64};
    make_map(fn, &p.wd, wd, 2, d, s, b, CU_TENSOR_MAP_SWIZZLE_128B);
  }
  {
    const cuuint64_t d[2] = {D_, D_}, s[1] = {D_ * 2};
    const cuuint32_t b[2] = {64, 64};
    make_map(fn, &p.ct, ctab, 2, d, s, b, CU_TENSOR_MAP_SWIZZLE_128B);
  }
  {
    const cuuint64_t d[3] = {64, D_, S_ / 64}, s[2] = {S_ * 2, 128};
    const cuuint32_t b[3] = {64, 64, 2};
    make_map(fn, &p.yt, yt, 3, d, s, b, CU_TENSOR_MAP_SWIZZLE_128B);
  }
  cudaFuncSetAttribute(fused_kernel, cudaFuncAttributeMaxDynamicSharedMemorySize, SM_TOTAL);
  fused_kernel<<<NCTA, 384, SM_TOTAL, cudaStreamPerThread>>>(p, x, w_r, w_i, gate_w, wd, (__nv_bfloat16*)d_out);
}
```

```cpp
#include <cuda_runtime.h>
#include <cuda_bf16.h>
#include <cuda.h>
#include <stdint.h>
#include <stddef.h>

namespace {

constexpr int S_ = 2048, D_ = 448, F_ = 1792, DF_ = 225;
constexpr int NFFN = 112, NSPEC = 20, NCTA = NFFN + NSPEC;
constexpr int NSTAGE = 7, STAGE_BYTES = 16384;
constexpr int SM_X = 0, SM_RING = 114688, SM_BAR = 229376, SM_TOTAL = SM_BAR + 512;
constexpr int SP_Z = 0, SP_W = 98304, SP_TW = 198656, SP_T = 215040, SLAB_BYTES = 16 * DF_ * 2;
constexpr uint32_t SPIN_LIMIT = 1u << 20;

namespace tab {
constexpr double PI = 3.14159265358979323846264338327950288;
constexpr double csin(double x) {
  double t = x, s = x;
  for (int i = 1; i < 20; i++) { t = -t * x * x / ((2 * i) * (2 * i + 1)); s += t; }
  return s;
}
constexpr double ccos(double x) {
  double t = 1, s = 1;
  for (int i = 1; i < 20; i++) { t = -t * x * x / ((2 * i - 1) * (2 * i)); s += t; }
  return s;
}
constexpr uint32_t to_bf16(double v) {
  uint32_t sign = v < 0 ? 0x8000u : 0u;
  double a = v < 0 ? -v : v;
  if (a < 1e-12) return 0;
  int e = 0;
  while (a >= 2.0) { a /= 2; e++; }
  while (a < 1.0) { a *= 2; e--; }
  double m = a * 128.0;
  int mi = (int)m;
  double fr = m - mi;
  if (fr > 0.5 || (fr == 0.5 && (mi & 1))) mi++;
  if (mi == 256) { mi = 128; e++; }
  return sign | (uint32_t)((e + 127) << 7) | (uint32_t)(mi - 128);
}
struct Base { uint32_t v[448]; };
constexpr Base make_base() {
  Base b{};
  for (int m = 0; m < 448; m++) {
    int mm = m > 224 ? m - 448 : m;
    double ang = 2 * PI * mm / 448.0;
    b.v[m] = to_bf16(ccos(ang)) | (to_bf16(-csin(ang)) << 16);
  }
  return b;
}
constexpr Base base = make_base();
struct Row { uint32_t v[224]; };
constexpr Row make_row(int d) {
  Row r{};
  r.v[0] = 0x3f80u | ((d & 1) ? 0xbf800000u : 0x3f800000u);
  int m = 0;
  for (int c = 1; c < 224; c++) { m += d; if (m >= 448) m -= 448; r.v[c] = base.v[m]; }
  return r;
}
struct Table { Row r[448]; };
constexpr Table make_table() {
  Table t{};
  for (int d = 0; d < 448; d++) t.r[d] = make_row(d);
  return t;
}
struct Cs { double c[2048], s[2048]; };
constexpr Cs make_cs() {
  Cs t{};
  for (int m = 0; m <= 256; m++) {
    const double a = 2 * PI * m / 2048.0, c = ccos(a), s = csin(a);
    t.c[m] = c; t.s[m] = s;
    t.c[512 - m] = s; t.s[512 - m] = c;
  }
  for (int m = 513; m < 2048; m++) { t.c[m] = -t.s[m - 512]; t.s[m] = t.c[m - 512]; }
  return t;
}
constexpr Cs cs = make_cs();
struct Spec {
  uint32_t fo[2048], fot[2048];
  uint16_t t32[4096];
  uint32_t fe[2048];
  uint32_t tw[2048];
};
constexpr uint32_t blk(int h, int c, int a) { return to_bf16(h == c ? cs.c[a & 2047] : (h ? -cs.s[a & 2047] : cs.s[a & 2047])); }
constexpr Spec make_spec() {
  Spec t{};
  for (int row = 0; row < 64; row++)
    for (int col = 0; col < 64; col++) {
      const int c = row & 31, k2 = col & 31, n2 = 8 * ((c >> 1) & 3) + 2 * (c >> 3) + (c & 1), m = 64 * ((n2 * k2) & 31);
      const double v = (row >> 5) == (col >> 5) ? cs.c[m] : (row < 32 ? -cs.s[m] : cs.s[m]);
      t.t32[row * 64 + (((col >> 3) ^ (row & 7)) << 3) + (col & 7)] = (uint16_t)to_bf16(v);
    }
  for (int th = 0; th < 128; th++)
    for (int i = 0; i < 16; i++) {
      const int r = 8 * (th >> 5) + ((th & 31) >> 2), h = i & 1, c = i >> 3, m = 8 * ((i >> 1) & 3) + 2 * (th & 3);
      const int o = ((i >> 2) * 128 + th) * 4 + (i & 3);
      t.fe[o] = blk(h, c, 64 * m * r) | (blk(h, c, 64 * (m + 1) * r) << 16);
      t.fo[o] = blk(h, c, 32 * (2 * m + 1) * r) | (blk(h, c, 32 * (2 * m + 3) * r) << 16);
      t.fot[o] = blk(h, c, 32 * (2 * r + 1) * m) | (blk(h, c, 32 * (2 * r + 1) * (m + 1)) << 16);
      const int k1 = r + 32 * h, n2 = 8 * (th & 3) + 2 * ((i >> 1) & 3);
      t.tw[o] = blk(0, c, n2 * k1) | (blk(0, c, (n2 + 1) * k1) << 16);
    }
  return t;
}
}
}

__device__ __align__(1024) const tab::Table g_ctab = tab::make_table();
__device__ __align__(1024) const tab::Spec g_spec = tab::make_spec();

struct Scratch {
  uint32_t cnt_w[32];
  uint32_t cnt_x1[7 * 32];
  uint32_t cnt_y[7 * 32];
  uint32_t epoch[NCTA * 12 + 240 + 256];
  uint32_t gate[S_];
  uint4 x1t[113 * 1024];
  __nv_bfloat16 yt[D_ * S_];
  uint4 wt[114 * 1024];
  uint4 part[16 * 7 * 6 * 2 * 4 * 128];
};
static_assert(offsetof(Scratch, x1t) % 1024 == 0, "alignment");
__device__ __align__(1024) Scratch g_scratch;
#define TL(i)

namespace {

struct Params {
  Scratch* s;
  __nv_bfloat16* out;
  const __nv_bfloat16 *px, *w_r, *w_i, *gate_w, *pwg, *pwu, *pwd;
  const tab::Table* ctab;
  const tab::Spec* spec;
  CUtensorMap x, wg, wu, wd, ct, yt;
};

__device__ __forceinline__ uint32_t smem_u32(const void* p) { return (uint32_t)__cvta_generic_to_shared(p); }
__device__ __forceinline__ void mbar_init(uint32_t bar, uint32_t cnt) {
  asm volatile("mbarrier.init.shared::cta.b64 [%0], %1;" ::"r"(bar), "r"(cnt) : "memory");
}
__device__ __forceinline__ void mbar_expect_tx(uint32_t bar, uint32_t bytes) {
  asm volatile("mbarrier.arrive.expect_tx.shared::cta.b64 _, [%0], %1;" ::"r"(bar), "r"(bytes) : "memory");
}
__device__ __forceinline__ void mbar_arrive(uint32_t bar) {
  asm volatile("mbarrier.arrive.shared::cta.b64 _, [%0];" ::"r"(bar) : "memory");
}
__device__ __forceinline__ void mbar_arrive_cluster(uint32_t bar, uint32_t cta) {
  asm volatile("{\n.reg .b32 ra;\nmapa.shared::cluster.u32 ra, %0, %1;\n"
               "mbarrier.arrive.shared::cluster.b64 _, [ra];\n}" ::"r"(bar), "r"(cta) : "memory");
}
__device__ __forceinline__ void mbar_wait(uint32_t bar, uint32_t parity) {
  uint32_t ok, n = 0;
  do {
    asm volatile("{\n.reg .pred p;\nmbarrier.try_wait.parity.shared::cta.b64 p, [%1], %2;\nselp.u32 %0, 1, 0, p;\n}"
                 : "=r"(ok) : "r"(bar), "r"(parity) : "memory");
  } while (!ok && ++n < SPIN_LIMIT);
}
__device__ __forceinline__ void mbar_wait_cluster(uint32_t bar, uint32_t parity) {
  uint32_t ok, n = 0;
  do {
    asm volatile("{\n.reg .pred p;\nmbarrier.try_wait.parity.acquire.cluster.shared::cta.b64 p, [%1], %2;\nselp.u32 %0, 1, 0, p;\n}"
                 : "=r"(ok) : "r"(bar), "r"(parity) : "memory");
  } while (!ok && ++n < SPIN_LIMIT);
}
__device__ __forceinline__ void tma2d(uint32_t dst, const CUtensorMap* m, int c0, int c1, uint32_t bar) {
  asm volatile("cp.async.bulk.tensor.2d.shared::cluster.global.mbarrier::complete_tx::bytes [%0], [%1, {%3, %4}], [%2];"
               ::"r"(dst), "l"(m), "r"(bar), "r"(c0), "r"(c1) : "memory");
}
__device__ __forceinline__ void tma3d(uint32_t dst, const CUtensorMap* m, int c0, int c1, int c2, uint32_t bar) {
  asm volatile("cp.async.bulk.tensor.3d.shared::cluster.global.mbarrier::complete_tx::bytes [%0], [%1, {%3, %4, %5}], [%2];"
               ::"r"(dst), "l"(m), "r"(bar), "r"(c0), "r"(c1), "r"(c2) : "memory");
}
__device__ __forceinline__ void tma2d_mc(uint32_t dst, const CUtensorMap* m, int c0, int c1, uint32_t bar) {
  asm volatile("cp.async.bulk.tensor.2d.shared::cluster.global.mbarrier::complete_tx::bytes.multicast::cluster [%0], [%1, {%3, %4}], [%2], %5;"
               ::"r"(dst), "l"(m), "r"(bar), "r"(c0), "r"(c1), "h"((uint16_t)3) : "memory");
}
__device__ __forceinline__ void tma3d_mc(uint32_t dst, const CUtensorMap* m, int c0, int c1, int c2, uint32_t bar) {
  asm volatile("cp.async.bulk.tensor.3d.shared::cluster.global.mbarrier::complete_tx::bytes.multicast::cluster [%0], [%1, {%3, %4, %5}], [%2], %6;"
               ::"r"(dst), "l"(m), "r"(bar), "r"(c0), "r"(c1), "r"(c2), "h"((uint16_t)3) : "memory");
}
__device__ __forceinline__ void bulk_g2s(uint32_t dst, const void* src, uint32_t bytes, uint32_t bar) {
  asm volatile("cp.async.bulk.shared::cluster.global.mbarrier::complete_tx::bytes [%0], [%1], %2, [%3];"
               ::"r"(dst), "l"(src), "r"(bytes), "r"(bar) : "memory");
}
__device__ __forceinline__ void bulk_s2g(void* dst, uint32_t src, uint32_t bytes) {
  asm volatile("cp.async.bulk.global.shared::cta.bulk_group [%0], [%1], %2;" ::"l"(dst), "r"(src), "r"(bytes) : "memory");
}
__device__ __forceinline__ void prefetch_tmap(const CUtensorMap* m) {
  asm volatile("prefetch.tensormap [%0];" ::"l"(m) : "memory");
}
__device__ __forceinline__ void l2_prefetch(const void* p, uint32_t bytes) {
  asm volatile("cp.async.bulk.prefetch.L2.global [%0], %1;" ::"l"(p), "r"(bytes) : "memory");
}
__device__ __forceinline__ void wg_fence() { asm volatile("wgmma.fence.sync.aligned;" ::: "memory"); }
__device__ __forceinline__ void wg_commit() { asm volatile("wgmma.commit_group.sync.aligned;" ::: "memory"); }
template <int N> __device__ __forceinline__ void wg_wait() { asm volatile("wgmma.wait_group.sync.aligned %0;" ::"n"(N) : "memory"); }
template <int N> __device__ __forceinline__ void fence_regs(float (&d)[N]) {
#pragma unroll
  for (int i = 0; i < N; i++) asm volatile("" : "+f"(d[i])::"memory");
}
template <int N> __device__ __forceinline__ void fence_regs(uint32_t (&d)[N]) {
#pragma unroll
  for (int i = 0; i < N; i++) asm volatile("" : "+r"(d[i])::"memory");
}
__device__ __forceinline__ void bar_sync(int id, int n) { asm volatile("bar.sync %0, %1;" ::"r"(id), "r"(n) : "memory"); }
__device__ __forceinline__ void bar_arrive(int id, int n) { asm volatile("bar.arrive %0, %1;" ::"r"(id), "r"(n) : "memory"); }
__device__ __forceinline__ void fence_gpu() { asm volatile("fence.acq_rel.gpu;" ::: "memory"); }
__device__ __forceinline__ void fence_async() { asm volatile("fence.proxy.async;" ::: "memory"); }
__device__ __forceinline__ void fence_async_smem() { asm volatile("fence.proxy.async.shared::cta;" ::: "memory"); }
__device__ __forceinline__ void red_add(uint32_t* p, uint32_t v) {
  asm volatile("red.relaxed.gpu.global.add.u32 [%0], %1;" ::"l"(p), "r"(v) : "memory");
}
__device__ __forceinline__ uint32_t ld_relaxed(const uint32_t* p) {
  uint32_t v;
  asm volatile("ld.relaxed.gpu.global.u32 %0, [%1];" : "=r"(v) : "l"(p) : "memory");
  return v;
}
__device__ __forceinline__ void wait_counter(const uint32_t* p, uint32_t target) {
  uint32_t v, n = 0;
  while (true) {
    asm volatile("ld.acquire.gpu.global.u32 %0, [%1];" : "=r"(v) : "l"(p) : "memory");
    if ((int32_t)(v - target) >= 0 || ++n > SPIN_LIMIT) break;
  }
}
__device__ __forceinline__ uint4 ld_relaxed(const uint4* p) {
  uint4 v;
  asm volatile("ld.relaxed.gpu.global.v4.u32 {%0, %1, %2, %3}, [%4];" : "=r"(v.x), "=r"(v.y), "=r"(v.z), "=r"(v.w) : "l"(p) : "memory");
  return v;
}
__device__ __forceinline__ void st_relaxed(uint4* p, uint4 v) {
  asm volatile("st.relaxed.gpu.global.v4.u32 [%0], {%1, %2, %3, %4};" ::"l"(p), "r"(v.x), "r"(v.y), "r"(v.z), "r"(v.w) : "memory");
}
__device__ __forceinline__ void st_relaxed(uint32_t* p, uint32_t v) {
  asm volatile("st.relaxed.gpu.global.u32 [%0], %1;" ::"l"(p), "r"(v) : "memory");
}
__device__ __forceinline__ uint32_t pack2(float lo, float hi) {
  uint32_t r;
  asm("cvt.rn.bf16x2.f32 %0, %1, %2;" : "=r"(r) : "f"(hi), "f"(lo));
  return r;
}
__device__ __forceinline__ uint32_t mul2(uint32_t a, uint32_t b) {
  uint32_t r;
  asm("mul.rn.bf16x2 %0, %1, %2;" : "=r"(r) : "r"(a), "r"(b));
  return r;
}
__device__ __forceinline__ uint32_t fma2(uint32_t a, uint32_t b, uint32_t c) {
  uint32_t r;
  asm("fma.rn.bf16x2 %0, %1, %2, %3;" : "=r"(r) : "r"(a), "r"(b), "r"(c));
  return r;
}
__device__ __forceinline__ uint32_t add2(uint32_t a, uint32_t b) {
  uint32_t r;
  asm("add.rn.bf16x2 %0, %1, %2;" : "=r"(r) : "r"(a), "r"(b));
  return r;
}
__device__ __forceinline__ uint32_t sub2(uint32_t a, uint32_t b) {
  uint32_t r;
  asm("sub.rn.bf16x2 %0, %1, %2;" : "=r"(r) : "r"(a), "r"(b));
  return r;
}
__device__ __forceinline__ uint32_t fms2(uint32_t a, uint32_t b, uint32_t c) {
  uint32_t r;
  asm("{\n.reg .b32 n;\nneg.bf16x2 n, %3;\nfma.rn.bf16x2 %0, %1, %2, n;\n}" : "=r"(r) : "r"(a), "r"(b), "r"(c));
  return r;
}
__device__ __forceinline__ float bf_lo(uint32_t v) { return __uint_as_float(v << 16); }
__device__ __forceinline__ float bf_hi(uint32_t v) { return __uint_as_float(v & 0xffff0000u); }
__device__ __forceinline__ float bf_round(float v) { return bf_lo(pack2(v, 0.f)); }
__device__ __forceinline__ float tanh_fast(float v) {
  float r;
  asm("tanh.approx.f32 %0, %1;" : "=f"(r) : "f"(v));
  return r;
}
__device__ __forceinline__ uint64_t mk_desc(uint32_t addr, uint32_t lbo, uint32_t sbo, uint32_t mode) {
  return (uint64_t)((addr & 0x3FFFF) >> 4) | ((uint64_t)(lbo >> 4) << 16) | ((uint64_t)(sbo >> 4) << 32) | ((uint64_t)mode << 62);
}
__device__ __forceinline__ void stmatrix_x4(uint32_t addr, uint32_t r0, uint32_t r1, uint32_t r2, uint32_t r3) {
  asm volatile("stmatrix.sync.aligned.m8n8.x4.shared.b16 [%0], {%1, %2, %3, %4};" ::"r"(addr), "r"(r0), "r"(r1), "r"(r2), "r"(r3) : "memory");
}

template <int TA, int TB>
__device__ __forceinline__ void wgmma_ss_n256(float (&d)[128], uint64_t da, uint64_t db, int sd) {
  asm volatile("{\n.reg .pred p;\nsetp.ne.b32 p, %130, 0;\n"
      "wgmma.mma_async.sync.aligned.m64n256k16.f32.bf16.bf16 {"
      "%0, %1, %2, %3, %4, %5, %6, %7, %8, %9, %10, %11, %12, %13, %14, %15, %16, %17, %18, %19, %20, %21, %22, %23, "
      "%24, %25, %26, %27, %28, %29, %30, %31, %32, %33, %34, %35, %36, %37, %38, %39, %40, %41, %42, %43, %44, %45, "
      "%46, %47, %48, %49, %50, %51, %52, %53, %54, %55, %56, %57, %58, %59, %60, %61, %62, %63, %64, %65, %66, %67, "
      "%68, %69, %70, %71, %72, %73, %74, %75, %76, %77, %78, %79, %80, %81, %82, %83, %84, %85, %86, %87, %88, %89, "
      "%90, %91, %92, %93, %94, %95, %96, %97, %98, %99, %100, %101, %102, %103, %104, %105, %106, %107, %108, %109, "
      "%110, %111, %112, %113, %114, %115, %116, %117, %118, %119, %120, %121, %122, %123, %124, %125, %126, %127"
      "}, %128, %129, p, 1, 1, %131, %132;\n}\n"
      : "+f"(d[0]), "+f"(d[1]), "+f"(d[2]), "+f"(d[3]), "+f"(d[4]), "+f"(d[5]), "+f"(d[6]), "+f"(d[7]), "+f"(d[8]),
        "+f"(d[9]), "+f"(d[10]), "+f"(d[11]), "+f"(d[12]), "+f"(d[13]), "+f"(d[14]), "+f"(d[15]), "+f"(d[16]),
        "+f"(d[17]), "+f"(d[18]), "+f"(d[19]), "+f"(d[20]), "+f"(d[21]), "+f"(d[22]), "+f"(d[23]), "+f"(d[24]),
        "+f"(d[25]), "+f"(d[26]), "+f"(d[27]), "+f"(d[28]), "+f"(d[29]), "+f"(d[30]), "+f"(d[31]), "+f"(d[32]),
        "+f"(d[33]), "+f"(d[34]), "+f"(d[35]), "+f"(d[36]), "+f"(d[37]), "+f"(d[38]), "+f"(d[39]), "+f"(d[40]),
        "+f"(d[41]), "+f"(d[42]), "+f"(d[43]), "+f"(d[44]), "+f"(d[45]), "+f"(d[46]), "+f"(d[47]), "+f"(d[48]),
        "+f"(d[49]), "+f"(d[50]), "+f"(d[51]), "+f"(d[52]), "+f"(d[53]), "+f"(d[54]), "+f"(d[55]), "+f"(d[56]),
        "+f"(d[57]), "+f"(d[58]), "+f"(d[59]), "+f"(d[60]), "+f"(d[61]), "+f"(d[62]), "+f"(d[63]), "+f"(d[64]),
        "+f"(d[65]), "+f"(d[66]), "+f"(d[67]), "+f"(d[68]), "+f"(d[69]), "+f"(d[70]), "+f"(d[71]), "+f"(d[72]),
        "+f"(d[73]), "+f"(d[74]), "+f"(d[75]), "+f"(d[76]), "+f"(d[77]), "+f"(d[78]), "+f"(d[79]), "+f"(d[80]),
        "+f"(d[81]), "+f"(d[82]), "+f"(d[83]), "+f"(d[84]), "+f"(d[85]), "+f"(d[86]), "+f"(d[87]), "+f"(d[88]),
        "+f"(d[89]), "+f"(d[90]), "+f"(d[91]), "+f"(d[92]), "+f"(d[93]), "+f"(d[94]), "+f"(d[95]), "+f"(d[96]),
        "+f"(d[97]), "+f"(d[98]), "+f"(d[99]), "+f"(d[100]), "+f"(d[101]), "+f"(d[102]), "+f"(d[103]), "+f"(d[104]),
        "+f"(d[105]), "+f"(d[106]), "+f"(d[107]), "+f"(d[108]), "+f"(d[109]), "+f"(d[110]), "+f"(d[111]),
        "+f"(d[112]), "+f"(d[113]), "+f"(d[114]), "+f"(d[115]), "+f"(d[116]), "+f"(d[117]), "+f"(d[118]),
        "+f"(d[119]), "+f"(d[120]), "+f"(d[121]), "+f"(d[122]), "+f"(d[123]), "+f"(d[124]), "+f"(d[125]),
        "+f"(d[126]), "+f"(d[127])
      : "l"(da), "l"(db), "r"(sd), "n"(TA), "n"(TB));
}
template <int TA, int TB>
__device__ __forceinline__ void wgmma_ss_n128(float (&d)[64], uint64_t da, uint64_t db, int sd) {
  asm volatile("{\n.reg .pred p;\nsetp.ne.b32 p, %66, 0;\n"
      "wgmma.mma_async.sync.aligned.m64n128k16.f32.bf16.bf16 {"
      "%0, %1, %2, %3, %4, %5, %6, %7, %8, %9, %10, %11, %12, %13, %14, %15, %16, %17, %18, %19, %20, %21, %22, %23, "
      "%24, %25, %26, %27, %28, %29, %30, %31, %32, %33, %34, %35, %36, %37, %38, %39, %40, %41, %42, %43, %44, %45, "
      "%46, %47, %48, %49, %50, %51, %52, %53, %54, %55, %56, %57, %58, %59, %60, %61, %62, %63"
      "}, %64, %65, p, 1, 1, %67, %68;\n}\n"
      : "+f"(d[0]), "+f"(d[1]), "+f"(d[2]), "+f"(d[3]), "+f"(d[4]), "+f"(d[5]), "+f"(d[6]), "+f"(d[7]), "+f"(d[8]),
        "+f"(d[9]), "+f"(d[10]), "+f"(d[11]), "+f"(d[12]), "+f"(d[13]), "+f"(d[14]), "+f"(d[15]), "+f"(d[16]),
        "+f"(d[17]), "+f"(d[18]), "+f"(d[19]), "+f"(d[20]), "+f"(d[21]), "+f"(d[22]), "+f"(d[23]), "+f"(d[24]),
        "+f"(d[25]), "+f"(d[26]), "+f"(d[27]), "+f"(d[28]), "+f"(d[29]), "+f"(d[30]), "+f"(d[31]), "+f"(d[32]),
        "+f"(d[33]), "+f"(d[34]), "+f"(d[35]), "+f"(d[36]), "+f"(d[37]), "+f"(d[38]), "+f"(d[39]), "+f"(d[40]),
        "+f"(d[41]), "+f"(d[42]), "+f"(d[43]), "+f"(d[44]), "+f"(d[45]), "+f"(d[46]), "+f"(d[47]), "+f"(d[48]),
        "+f"(d[49]), "+f"(d[50]), "+f"(d[51]), "+f"(d[52]), "+f"(d[53]), "+f"(d[54]), "+f"(d[55]), "+f"(d[56]),
        "+f"(d[57]), "+f"(d[58]), "+f"(d[59]), "+f"(d[60]), "+f"(d[61]), "+f"(d[62]), "+f"(d[63])
      : "l"(da), "l"(db), "r"(sd), "n"(TA), "n"(TB));
}
template <int TA, int TB>
__device__ __forceinline__ void wgmma_ss_n64(float (&d)[32], uint64_t da, uint64_t db, int sd) {
  asm volatile("{\n.reg .pred p;\nsetp.ne.b32 p, %34, 0;\n"
      "wgmma.mma_async.sync.aligned.m64n64k16.f32.bf16.bf16 {"
      "%0, %1, %2, %3, %4, %5, %6, %7, %8, %9, %10, %11, %12, %13, %14, %15, %16, %17, %18, %19, %20, %21, %22, %23, "
      "%24, %25, %26, %27, %28, %29, %30, %31"
      "}, %32, %33, p, 1, 1, %35, %36;\n}\n"
      : "+f"(d[0]), "+f"(d[1]), "+f"(d[2]), "+f"(d[3]), "+f"(d[4]), "+f"(d[5]), "+f"(d[6]), "+f"(d[7]), "+f"(d[8]),
        "+f"(d[9]), "+f"(d[10]), "+f"(d[11]), "+f"(d[12]), "+f"(d[13]), "+f"(d[14]), "+f"(d[15]), "+f"(d[16]),
        "+f"(d[17]), "+f"(d[18]), "+f"(d[19]), "+f"(d[20]), "+f"(d[21]), "+f"(d[22]), "+f"(d[23]), "+f"(d[24]),
        "+f"(d[25]), "+f"(d[26]), "+f"(d[27]), "+f"(d[28]), "+f"(d[29]), "+f"(d[30]), "+f"(d[31])
      : "l"(da), "l"(db), "r"(sd), "n"(TA), "n"(TB));
}
template <int SA, int TB>
__device__ __forceinline__ void wgmma_rs_n64(float (&d)[32], uint32_t a0, uint32_t a1, uint32_t a2, uint32_t a3, uint64_t db, int sd) {
  asm volatile("{\n.reg .pred p;\nsetp.ne.b32 p, %37, 0;\n"
      "wgmma.mma_async.sync.aligned.m64n64k16.f32.bf16.bf16 {"
      "%0, %1, %2, %3, %4, %5, %6, %7, %8, %9, %10, %11, %12, %13, %14, %15, %16, %17, %18, %19, %20, %21, %22, %23, "
      "%24, %25, %26, %27, %28, %29, %30, %31"
      "}, {%32, %33, %34, %35}, %36, p, %38, 1, %39;\n}\n"
      : "+f"(d[0]), "+f"(d[1]), "+f"(d[2]), "+f"(d[3]), "+f"(d[4]), "+f"(d[5]), "+f"(d[6]), "+f"(d[7]), "+f"(d[8]),
        "+f"(d[9]), "+f"(d[10]), "+f"(d[11]), "+f"(d[12]), "+f"(d[13]), "+f"(d[14]), "+f"(d[15]), "+f"(d[16]),
        "+f"(d[17]), "+f"(d[18]), "+f"(d[19]), "+f"(d[20]), "+f"(d[21]), "+f"(d[22]), "+f"(d[23]), "+f"(d[24]),
        "+f"(d[25]), "+f"(d[26]), "+f"(d[27]), "+f"(d[28]), "+f"(d[29]), "+f"(d[30]), "+f"(d[31])
      : "r"(a0), "r"(a1), "r"(a2), "r"(a3), "l"(db), "r"(sd), "n"(SA), "n"(TB));
}

__device__ __forceinline__ uint32_t BAR_FULL(uint32_t sb, int i) { return sb + SM_BAR + 8 * i; }
__device__ __forceinline__ uint32_t BAR_EMPTY(uint32_t sb, int i) { return sb + SM_BAR + 64 + 8 * i; }
__device__ __forceinline__ uint32_t BAR_X(uint32_t sb, int i) { return sb + SM_BAR + 128 + 8 * i; }
__device__ __forceinline__ uint32_t BAR_Y(uint32_t sb, int i) { return sb + SM_BAR + 192 + 8 * i; }
__device__ __forceinline__ uint32_t BAR_XFREE(uint32_t sb) { return sb + SM_BAR + 256; }

__device__ __forceinline__ uint32_t BAR_E2(uint32_t sb, int i) { return sb + SM_BAR + 264 + 8 * i; }
#define CMASK 0xd4u
#define XORDER 0, 1, 11, 2, 3, 12, 13, 4, 5, 14, 6, 15, 16
#define XSPREAD 2
#define PFAT 3
#define SKEW 3
#define EQW 38
#define EQA 37
#define SPREAD 1
#define WTID 32
#define GL1 0
#define GS0 2
#define GL2 6
#define GS1 4
constexpr int Q_G1B = 18, Q_G2 = 32, Q_XR = 39, Q_P3 = 46, Q_END = 50;

__device__ __forceinline__ uint32_t y_addr(int kb) { return kb < 3 ? SM_RING + (kb + (Q_G2 + 4) % NSTAGE) * STAGE_BYTES : SM_X + (kb - 3) * 16384; }
static_assert((Q_G2 + 4) % NSTAGE + 2 < NSTAGE, "");

struct Ring {
  uint32_t slot, phase;
  __device__ __forceinline__ void next() { if (++slot == NSTAGE) { slot = 0; phase ^= 1; } }
};

__device__ __forceinline__ void release_slot(uint32_t sb, uint32_t slot, int tid, int times) {
  if (tid < 2 * times) mbar_arrive_cluster(BAR_EMPTY(sb, slot), tid & 1);
}

__device__ __forceinline__ void ffn_consumer(uint32_t sb, const uint8_t* smem, const Params& p, int bid, int wg, int tid, int mt, int jj) {
  const int lane = tid & 31, warp = tid >> 5, q = lane & 3, r0 = 16 * warp + (lane >> 2);
  uint32_t* const my_epoch = &p.s->epoch[blockIdx.x * 12 + (threadIdx.x >> 5)];
  const uint32_t epoch = ld_relaxed(my_epoch) + 1;
  Ring rg{0, 0};
  uint32_t u[64];
  float acc[128];
  uint32_t prev = 0, cmask = CMASK;
  int st = 0;
  auto g1_stage = [&](uint32_t slot, int s) {
    const uint64_t da = mk_desc(sb + SM_X + (s >> 1) * 16384 + wg * 8192 + (s & 1) * 64, 16, 1024, 1);
    const uint64_t db = mk_desc(sb + SM_RING + slot * STAGE_BYTES, 4096, 1024, 1);
    wg_fence();
    wgmma_ss_n256<0, 1>(acc, da, db, s != 0);
    wgmma_ss_n256<0, 1>(acc, da + 2, db + 128, 1);
    wg_commit();
  };
  if (wg == 1) {
    float ap[64];
    constexpr int QX = 32 - __builtin_clz(CMASK);
    constexpr int NPRE = QX + XSPREAD;
    uint4* const x1dst = p.s->x1t + ((64 * jj + r0 + 8) >> 2) * 1024 + (r0 & 3) * 128 + 8 * mt + (q ^ (mt & 3));
    const int x1lo = 64 * jj + r0 == 1 ? 110 * 1024 - 128 : -2048;
#pragma unroll
    for (int qi = 0; qi < NPRE; qi++) {
      const int slot = qi % NSTAGE, nc = __builtin_popcount(CMASK & ((1u << qi) - 1));
      if (qi == 0) TL(60);
      mbar_wait(BAR_FULL(sb, slot), (qi / NSTAGE) & 1);
      if (qi == 0) TL(61);
      if ((CMASK >> qi) & 1) {
#pragma unroll
        for (int kb = 2 * nc; kb < 2 * nc + 2 && kb < 7; kb++) {
          const uint64_t da = mk_desc(sb + SM_RING + slot * STAGE_BYTES + (kb & 1) * 8192, 8192, 1024, 1);
          const uint64_t db = mk_desc(sb + SM_X + kb * 16384, 16, 1024, 1);
          mbar_wait(BAR_X(sb, kb), 0);
          TL(16 + kb);
          wg_fence();
#pragma unroll
          for (int kk = 0; kk < 4; kk++) wgmma_ss_n128<1, 0>(ap, da + kk * 128, db + kk * 2, (kb | kk) != 0);
          wg_commit();
        }
      } else {
        if (((qi - nc) & 1) == 0 && qi - nc >= 4 * nc) mbar_wait(BAR_X(sb, (qi - nc) >> 1), 0);
        TL(32 + qi - nc);
        g1_stage(slot, qi - nc);
      }
      if (qi > 0) {
        wg_wait<1>();
        release_slot(sb, (qi - 1) % NSTAGE, tid, ((CMASK >> (qi - 1)) & 1) ? 2 : 1);
      }
      if (qi >= QX) {
        if (qi == QX) { fence_regs(ap); TL(2); }
#pragma unroll
        for (int t = (qi - QX) * (4 / XSPREAD); t < (qi - QX + 1) * (4 / XSPREAD); t++)
#pragma unroll
        for (int h = 0; h < 2; h++)
          x1dst[(h ? 0 : x1lo) + 512 * (t & 1) + 4 * (t >> 1)] = make_uint4((pack2(ap[16 * t + 2 * h], ap[16 * t + 2 * h + 1]) & ~1u) | (epoch & 1), pack2(ap[16 * t + 4 + 2 * h], ap[16 * t + 5 + 2 * h]),
                                             pack2(ap[16 * t + 8 + 2 * h], ap[16 * t + 9 + 2 * h]), pack2(ap[16 * t + 12 + 2 * h], ap[16 * t + 13 + 2 * h]));
      }
    }
    bar_arrive(7, 160);
    st = NPRE - 4; cmask = 0; prev = (NPRE - 1) % NSTAGE;
    rg.slot = NPRE % NSTAGE; rg.phase = (NPRE / NSTAGE) & 1;
  }
#pragma unroll 1
  for (int pass = 0; pass < 2; pass++) {
#pragma unroll 1
    for (; st < 14; st++) {
      while (cmask & 1) { cmask >>= 1; rg.next(); }
      cmask >>= 1;
      if (pass == 0 && (st & 1) == 0) mbar_wait(BAR_X(sb, st >> 1), 0);
      if (st == 14 - SKEW && wg == 1) bar_sync(9 + pass, 256);
      mbar_wait(BAR_FULL(sb, rg.slot), rg.phase);
      TL(32 + 14 * pass + st);
      g1_stage(rg.slot, st);
      wg_wait<1>();
      if (st > 0) release_slot(sb, prev, tid, 1);
      prev = rg.slot;
      rg.next();
    }
    st = 0;
    if (wg == 0) bar_arrive(9 + pass, 256);
    wg_wait<0>();
    fence_regs(acc);
    release_slot(sb, prev, tid, 1);
    TL(3 + 2 * pass);
#pragma unroll
    for (int i = 0; i < 32; i++) {
      const float g0 = 0.5f * acc[2 * i], g1 = 0.5f * acc[2 * i + 1];
      const float s0 = fmaf(g0, tanh_fast(g0), g0), s1 = fmaf(g1, tanh_fast(g1), g1);
      u[32 + i] = pack2(s0 * acc[64 + 2 * i], s1 * acc[64 + 2 * i + 1]);
    }
    if (pass == 0) {
#pragma unroll
      for (int i = 0; i < 32; i++) u[i] = u[32 + i];
    }
    TL(4 + 2 * pass);
  }
  fence_regs(u);
  float accA[32], accB[32];
  auto stage = [&](float (&acc)[32], int qi) {
    const int st = qi & 1;
    if (qi == EQW && wg == 0) bar_sync(1, 256);
    if (qi < Q_XR) mbar_wait(BAR_FULL(sb, qi % NSTAGE), (qi / NSTAGE) & 1);
    else mbar_wait(BAR_X(sb, qi - Q_XR), 1);
    const uint64_t db = mk_desc(sb + (qi < Q_XR ? SM_RING + (qi % NSTAGE) * STAGE_BYTES : SM_X + (qi - Q_XR) * 16384), 8192, 1024, 1);
    wg_fence();
#pragma unroll
    for (int kk = 0; kk < 8; kk++) {
      const uint32_t* a = u + 32 * st + 4 * kk;
      wgmma_rs_n64<1, 1>(acc, a[0], a[1], a[2], a[3], db + kk * 128, (st | kk) != 0);
    }
    wg_commit();
    if (qi == EQA && wg == 1) bar_arrive(1, 256);
  };
  auto retire = [&](int qi) {
    wg_wait<1>();
    if (qi >= Q_G2 && qi < Q_G2 + 4) release_slot(sb, qi % NSTAGE, tid, 1);
    else if (qi >= Q_G2 + 4 && qi < Q_G2 + 11 && tid == 0) mbar_arrive(BAR_E2(sb, qi - Q_G2 - 4));
  };
  const uint32_t par = epoch & 1;
  auto put = [&](float (&acc)[32], int c) {
    fence_regs(acc);
    int o = jj + 1 + c;
    if (o >= 7) o -= 7;
    uint4* dst = p.s->part + ((((mt * 7 + o) * 6 + c) * 2 + wg) * 4) * 128 + tid;
#pragma unroll
    for (int v = 0; v < 4; v++) {
      const float* a = acc + 8 * v;
      st_relaxed(dst + v * 128, make_uint4((pack2(a[0], a[1]) & ~1u) | par, pack2(a[2], a[3]), pack2(a[4], a[5]), pack2(a[6], a[7])));
    }
  };
  const uint4* const src = p.s->part + (((mt * 7 + jj) * 6 * 2 + wg) * 4) * 128 + tid;
  auto gload = [&](uint4 (&pv)[8], int c) {
#pragma unroll
    for (int i = 0; i < 8; i++) pv[i] = ld_relaxed(src + ((2 * c + (i >> 2)) * 8 + (i & 3)) * 128);
  };
  auto gload1 = [&](uint4 (&pv)[8], int c) {
#pragma unroll
    for (int i = 0; i < 4; i++) pv[4 * (c & 1) + i] = ld_relaxed(src + (c * 8 + i) * 128);
  };
  auto gsum = [&](uint4 (&pv)[8], int c) {
#pragma unroll 1
    for (uint32_t n = 0; n < SPIN_LIMIT; n++) {
      uint32_t bad = 0;
#pragma unroll
      for (int i = 0; i < 8; i++) bad |= pv[i].x ^ par;
      if (!__any_sync(0xffffffffu, bad & 1)) break;
      gload(pv, c);
    }
    TL(24 + c);
#pragma unroll
    for (int i = 0; i < 8; i++) {
      const float t[8] = {bf_lo(pv[i].x), bf_hi(pv[i].x), bf_lo(pv[i].y), bf_hi(pv[i].y), bf_lo(pv[i].z), bf_hi(pv[i].z), bf_lo(pv[i].w), bf_hi(pv[i].w)};
#pragma unroll
      for (int k = 0; k < 8; k++) accA[8 * (i & 3) + k] += t[k];
    }
  };
  uint4 pv0[8], pv1[8], pv2[8];
  const int row = 128 * mt + 64 * wg + r0;
  uint32_t gt0, gt1;
#pragma unroll
  for (int c2 = 0; c2 < 4; c2++) {
    const int qi = Q_G2 + 4 * c2;
    stage(accA, qi);
    retire(qi - 1);
    stage(accA, qi + 1);
    if (c2 == 3) TL(27);
    if (c2 > 0) put(accB, 2 * c2 - 1);
    if (c2 == 2) gload1(pv0, 1);
    if (c2 == 3) gload1(pv1, 3);
    TL(7 + c2);
    if (c2 == 3) break;
    retire(qi);
    stage(accB, qi + 2);
    retire(qi + 1);
    stage(accB, qi + 3);
    put(accA, 2 * c2);
    if (c2 == 1) gload1(pv0, 0);
    if (c2 == 2) gload1(pv1, 2);
    if (c2 == 0) { gt0 = ld_relaxed(&p.s->gate[row]); gt1 = ld_relaxed(&p.s->gate[row + 8]); }
    retire(qi + 2);
  }
#pragma unroll
  for (int kb = 0; kb < 7; kb++) {
    const int qt = Q_XR + (kb >> 1);
    if ((kb & 1) == 0) mbar_wait(BAR_FULL(sb, qt % NSTAGE), (qt / NSTAGE) & 1);
    mbar_wait(BAR_Y(sb, kb), 0);
    const uint64_t da = mk_desc(sb + y_addr(kb) + wg * 8192, 8192, 1024, 1);
    const uint64_t db = mk_desc(sb + SM_RING + (qt % NSTAGE) * STAGE_BYTES + (kb & 1) * 8192, 16, 1024, 1);
    wg_fence();
#pragma unroll
    for (int kk = 0; kk < 4; kk++) wgmma_ss_n64<1, 0>(accB, da + kk * 128, db + kk * 2, (kb | kk) != 0);
    wg_commit();
    if (kb == 1) { wg_wait<2>(); fence_regs(accA); TL(15); }
    if (kb == GS0) gsum(pv0, 0);
    if (kb == GL2) gload(pv2, 2);
    if (kb == GS1) gsum(pv1, 1);
  }
  TL(11);
  for (uint32_t n = 0; (((gt0 ^ epoch) | (gt1 ^ epoch)) & 0xffffu) && n < SPIN_LIMIT; n++) {
    gt0 = ld_relaxed(&p.s->gate[row]); gt1 = ld_relaxed(&p.s->gate[row + 8]);
  }
  gsum(pv2, 2);
  const float ga0 = bf_hi(gt0), ga1 = bf_hi(gt1);
  TL(12);
  wg_wait<0>();
  fence_regs(accB);
  TL(13);
  const float gb0 = bf_round(1.f - ga0), gb1 = bf_round(1.f - ga1);
  const float gs0 = ga0 * (2.f / (float)(S_ * D_)), gs1 = ga1 * (2.f / (float)(S_ * D_));
  uint4* const o = reinterpret_cast<uint4*>(p.out + (size_t)row * D_ + 64 * jj + 8 * q);
#pragma unroll
  for (int h = 0; h < 2; h++) {
    const float gs = h ? gs1 : gs0, gb = h ? gb1 : gb0;
#pragma unroll
    for (int k = 0; k < 2; k++) {
      uint32_t w[4];
#pragma unroll
      for (int j = 0; j < 4; j++) {
        const int i = 16 * k + 4 * j + 2 * h;
        w[j] = pack2(fmaf(gs, accB[i], gb * accA[i]), fmaf(gs, accB[i + 1], gb * accA[i + 1]));
      }
      const bool o1 = q & 1, o2 = q & 2;
      uint32_t a = __shfl_xor_sync(0xffffffffu, o1 ? w[0] : w[1], 1), b = __shfl_xor_sync(0xffffffffu, o1 ? w[2] : w[3], 1);
      if (o1) { w[0] = a; w[2] = b; } else { w[1] = a; w[3] = b; }
      a = __shfl_xor_sync(0xffffffffu, o2 ? w[0] : w[2], 2); b = __shfl_xor_sync(0xffffffffu, o2 ? w[1] : w[3], 2);
      if (o2) { w[0] = a; w[1] = b; } else { w[2] = a; w[3] = b; }
      o[h * D_ + 4 * k] = make_uint4(w[0], w[1], w[2], w[3]);
    }
  }
  if (lane == 0) *my_epoch = epoch;
  TL(14);
}

__device__ __forceinline__ void ring_issue(uint32_t sb, const Params& p, int qi, uint32_t slot, bool wait, uint32_t phase, int jj, uint32_t rank) {
  const CUtensorMap* m;
  int c0, c1, c2 = 0;
  bool half = false, is3d = false;
  if (qi < Q_G2) {
    const int nc = __popc(CMASK & ((1u << qi) - 1));
    if ((CMASK >> qi) & 1) {
      m = &p.ct; c0 = 64 * jj; c1 = 128 * nc + 64 * rank; half = nc == 3;
    } else {
      const int pass = qi >= Q_G1B;
      m = rank ? &p.wu : &p.wg; c0 = 0; c1 = 32 * (qi - nc - 14 * pass); c2 = 4 * jj + 2 * pass; is3d = true;
    }
  } else if (qi < Q_P3) {
    int o = jj + 1 + ((qi - Q_G2) >> 1);
    if (o >= 7) o -= 7;
    m = &p.wd; c0 = 64 * o; c1 = 256 * jj + 128 * (qi & 1) + 64 * rank;
  } else {
    m = &p.ct; c0 = 128 * (qi - Q_P3) + 64 * rank; c1 = 64 * jj; half = qi == Q_END - 1;
  }
  uint32_t bar = BAR_FULL(sb, slot), dst = sb + SM_RING + slot * STAGE_BYTES + rank * 8192;
  if (qi >= Q_XR && qi < Q_P3) {
    bar = BAR_X(sb, qi - Q_XR); dst = sb + SM_X + (qi - Q_XR) * 16384 + rank * 8192;
    if (qi == Q_XR) mbar_wait_cluster(BAR_XFREE(sb), 0);
  } else {
    if (wait) mbar_wait_cluster(BAR_EMPTY(sb, slot), phase ^ (qi >= Q_P3));
    mbar_expect_tx(bar, half ? 8192 : 16384);
  }
  if (is3d) tma3d_mc(dst, m, c0, c1, c2, bar);
  else if (!(half && rank)) tma2d_mc(dst, m, c0, c1, bar);
}

__device__ __forceinline__ void ffn_producer(uint32_t sb, const uint8_t* smem, int bid, const Params& p, int warp, int lane, int mt, int jj, uint32_t rank) {
  if (warp < 2) {
    if (lane == 0) {
      uint32_t slot = warp, phase = 0;
#pragma unroll 1
      for (int qi = NSTAGE + warp; qi < Q_END; qi += 2) {
        if (qi < Q_XR || qi >= Q_P3) ring_issue(sb, p, qi, slot, true, phase, jj, rank);
        if (warp == 1 && qi >= Q_G1B + 8 && qi < Q_XR) ring_issue(sb, p, Q_XR + ((qi - Q_G1B - 8) >> 1), 0, false, 0, jj, rank);
        TL(10 + qi);
        slot += 2;
        if (slot >= NSTAGE) { slot -= NSTAGE; phase ^= 1; }
      }
    }
  } else {
    const int wg = warp - 2;
    uint32_t* const my_epoch = &p.s->epoch[blockIdx.x * 12 + 8 + warp];
    const uint32_t epoch = ld_relaxed(my_epoch) + 1;
    if (wg == 0) {
      if (lane == 0) { prefetch_tmap(&p.wd); prefetch_tmap(&p.yt); }
      {
        const uint4* gw4 = reinterpret_cast<const uint4*>(p.gate_w);
        const uint4 ga = __ldg(gw4 + lane), gb = lane < 24 ? __ldg(gw4 + 32 + lane) : make_uint4(0, 0, 0, 0);
        if (lane < 7) { mbar_wait(BAR_X(sb, lane), 0); mbar_expect_tx(BAR_X(sb, lane), 16384); mbar_expect_tx(BAR_Y(sb, lane), 16384); }
        __syncwarp();
        float mine = 0.f;
#pragma unroll 1
        for (int u = 0; u < 19; u++) {
          const int r = min(19 * jj + u, 127);
          const uint8_t* xr = smem + SM_X + (lane >> 3) * 16384 + r * 128 + (((lane ^ r) & 7) << 4);
          const uint4 xa = *reinterpret_cast<const uint4*>(xr);
          const uint4 xb = lane < 24 ? *reinterpret_cast<const uint4*>(xr + 65536) : make_uint4(0, 0, 0, 0);
          float s = 0.f;
          auto dot2 = [&](uint32_t a, uint32_t b) {
            const uint32_t pr = mul2(a, b);
            s += bf_lo(pr) + bf_hi(pr);
          };
          dot2(xa.x, ga.x); dot2(xa.y, ga.y); dot2(xa.z, ga.z); dot2(xa.w, ga.w);
          dot2(xb.x, gb.x); dot2(xb.y, gb.y); dot2(xb.z, gb.z); dot2(xb.w, gb.w);
#pragma unroll
          for (int o = 16; o > 0; o >>= 1) s += __shfl_xor_sync(0xffffffffu, s, o);
          if (lane == u) mine = s;
        }
        if (lane < 19 && 19 * jj + lane < 128)
          st_relaxed(&p.s->gate[128 * mt + 19 * jj + lane], pack2(0.f, 1.f / (1.f + __expf(-bf_round(mine)))) | (epoch & 0xffffu));
      }
      TL(9);
      if (lane < 2) mbar_arrive_cluster(BAR_XFREE(sb), lane);
    } else {
      mbar_wait(BAR_X(sb, PFAT), 0);
      if (lane < 6) {
        int row = 176 + 3 * bid + (lane >> 1);
        if (row >= D_) row -= D_;
        l2_prefetch(((lane & 1) ? p.pwu : p.pwg) + row * F_, F_ * 2);
      }
      TL(2);
      bar_sync(7, 160);
      if (lane == 0) { red_add(&p.s->cnt_x1[jj * 32], 1);
        l2_prefetch(p.pwd + bid * 16 * D_, 32 * D_); }
      TL(5);
    }
    mbar_wait(BAR_E2(sb, 0), 0);
    TL(3);
    const int kb = 2 * lane + wg;
    bool todo = kb < 7, ready = false;
    uint32_t n = 0;
    while (__any_sync(0xffffffffu, todo)) {
      if (todo) {
        uint32_t ok;
        if (!ready) {
          asm volatile("ld.acquire.gpu.global.u32 %0, [%1];" : "=r"(ok) : "l"(&p.s->cnt_y[kb * 32]) : "memory");
          ready = (int32_t)(ok - epoch * (kb ? 16 : 17)) >= 0;
        }
        asm volatile("{\n.reg .pred p;\nmbarrier.test_wait.parity.shared::cta.b64 p, [%1], 0;\nselp.u32 %0, 1, 0, p;\n}"
                     : "=r"(ok) : "r"(BAR_E2(sb, kb)) : "memory");
        if ((ok && ready) || ++n > SPIN_LIMIT) {
          tma3d(sb + y_addr(kb), &p.yt, 0, 64 * kb, 2 * mt, BAR_Y(sb, kb));
          todo = false;
        }
      }
      __nanosleep(40);
    }
    TL(4);
    if (lane == 0) *my_epoch = epoch;
  }
}

__device__ __forceinline__ void spectral_cta(uint32_t sb, uint8_t* smem, const Params& p, int sc, int wg) {
  const int t384 = threadIdx.x, lane = t384 & 31, warp12 = t384 >> 5, tid = t384 & 127;
  const int warp = tid >> 5, q = lane & 3;
  const int sl0 = 6 * sc + min(sc, 8), nsl = sc < 8 ? 7 : 6;
  if (t384 == 320) {
#pragma unroll 1
    for (int i = 0; i < nsl; i++) {
      mbar_expect_tx(BAR_X(sb, i), 2 * SLAB_BYTES);
      const int row = 128 * ((sl0 + i) >> 3) + 8 * ((sl0 + i) & 7);
      const uint32_t dst = sb + SP_Z + 2 * i * SLAB_BYTES;
      bulk_g2s(dst, p.w_r + row * DF_, SLAB_BYTES / 2, BAR_X(sb, i));
      bulk_g2s(dst + SLAB_BYTES / 2, p.w_r + (row + 64) * DF_, SLAB_BYTES / 2, BAR_X(sb, i));
      bulk_g2s(dst + SLAB_BYTES, p.w_i + row * DF_, SLAB_BYTES / 2, BAR_X(sb, i));
      bulk_g2s(dst + 3 * SLAB_BYTES / 2, p.w_i + (row + 64) * DF_, SLAB_BYTES / 2, BAR_X(sb, i));
    }
    if (sc < 19) {
      mbar_expect_tx(BAR_Y(sb, 6), 24576);
      bulk_g2s(sb + SP_TW, p.spec, 24576, BAR_Y(sb, 6));
    }
  }
  uint32_t* const my_epoch = &p.s->epoch[blockIdx.x * 12 + warp12];
  const uint32_t epoch = ld_relaxed(my_epoch) + 1;
  uint32_t fe[16], tw[16];
#pragma unroll
  for (int i = 0; i < 4; i++) {
    const uint4 a = __ldg(reinterpret_cast<const uint4*>(p.spec->fe) + i * 128 + tid);
    const uint4 b = __ldg(reinterpret_cast<const uint4*>(p.spec->tw) + i * 128 + tid);
    fe[4 * i] = a.x; fe[4 * i + 1] = a.y; fe[4 * i + 2] = a.z; fe[4 * i + 3] = a.w;
    tw[4 * i] = b.x; tw[4 * i + 1] = b.y; tw[4 * i + 2] = b.z; tw[4 * i + 3] = b.w;
  }
  __syncwarp();
  asm volatile("barrier.cluster.wait.acquire.aligned;" ::: "memory");
#pragma unroll 2
  for (int un = wg; un < 8 * nsl; un += 3) {
    const int i = un >> 3, sl = sl0 + i, pr = 16 * (un & 7) + 4 * (lane >> 3) + warp, r = lane & 7;
    mbar_wait(BAR_X(sb, i), 0);
    if (pr < 113) {
      const uint16_t* w = reinterpret_cast<const uint16_t*>(smem + SP_Z + 2 * i * SLAB_BYTES) + r * DF_ + 2 * pr;
      const uint32_t m = pr < 112 ? 0xffffffffu : 0u;
      p.s->wt[pr * 1024 + sl * 8 + (r ^ ((sl >> 2) & 6))] =
          make_uint4(w[0] | ((uint32_t)w[8 * DF_] << 16), w[16 * DF_] | ((uint32_t)w[24 * DF_] << 16),
                     (w[1] | ((uint32_t)w[8 * DF_ + 1] << 16)) & m, (w[16 * DF_ + 1] | ((uint32_t)w[24 * DF_ + 1] << 16)) & m);
    }
  }
  __syncthreads();
  if (t384 == 352) { fence_gpu(); red_add(&p.s->cnt_w[0], 1); TL(2); }
  TL(1);
  if (sc == 19) return;
  const int nrnd = (sc == 18 && wg == 2) ? 1 : 2;
  if (lane < nrnd && warp < 2) {
    const int item = wg + 3 * lane, pr = 6 * sc + item;
    const uint32_t bar = warp ? BAR_Y(sb, item) : BAR_FULL(sb, item);
    mbar_expect_tx(bar, 16384);
    wait_counter(warp ? &p.s->cnt_w[0] : &p.s->cnt_x1[(pr < 112 ? pr >> 4 : 0) * 32], epoch * (warp ? NSPEC : 16));
    if (warp) fence_async();
    bulk_g2s(sb + (warp ? SP_W : SP_Z) + item * 16384, (warp ? p.s->wt : p.s->x1t) + pr * 1024, 16384, bar);
  }
  __syncwarp();
  fence_regs(fe); fence_regs(tw);
  mbar_wait(BAR_Y(sb, 6), 0);
  TL(3);
  const uint64_t dT_n = mk_desc(sb + SP_T, 8192, 1024, 1);
#pragma unroll 1
  for (int rnd = 0; rnd < nrnd; rnd++) {
    const int item = wg + 3 * rnd, pr = 6 * sc + item;
    const uint32_t z = sb + SP_Z + item * 16384;
    uint32_t fa[16], fb[16];
    auto load_frag = [&](int off) {
#pragma unroll
      for (int i = 0; i < 4; i++) {
        const uint4 a = *reinterpret_cast<const uint4*>(smem + SP_TW + off + i * 2048 + tid * 16);
        fa[4 * i] = a.x; fa[4 * i + 1] = a.y; fa[4 * i + 2] = a.z; fa[4 * i + 3] = a.w;
      }
      fence_regs(fa);
    };
    load_frag(0);
    {
      const uint32_t live = pr == 0 ? 0xddu : (pr == 112 ? 0x11u : 0xffu);
#pragma unroll 1
      for (uint32_t n = 0; n < 4096; n++) {
        mbar_wait(BAR_FULL(sb, item), n & 1);
        uint32_t bad = 0;
#pragma unroll
        for (int i = 0; i < 8; i++) bad |= ((*reinterpret_cast<const volatile uint32_t*>(smem + SP_Z + item * 16384 + i * 2048 + tid * 16) ^ epoch) & 1) << i;
        uint32_t again;
        asm volatile("{\n.reg .pred p, q;\nsetp.ne.u32 p, %1, 0;\nbarrier.red.or.pred q, %2, 128, p;\nselp.u32 %0, 1, 0, q;\n}"
                     : "=r"(again) : "r"(bad & live), "r"(1 + wg) : "memory");
        if (!again) break;
        TL(20);
        if (tid == 0) { mbar_expect_tx(BAR_FULL(sb, item), 16384); bulk_g2s(z, p.s->x1t + pr * 1024, 16384, BAR_FULL(sb, item)); }
      }
    }
    TL(4 + 8 * rnd);
    if (rnd == 0 && wg > 0) bar_sync(3 + wg, 256);
    float aR[32], aI[32];
    {
      const uint64_t de = mk_desc(z, 4096, 512, 2);
      wg_fence();
#pragma unroll
      for (int kk = 0; kk < 4; kk++) {
        wgmma_rs_n64<1, 1>(aR, fe[4 * kk], fe[4 * kk + 1], fe[4 * kk + 2], fe[4 * kk + 3], de + kk * 64, kk != 0);
        wgmma_rs_n64<1, 1>(aI, fa[4 * kk], fa[4 * kk + 1], fa[4 * kk + 2], fa[4 * kk + 3], de + 512 + kk * 64, kk != 0);
      }
      wg_commit();
      if (rnd == 0 && wg < 2) bar_arrive(4 + wg, 256);
      wg_wait<0>();
      fence_regs(aR); fence_regs(aI);
    }
    TL(5 + 8 * rnd);
#pragma unroll
    for (int v = 0; v < 8; v++) {
      uint32_t* f = (v < 4 ? fa : fb) + 2 * (v & 3);
      const uint32_t* t = tw + 2 * (v & 3);
      const float *e = aR + 4 * v, *o = aI + 4 * v;
      const uint32_t er = pack2(e[0], e[1]), ei = pack2(e[2], e[3]), qr = pack2(o[0], o[1]), qi = pack2(o[2], o[3]);
      const uint32_t u0r = add2(er, qr), u0i = add2(ei, qi), u1r = sub2(er, qr), u1i = sub2(ei, qi);
      f[0] = fma2(u0r, t[0], mul2(u0i, t[8]));
      f[8] = fms2(u0i, t[0], mul2(u0r, t[8]));
      f[1] = fma2(u1r, t[1], mul2(u1i, t[9]));
      f[9] = fms2(u1i, t[1], mul2(u1r, t[9]));
    }
    fence_regs(fa); fence_regs(fb);
    wg_fence();
#pragma unroll
    for (int kk = 0; kk < 4; kk++) {
      wgmma_rs_n64<1, 1>(aR, fa[4 * kk], fa[4 * kk + 1], fa[4 * kk + 2], fa[4 * kk + 3], dT_n + kk * 128, kk != 0);
      wgmma_rs_n64<1, 1>(aI, fb[4 * kk], fb[4 * kk + 1], fb[4 * kk + 2], fb[4 * kk + 3], dT_n + kk * 128, kk != 0);
    }
    wg_commit();
    mbar_wait(BAR_Y(sb, item), 0);
    wg_wait<0>();
    fence_regs(aR); fence_regs(aI);
    TL(6 + 8 * rnd);
    {
      const uint8_t* wp = smem + SP_W + item * 16384 + q * 1024 + warp * 128 + (((lane >> 2) ^ (2 * q)) << 4);
#pragma unroll
      for (int jb = 0; jb < 4; jb++) {
#pragma unroll
        for (int h = 0; h < 2; h++) {
          const uint4 w = *reinterpret_cast<const uint4*>(wp + jb * 4096 + h * 512);
          const int i = 4 * jb + 2 * h;
          const uint32_t ar = pack2(aR[i], aR[i + 1]), ai = pack2(aR[16 + i], aR[17 + i]);
          const uint32_t br = pack2(aI[i], aI[i + 1]), bi = pack2(aI[16 + i], aI[17 + i]);
          fa[2 * jb + h] = fms2(ar, w.x, mul2(ai, w.y));
          fa[8 + 2 * jb + h] = fma2(ar, w.y, mul2(ai, w.x));
          fb[2 * jb + h] = fms2(br, w.z, mul2(bi, w.w));
          fb[8 + 2 * jb + h] = fma2(br, w.w, mul2(bi, w.z));
        }
      }
    }
    fence_regs(fa); fence_regs(fb);
    wg_fence();
#pragma unroll
    for (int kk = 0; kk < 4; kk++) {
      wgmma_rs_n64<1, 0>(aR, fa[4 * kk], fa[4 * kk + 1], fa[4 * kk + 2], fa[4 * kk + 3], dT_n + kk * 2, kk != 0);
      wgmma_rs_n64<1, 0>(aI, fb[4 * kk], fb[4 * kk + 1], fb[4 * kk + 2], fb[4 * kk + 3], dT_n + kk * 2, kk != 0);
    }
    wg_commit();
    wg_wait<0>();
    fence_regs(aR); fence_regs(aI);
    TL(7 + 8 * rnd);
#pragma unroll
    for (int v = 0; v < 8; v++) {
      const float* a = (v < 4 ? aR : aI) + 4 * (v & 3);
      const uint32_t* t = tw + 2 * (v & 3);
      const uint32_t u0r = pack2(a[0], a[1]), u1r = pack2(a[2], a[3]), u0i = pack2(a[16], a[17]), u1i = pack2(a[18], a[19]);
      const uint32_t t0r = fms2(u0r, t[0], mul2(u0i, t[8])), t0i = fma2(u0i, t[0], mul2(u0r, t[8]));
      const uint32_t t1r = fms2(u1r, t[1], mul2(u1i, t[9])), t1i = fma2(u1i, t[1], mul2(u1r, t[9]));
      fa[v] = add2(t0i, t1i); fa[8 + v] = add2(t0r, t1r);
      fb[v] = sub2(t0i, t1i); fb[8 + v] = sub2(t0r, t1r);
    }
    bar_sync(1 + wg, 128);
#pragma unroll
    for (int u = 0; u < 4; u++) {
      const uint32_t a = z + (32 * (u >> 1) + 8 * warp + (lane & 7)) * 128 + (((4 * (u & 1) + (lane >> 3)) ^ (lane & 7)) << 4);
      stmatrix_x4(a, fa[4 * u], fa[4 * u + 1], fa[4 * u + 2], fa[4 * u + 3]);
      stmatrix_x4(a + 8192, fb[4 * u], fb[4 * u + 1], fb[4 * u + 2], fb[4 * u + 3]);
    }
    load_frag(8192);
    fence_async_smem();
    bar_sync(1 + wg, 128);
    TL(8 + 8 * rnd);
    {
      const uint64_t de = mk_desc(z, 8192, 1024, 1);
      wg_fence();
#pragma unroll
      for (int kk = 0; kk < 4; kk++) {
        wgmma_rs_n64<1, 1>(aR, fe[4 * kk], fe[4 * kk + 1], fe[4 * kk + 2], fe[4 * kk + 3], de + kk * 128, kk != 0);
        wgmma_rs_n64<1, 1>(aI, fa[4 * kk], fa[4 * kk + 1], fa[4 * kk + 2], fa[4 * kk + 3], de + 512 + kk * 128, kk != 0);
      }
      wg_commit();
      wg_wait<0>();
      fence_regs(aR); fence_regs(aI);
    }
    TL(9 + 8 * rnd);
    const bool edge = pr == 0 || pr == 112;
    if (edge) {
#pragma unroll
      for (int i = 0; i < 16; i++) { aR[i] *= 0.5f; aI[i] *= 0.5f; }
    }
#pragma unroll
    for (int i = 0; i < 8; i++) {
      const float* a = ((i & 1) ? aI : aR) + 16 * (i >> 2) + 2 - (i & 2);
      *reinterpret_cast<uint4*>(smem + SP_W + item * 16384 + (i >> 1) * 4096 + (i & 1) * 64 + (tid >> 2) * 128 + q * 16) =
          make_uint4(pack2(a[0], a[1]), pack2(a[4], a[5]), pack2(a[8], a[9]), pack2(a[12], a[13]));
    }
    fence_async_smem();
    bar_sync(1 + wg, 128);
    if (tid == 0) {
      const uint32_t src = sb + SP_W + item * 16384;
      __nv_bfloat16* dst = p.s->yt + (size_t)(pr < 112 ? 4 * pr : 1) * S_;
      bulk_s2g(dst, src, edge ? 4096 : 16384);
      if (pr == 0) bulk_s2g(dst + 2 * S_, src + 8192, 8192);
      asm volatile("cp.async.bulk.commit_group;" ::: "memory");
      if (rnd == nrnd - 1) {
        asm volatile("cp.async.bulk.wait_group 0;" ::: "memory");
        TL(11);
        red_add(&p.s->cnt_y[(pr < 112 ? pr >> 4 : 0) * 32], 1);
        if (rnd) red_add(&p.s->cnt_y[((pr - 3) >> 4) * 32], 1);
      }
    }
    __syncwarp();
    TL(10 + 8 * rnd);
  }
  if (lane == 0) *my_epoch = epoch;
}

__global__ void __cluster_dims__(2, 1, 1) __launch_bounds__(384, 1)
fused_kernel(const __grid_constant__ Params p) {
  extern __shared__ __align__(1024) uint8_t smem[];
  const uint32_t sb = smem_u32(smem);
  TL(0);
  const uint32_t rank = blockIdx.x & 1;
  const int hc = blockIdx.x >> 1;
  int grp, jj;
  if (hc < 4) { grp = 8; jj = hc; }
  else if (hc < 36) { grp = (hc - 4) & 7; jj = (hc - 4) >> 3; }
  else if (hc < 57) { jj = (hc - 36) / 7; grp = 1 + (hc - 36) - 7 * jj; jj += 4; }
  else if (hc < 60) { grp = 0; jj = hc - 53; }
  else { grp = 8; jj = hc - 56; }
  const int mt = 2 * grp + rank, bid = 2 * (7 * grp + jj) + rank;
  if (threadIdx.x == 256) {
#pragma unroll
    for (int i = 0; i < NSTAGE; i++) { mbar_init(BAR_FULL(sb, i), 1); mbar_init(BAR_EMPTY(sb, i), 4); }
    asm volatile("fence.mbarrier_init.release.cluster;" ::: "memory");
  } else if (threadIdx.x == 320) {
#pragma unroll
    for (int i = 0; i < NSTAGE; i++) { mbar_init(BAR_X(sb, i), 1); mbar_init(BAR_Y(sb, i), 1); }
    mbar_init(BAR_XFREE(sb), 2);
#pragma unroll
    for (int i = 0; i < 7; i++) mbar_init(BAR_E2(sb, i), 2);
    asm volatile("fence.mbarrier_init.release.cluster;" ::: "memory");
  } else if (threadIdx.x == 288) {
    prefetch_tmap(rank ? &p.wu : &p.wg); prefetch_tmap(&p.ct);
  }
  __syncwarp();
  asm volatile("barrier.cluster.arrive.relaxed.aligned;" ::: "memory");
  const int wg = __shfl_sync(0xffffffffu, threadIdx.x >> 7, 0);
  if (bid >= NFFN) {
    spectral_cta(sb, smem, p, bid - NFFN, wg);
  } else if (wg < 2) {
    asm volatile("setmaxnreg.inc.sync.aligned.u32 232;");
    asm volatile("barrier.cluster.wait.acquire.aligned;" ::: "memory");
    TL(1);
    ffn_consumer(sb, smem, p, bid, wg, threadIdx.x & 127, mt, jj);
  } else {
    asm volatile("setmaxnreg.dec.sync.aligned.u32 40;");
    if (threadIdx.x == 320) {
      mbar_expect_tx(BAR_X(sb, 0), 16384);
      tma2d(sb + SM_X, &p.x, 0, 128 * mt, BAR_X(sb, 0));
    }
    __syncwarp();
    asm volatile("barrier.cluster.wait.acquire.aligned;" ::: "memory");
    TL(1);
    if (threadIdx.x == 320) {
      constexpr int order[13] = {XORDER};
#pragma unroll
      for (int i = 0; i < 13; i++) {
        if (order[i] < 8) {
          ring_issue(sb, p, order[i], order[i], false, 0, jj, rank);
        } else {
          const int kb = order[i] - 10;
          mbar_expect_tx(BAR_X(sb, kb), 16384);
          tma2d(sb + SM_X + kb * 16384, &p.x, 64 * kb, 128 * mt, BAR_X(sb, kb));
        }
      }
      TL(2);
    } else if (threadIdx.x == 352) {
    }
    __syncwarp();
    ffn_producer(sb, smem, bid, p, (threadIdx.x >> 5) & 3, threadIdx.x & 31, mt, jj, rank);
  }
}

typedef CUresult (*EncodeFn)(CUtensorMap*, CUtensorMapDataType, cuuint32_t, void*, const cuuint64_t*, const cuuint64_t*,
                             const cuuint32_t*, const cuuint32_t*, CUtensorMapInterleave, CUtensorMapSwizzle,
                             CUtensorMapL2promotion, CUtensorMapFloatOOBfill);

void make_map(EncodeFn fn, CUtensorMap* m, const void* base, int rank, const cuuint64_t* dims, const cuuint64_t* strides,
              const cuuint32_t* box, CUtensorMapSwizzle sw) {
  const cuuint32_t es[4] = {1, 1, 1, 1};
  fn(m, CU_TENSOR_MAP_DATA_TYPE_BFLOAT16, rank, const_cast<void*>(base), dims, strides, box, es,
     CU_TENSOR_MAP_INTERLEAVE_NONE, sw, CU_TENSOR_MAP_L2_PROMOTION_L2_256B, CU_TENSOR_MAP_FLOAT_OOB_FILL_NONE);
}

}

extern "C" void kernel_launch(void* const* d_in, const int* in_sizes, int n_in, void* d_out, int out_size) {
  const __nv_bfloat16* x = (const __nv_bfloat16*)d_in[0];
  const __nv_bfloat16* w_r = (const __nv_bfloat16*)d_in[1];
  const __nv_bfloat16* w_i = (const __nv_bfloat16*)d_in[2];
  const __nv_bfloat16* wg = (const __nv_bfloat16*)d_in[4];
  const __nv_bfloat16* wu = (const __nv_bfloat16*)d_in[5];
  const __nv_bfloat16* wd = (const __nv_bfloat16*)d_in[6];
  const __nv_bfloat16* gate_w = (const __nv_bfloat16*)d_in[7];

  void* fnp = nullptr;
  cudaDriverEntryPointQueryResult qr;
  cudaGetDriverEntryPoint("cuTensorMapEncodeTiled", &fnp, cudaEnableDefault, &qr);
  EncodeFn fn = (EncodeFn)fnp;
  void *ctab, *spec, *scr;
  cudaGetSymbolAddress(&ctab, g_ctab);
  cudaGetSymbolAddress(&spec, g_spec);
  cudaGetSymbolAddress(&scr, g_scratch);
  const void* yt = (const char*)scr + offsetof(Scratch, yt);
  Params p;
  p.s = (Scratch*)scr; p.out = (__nv_bfloat16*)d_out;
  p.px = x; p.w_r = w_r; p.w_i = w_i; p.gate_w = gate_w; p.pwg = wg; p.pwu = wu; p.pwd = wd;
  p.ctab = (const tab::Table*)ctab; p.spec = (const tab::Spec*)spec;
  {
    const cuuint64_t d[2] = {D_, S_}, s[1] = {D_ * 2};
    const cuuint32_t b[2] = {64, 128};
    make_map(fn, &p.x, x, 2, d, s, b, CU_TENSOR_MAP_SWIZZLE_128B);
  }
  {
    const cuuint64_t d[3] = {64, D_, F_ / 64}, s[2] = {F_ * 2, 128};
    const cuuint32_t b[3] = {64, 32, 2};
    make_map(fn, &p.wg, wg, 3, d, s, b, CU_TENSOR_MAP_SWIZZLE_128B);
    make_map(fn, &p.wu, wu, 3, d, s, b, CU_TENSOR_MAP_SWIZZLE_128B);
  }
  {
    const cuuint64_t d[2] = {D_, F_}, s[1] = {D_ * 2};
    const cuuint32_t b[2] = {64, 64};
    make_map(fn, &p.wd, wd, 2, d, s, b, CU_TENSOR_MAP_SWIZZLE_128B);
  }
  {
    const cuuint64_t d[2] = {D_, D_}, s[1] = {D_ * 2};
    const cuuint32_t b[2] = {64, 64};
    make_map(fn, &p.ct, ctab, 2, d, s, b, CU_TENSOR_MAP_SWIZZLE_128B);
  }
  {
    const cuuint64_t d[3] = {64, D_, S_ / 64}, s[2] = {S_ * 2, 128};
    const cuuint32_t b[3] = {64, 64, 2};
    make_map(fn, &p.yt, yt, 3, d, s, b, CU_TENSOR_MAP_SWIZZLE_128B);
  }
  cudaFuncSetAttribute(fused_kernel, cudaFuncAttributeMaxDynamicSharedMemorySize, SM_TOTAL);
  fused_kernel<<<NCTA, 384, SM_TOTAL, cudaStreamPerThread>>>(p, x, w_r, w_i, gate_w, wd, (__nv_bfloat16*)d_out);
}
```

```cpp
#include <cuda_runtime.h>
#include <cuda_bf16.h>
#include <cuda.h>
#include <stdint.h>
#include <stddef.h>

namespace {

constexpr int S_ = 2048, D_ = 448, F_ = 1792, DF_ = 225;
constexpr int NFFN = 112, NSPEC = 20, NCTA = NFFN + NSPEC;
constexpr int NSTAGE = 7, STAGE_BYTES = 16384;
constexpr int SM_X = 0, SM_RING = 114688, SM_BAR = 229376, SM_TOTAL = SM_BAR + 512;
constexpr int SP_Z = 0, SP_W = 98304, SP_TW = 198656, SP_T = 215040, SLAB_BYTES = 16 * DF_ * 2;
constexpr uint32_t SPIN_LIMIT = 1u << 20;

namespace tab {
constexpr double PI = 3.14159265358979323846264338327950288;
constexpr double csin(double x) {
  double t = x, s = x;
  for (int i = 1; i < 20; i++) { t = -t * x * x / ((2 * i) * (2 * i + 1)); s += t; }
  return s;
}
constexpr double ccos(double x) {
  double t = 1, s = 1;
  for (int i = 1; i < 20; i++) { t = -t * x * x / ((2 * i - 1) * (2 * i)); s += t; }
  return s;
}
constexpr uint32_t to_bf16(double v) {
  uint32_t sign = v < 0 ? 0x8000u : 0u;
  double a = v < 0 ? -v : v;
  if (a < 1e-12) return 0;
  int e = 0;
  while (a >= 2.0) { a /= 2; e++; }
  while (a < 1.0) { a *= 2; e--; }
  double m = a * 128.0;
  int mi = (int)m;
  double fr = m - mi;
  if (fr > 0.5 || (fr == 0.5 && (mi & 1))) mi++;
  if (mi == 256) { mi = 128; e++; }
  return sign | (uint32_t)((e + 127) << 7) | (uint32_t)(mi - 128);
}
struct Base { uint32_t v[448]; };
constexpr Base make_base() {
  Base b{};
  for (int m = 0; m < 448; m++) {
    int mm = m > 224 ? m - 448 : m;
    double ang = 2 * PI * mm / 448.0;
    b.v[m] = to_bf16(ccos(ang)) | (to_bf16(-csin(ang)) << 16);
  }
  return b;
}
constexpr Base base = make_base();
struct Row { uint32_t v[224]; };
constexpr Row make_row(int d) {
  Row r{};
  r.v[0] = 0x3f80u | ((d & 1) ? 0xbf800000u : 0x3f800000u);
  int m = 0;
  for (int c = 1; c < 224; c++) { m += d; if (m >= 448) m -= 448; r.v[c] = base.v[m]; }
  return r;
}
struct Table { Row r[448]; };
constexpr Table make_table() {
  Table t{};
  for (int d = 0; d < 448; d++) t.r[d] = make_row(d);
  return t;
}
struct Cs { double c[2048], s[2048]; };
constexpr Cs make_cs() {
  Cs t{};
  for (int m = 0; m <= 256; m++) {
    const double a = 2 * PI * m / 2048.0, c = ccos(a), s = csin(a);
    t.c[m] = c; t.s[m] = s;
    t.c[512 - m] = s; t.s[512 - m] = c;
  }
  for (int m = 513; m < 2048; m++) { t.c[m] = -t.s[m - 512]; t.s[m] = t.c[m - 512]; }
  return t;
}
constexpr Cs cs = make_cs();
struct Spec {
  uint32_t fo[2048], fot[2048];
  uint16_t t32[4096];
  uint32_t fe[2048];
  uint32_t tw[2048];
};
constexpr uint32_t blk(int h, int c, int a) { return to_bf16(h == c ? cs.c[a & 2047] : (h ? -cs.s[a & 2047] : cs.s[a & 2047])); }
constexpr Spec make_spec() {
  Spec t{};
  for (int row = 0; row < 64; row++)
    for (int col = 0; col < 64; col++) {
      const int c = row & 31, k2 = col & 31, n2 = 8 * ((c >> 1) & 3) + 2 * (c >> 3) + (c & 1), m = 64 * ((n2 * k2) & 31);
      const double v = (row >> 5) == (col >> 5) ? cs.c[m] : (row < 32 ? -cs.s[m] : cs.s[m]);
      t.t32[row * 64 + (((col >> 3) ^ (row & 7)) << 3) + (col & 7)] = (uint16_t)to_bf16(v);
    }
  for (int th = 0; th < 128; th++)
    for (int i = 0; i < 16; i++) {
      const int r = 8 * (th >> 5) + ((th & 31) >> 2), h = i & 1, c = i >> 3, m = 8 * ((i >> 1) & 3) + 2 * (th & 3);
      const int o = ((i >> 2) * 128 + th) * 4 + (i & 3);
      t.fe[o] = blk(h, c, 64 * m * r) | (blk(h, c, 64 * (m + 1) * r) << 16);
      t.fo[o] = blk(h, c, 32 * (2 * m + 1) * r) | (blk(h, c, 32 * (2 * m + 3) * r) << 16);
      t.fot[o] = blk(h, c, 32 * (2 * r + 1) * m) | (blk(h, c, 32 * (2 * r + 1) * (m + 1)) << 16);
      const int k1 = r + 32 * h, n2 = 8 * (th & 3) + 2 * ((i >> 1) & 3);
      t.tw[o] = blk(0, c, n2 * k1) | (blk(0, c, (n2 + 1) * k1) << 16);
    }
  return t;
}
}
}

__device__ __align__(1024) const tab::Table g_ctab = tab::make_table();
__device__ __align__(1024) const tab::Spec g_spec = tab::make_spec();

struct Scratch {
  uint32_t cnt_w[32];
  uint32_t cnt_x1[7 * 32];
  uint32_t cnt_y[7 * 32];
  uint32_t epoch[NCTA * 12 + 240 + 256];
  uint32_t gate[S_];
  uint4 x1t[113 * 1024];
  __nv_bfloat16 yt[D_ * S_];
  uint4 wt[114 * 1024];
  uint4 part[16 * 7 * 6 * 2 * 4 * 128];
};
static_assert(offsetof(Scratch, x1t) % 1024 == 0, "alignment");
__device__ __align__(1024) Scratch g_scratch;
#define TL(i)

namespace {

struct Params {
  Scratch* s;
  __nv_bfloat16* out;
  const __nv_bfloat16 *px, *w_r, *w_i, *gate_w, *pwg, *pwu, *pwd;
  const tab::Table* ctab;
  const tab::Spec* spec;
  CUtensorMap x, wg, wu, wd, ct, yt, yt2;
};

__device__ __forceinline__ uint32_t smem_u32(const void* p) { return (uint32_t)__cvta_generic_to_shared(p); }
__device__ __forceinline__ void mbar_init(uint32_t bar, uint32_t cnt) {
  asm volatile("mbarrier.init.shared::cta.b64 [%0], %1;" ::"r"(bar), "r"(cnt) : "memory");
}
__device__ __forceinline__ void mbar_expect_tx(uint32_t bar, uint32_t bytes) {
  asm volatile("mbarrier.arrive.expect_tx.shared::cta.b64 _, [%0], %1;" ::"r"(bar), "r"(bytes) : "memory");
}
__device__ __forceinline__ void mbar_arrive(uint32_t bar) {
  asm volatile("mbarrier.arrive.shared::cta.b64 _, [%0];" ::"r"(bar) : "memory");
}
__device__ __forceinline__ void mbar_arrive_cluster(uint32_t bar, uint32_t cta) {
  asm volatile("{\n.reg .b32 ra;\nmapa.shared::cluster.u32 ra, %0, %1;\n"
               "mbarrier.arrive.shared::cluster.b64 _, [ra];\n}" ::"r"(bar), "r"(cta) : "memory");
}
__device__ __forceinline__ void mbar_wait(uint32_t bar, uint32_t parity) {
  uint32_t ok, n = 0;
  do {
    asm volatile("{\n.reg .pred p;\nmbarrier.try_wait.parity.shared::cta.b64 p, [%1], %2;\nselp.u32 %0, 1, 0, p;\n}"
                 : "=r"(ok) : "r"(bar), "r"(parity) : "memory");
  } while (!ok && ++n < SPIN_LIMIT);
}
__device__ __forceinline__ void mbar_wait_cluster(uint32_t bar, uint32_t parity) {
  uint32_t ok, n = 0;
  do {
    asm volatile("{\n.reg .pred p;\nmbarrier.try_wait.parity.acquire.cluster.shared::cta.b64 p, [%1], %2;\nselp.u32 %0, 1, 0, p;\n}"
                 : "=r"(ok) : "r"(bar), "r"(parity) : "memory");
  } while (!ok && ++n < SPIN_LIMIT);
}
__device__ __forceinline__ void tma2d(uint32_t dst, const CUtensorMap* m, int c0, int c1, uint32_t bar) {
  asm volatile("cp.async.bulk.tensor.2d.shared::cluster.global.mbarrier::complete_tx::bytes [%0], [%1, {%3, %4}], [%2];"
               ::"r"(dst), "l"(m), "r"(bar), "r"(c0), "r"(c1) : "memory");
}
__device__ __forceinline__ void tma3d(uint32_t dst, const CUtensorMap* m, int c0, int c1, int c2, uint32_t bar) {
  asm volatile("cp.async.bulk.tensor.3d.shared::cluster.global.mbarrier::complete_tx::bytes [%0], [%1, {%3, %4, %5}], [%2];"
               ::"r"(dst), "l"(m), "r"(bar), "r"(c0), "r"(c1), "r"(c2) : "memory");
}
__device__ __forceinline__ void tma2d_mc(uint32_t dst, const CUtensorMap* m, int c0, int c1, uint32_t bar) {
  asm volatile("cp.async.bulk.tensor.2d.shared::cluster.global.mbarrier::complete_tx::bytes.multicast::cluster [%0], [%1, {%3, %4}], [%2], %5;"
               ::"r"(dst), "l"(m), "r"(bar), "r"(c0), "r"(c1), "h"((uint16_t)3) : "memory");
}
__device__ __forceinline__ void tma3d_mc(uint32_t dst, const CUtensorMap* m, int c0, int c1, int c2, uint32_t bar) {
  asm volatile("cp.async.bulk.tensor.3d.shared::cluster.global.mbarrier::complete_tx::bytes.multicast::cluster [%0], [%1, {%3, %4, %5}], [%2], %6;"
               ::"r"(dst), "l"(m), "r"(bar), "r"(c0), "r"(c1), "r"(c2), "h"((uint16_t)3) : "memory");
}
__device__ __forceinline__ void bulk_g2s(uint32_t dst, const void* src, uint32_t bytes, uint32_t bar) {
  asm volatile("cp.async.bulk.shared::cluster.global.mbarrier::complete_tx::bytes [%0], [%1], %2, [%3];"
               ::"r"(dst), "l"(src), "r"(bytes), "r"(bar) : "memory");
}
__device__ __forceinline__ void bulk_s2g(void* dst, uint32_t src, uint32_t bytes) {
  asm volatile("cp.async.bulk.global.shared::cta.bulk_group [%0], [%1], %2;" ::"l"(dst), "r"(src), "r"(bytes) : "memory");
}
__device__ __forceinline__ void prefetch_tmap(const CUtensorMap* m) {
  asm volatile("prefetch.tensormap [%0];" ::"l"(m) : "memory");
}
__device__ __forceinline__ void l2_prefetch(const void* p, uint32_t bytes) {
  asm volatile("cp.async.bulk.prefetch.L2.global [%0], %1;" ::"l"(p), "r"(bytes) : "memory");
}
__device__ __forceinline__ void wg_fence() { asm volatile("wgmma.fence.sync.aligned;" ::: "memory"); }
__device__ __forceinline__ void wg_commit() { asm volatile("wgmma.commit_group.sync.aligned;" ::: "memory"); }
template <int N> __device__ __forceinline__ void wg_wait() { asm volatile("wgmma.wait_group.sync.aligned %0;" ::"n"(N) : "memory"); }
template <int N> __device__ __forceinline__ void fence_regs(float (&d)[N]) {
#pragma unroll
  for (int i = 0; i < N; i++) asm volatile("" : "+f"(d[i])::"memory");
}
template <int N> __device__ __forceinline__ void fence_regs(uint32_t (&d)[N]) {
#pragma unroll
  for (int i = 0; i < N; i++) asm volatile("" : "+r"(d[i])::"memory");
}
__device__ __forceinline__ void bar_sync(int id, int n) { asm volatile("bar.sync %0, %1;" ::"r"(id), "r"(n) : "memory"); }
__device__ __forceinline__ void bar_arrive(int id, int n) { asm volatile("bar.arrive %0, %1;" ::"r"(id), "r"(n) : "memory"); }
__device__ __forceinline__ void fence_gpu() { asm volatile("fence.acq_rel.gpu;" ::: "memory"); }
__device__ __forceinline__ void fence_async() { asm volatile("fence.proxy.async;" ::: "memory"); }
__device__ __forceinline__ void fence_async_smem() { asm volatile("fence.proxy.async.shared::cta;" ::: "memory"); }
__device__ __forceinline__ void red_add(uint32_t* p, uint32_t v) {
  asm volatile("red.relaxed.gpu.global.add.u32 [%0], %1;" ::"l"(p), "r"(v) : "memory");
}
__device__ __forceinline__ uint32_t ld_relaxed(const uint32_t* p) {
  uint32_t v;
  asm volatile("ld.relaxed.gpu.global.u32 %0, [%1];" : "=r"(v) : "l"(p) : "memory");
  return v;
}
__device__ __forceinline__ void wait_counter(const uint32_t* p, uint32_t target) {
  uint32_t v, n = 0;
  while (true) {
    asm volatile("ld.acquire.gpu.global.u32 %0, [%1];" : "=r"(v) : "l"(p) : "memory");
    if ((int32_t)(v - target) >= 0 || ++n > SPIN_LIMIT) break;
  }
}
__device__ __forceinline__ uint4 ld_relaxed(const uint4* p) {
  uint4 v;
  asm volatile("ld.relaxed.gpu.global.v4.u32 {%0, %1, %2, %3}, [%4];" : "=r"(v.x), "=r"(v.y), "=r"(v.z), "=r"(v.w) : "l"(p) : "memory");
  return v;
}
__device__ __forceinline__ void st_relaxed(uint4* p, uint4 v) {
  asm volatile("st.relaxed.gpu.global.v4.u32 [%0], {%1, %2, %3, %4};" ::"l"(p), "r"(v.x), "r"(v.y), "r"(v.z), "r"(v.w) : "memory");
}
__device__ __forceinline__ void st_relaxed(uint32_t* p, uint32_t v) {
  asm volatile("st.relaxed.gpu.global.u32 [%0], %1;" ::"l"(p), "r"(v) : "memory");
}
__device__ __forceinline__ uint32_t pack2(float lo, float hi) {
  uint32_t r;
  asm("cvt.rn.bf16x2.f32 %0, %1, %2;" : "=r"(r) : "f"(hi), "f"(lo));
  return r;
}
__device__ __forceinline__ uint32_t mul2(uint32_t a, uint32_t b) {
  uint32_t r;
  asm("mul.rn.bf16x2 %0, %1, %2;" : "=r"(r) : "r"(a), "r"(b));
  return r;
}
__device__ __forceinline__ uint32_t fma2(uint32_t a, uint32_t b, uint32_t c) {
  uint32_t r;
  asm("fma.rn.bf16x2 %0, %1, %2, %3;" : "=r"(r) : "r"(a), "r"(b), "r"(c));
  return r;
}
__device__ __forceinline__ uint32_t add2(uint32_t a, uint32_t b) {
  uint32_t r;
  asm("add.rn.bf16x2 %0, %1, %2;" : "=r"(r) : "r"(a), "r"(b));
  return r;
}
__device__ __forceinline__ uint32_t sub2(uint32_t a, uint32_t b) {
  uint32_t r;
  asm("sub.rn.bf16x2 %0, %1, %2;" : "=r"(r) : "r"(a), "r"(b));
  return r;
}
__device__ __forceinline__ uint32_t fms2(uint32_t a, uint32_t b, uint32_t c) {
  uint32_t r;
  asm("{\n.reg .b32 n;\nneg.bf16x2 n, %3;\nfma.rn.bf16x2 %0, %1, %2, n;\n}" : "=r"(r) : "r"(a), "r"(b), "r"(c));
  return r;
}
__device__ __forceinline__ float bf_lo(uint32_t v) { return __uint_as_float(v << 16); }
__device__ __forceinline__ float bf_hi(uint32_t v) { return __uint_as_float(v & 0xffff0000u); }
__device__ __forceinline__ float bf_round(float v) { return bf_lo(pack2(v, 0.f)); }
__device__ __forceinline__ float tanh_fast(float v) {
  float r;
  asm("tanh.approx.f32 %0, %1;" : "=f"(r) : "f"(v));
  return r;
}
__device__ __forceinline__ uint64_t mk_desc(uint32_t addr, uint32_t lbo, uint32_t sbo, uint32_t mode) {
  return (uint64_t)((addr & 0x3FFFF) >> 4) | ((uint64_t)(lbo >> 4) << 16) | ((uint64_t)(sbo >> 4) << 32) | ((uint64_t)mode << 62);
}
__device__ __forceinline__ void stmatrix_x4(uint32_t addr, uint32_t r0, uint32_t r1, uint32_t r2, uint32_t r3) {
  asm volatile("stmatrix.sync.aligned.m8n8.x4.shared.b16 [%0], {%1, %2, %3, %4};" ::"r"(addr), "r"(r0), "r"(r1), "r"(r2), "r"(r3) : "memory");
}

template <int TA, int TB>
__device__ __forceinline__ void wgmma_ss_n256(float (&d)[128], uint64_t da, uint64_t db, int sd) {
  asm volatile("{\n.reg .pred p;\nsetp.ne.b32 p, %130, 0;\n"
      "wgmma.mma_async.sync.aligned.m64n256k16.f32.bf16.bf16 {"
      "%0, %1, %2, %3, %4, %5, %6, %7, %8, %9, %10, %11, %12, %13, %14, %15, %16, %17, %18, %19, %20, %21, %22, %23, "
      "%24, %25, %26, %27, %28, %29, %30, %31, %32, %33, %34, %35, %36, %37, %38, %39, %40, %41, %42, %43, %44, %45, "
      "%46, %47, %48, %49, %50, %51, %52, %53, %54, %55, %56, %57, %58, %59, %60, %61, %62, %63, %64, %65, %66, %67, "
      "%68, %69, %70, %71, %72, %73, %74, %75, %76, %77, %78, %79, %80, %81, %82, %83, %84, %85, %86, %87, %88, %89, "
      "%90, %91, %92, %93, %94, %95, %96, %97, %98, %99, %100, %101, %102, %103, %104, %105, %106, %107, %108, %109, "
      "%110, %111, %112, %113, %114, %115, %116, %117, %118, %119, %120, %121, %122, %123, %124, %125, %126, %127"
      "}, %128, %129, p, 1, 1, %131, %132;\n}\n"
      : "+f"(d[0]), "+f"(d[1]), "+f"(d[2]), "+f"(d[3]), "+f"(d[4]), "+f"(d[5]), "+f"(d[6]), "+f"(d[7]), "+f"(d[8]),
        "+f"(d[9]), "+f"(d[10]), "+f"(d[11]), "+f"(d[12]), "+f"(d[13]), "+f"(d[14]), "+f"(d[15]), "+f"(d[16]),
        "+f"(d[17]), "+f"(d[18]), "+f"(d[19]), "+f"(d[20]), "+f"(d[21]), "+f"(d[22]), "+f"(d[23]), "+f"(d[24]),
        "+f"(d[25]), "+f"(d[26]), "+f"(d[27]), "+f"(d[28]), "+f"(d[29]), "+f"(d[30]), "+f"(d[31]), "+f"(d[32]),
        "+f"(d[33]), "+f"(d[34]), "+f"(d[35]), "+f"(d[36]), "+f"(d[37]), "+f"(d[38]), "+f"(d[39]), "+f"(d[40]),
        "+f"(d[41]), "+f"(d[42]), "+f"(d[43]), "+f"(d[44]), "+f"(d[45]), "+f"(d[46]), "+f"(d[47]), "+f"(d[48]),
        "+f"(d[49]), "+f"(d[50]), "+f"(d[51]), "+f"(d[52]), "+f"(d[53]), "+f"(d[54]), "+f"(d[55]), "+f"(d[56]),
        "+f"(d[57]), "+f"(d[58]), "+f"(d[59]), "+f"(d[60]), "+f"(d[61]), "+f"(d[62]), "+f"(d[63]), "+f"(d[64]),
        "+f"(d[65]), "+f"(d[66]), "+f"(d[67]), "+f"(d[68]), "+f"(d[69]), "+f"(d[70]), "+f"(d[71]), "+f"(d[72]),
        "+f"(d[73]), "+f"(d[74]), "+f"(d[75]), "+f"(d[76]), "+f"(d[77]), "+f"(d[78]), "+f"(d[79]), "+f"(d[80]),
        "+f"(d[81]), "+f"(d[82]), "+f"(d[83]), "+f"(d[84]), "+f"(d[85]), "+f"(d[86]), "+f"(d[87]), "+f"(d[88]),
        "+f"(d[89]), "+f"(d[90]), "+f"(d[91]), "+f"(d[92]), "+f"(d[93]), "+f"(d[94]), "+f"(d[95]), "+f"(d[96]),
        "+f"(d[97]), "+f"(d[98]), "+f"(d[99]), "+f"(d[100]), "+f"(d[101]), "+f"(d[102]), "+f"(d[103]), "+f"(d[104]),
        "+f"(d[105]), "+f"(d[106]), "+f"(d[107]), "+f"(d[108]), "+f"(d[109]), "+f"(d[110]), "+f"(d[111]),
        "+f"(d[112]), "+f"(d[113]), "+f"(d[114]), "+f"(d[115]), "+f"(d[116]), "+f"(d[117]), "+f"(d[118]),
        "+f"(d[119]), "+f"(d[120]), "+f"(d[121]), "+f"(d[122]), "+f"(d[123]), "+f"(d[124]), "+f"(d[125]),
        "+f"(d[126]), "+f"(d[127])
      : "l"(da), "l"(db), "r"(sd), "n"(TA), "n"(TB));
}
template <int TA, int TB>
__device__ __forceinline__ void wgmma_ss_n128(float (&d)[64], uint64_t da, uint64_t db, int sd) {
  asm volatile("{\n.reg .pred p;\nsetp.ne.b32 p, %66, 0;\n"
      "wgmma.mma_async.sync.aligned.m64n128k16.f32.bf16.bf16 {"
      "%0, %1, %2, %3, %4, %5, %6, %7, %8, %9, %10, %11, %12, %13, %14, %15, %16, %17, %18, %19, %20, %21, %22, %23, "
      "%24, %25, %26, %27, %28, %29, %30, %31, %32, %33, %34, %35, %36, %37, %38, %39, %40, %41, %42, %43, %44, %45, "
      "%46, %47, %48, %49, %50, %51, %52, %53, %54, %55, %56, %57, %58, %59, %60, %61, %62, %63"
      "}, %64, %65, p, 1, 1, %67, %68;\n}\n"
      : "+f"(d[0]), "+f"(d[1]), "+f"(d[2]), "+f"(d[3]), "+f"(d[4]), "+f"(d[5]), "+f"(d[6]), "+f"(d[7]), "+f"(d[8]),
        "+f"(d[9]), "+f"(d[10]), "+f"(d[11]), "+f"(d[12]), "+f"(d[13]), "+f"(d[14]), "+f"(d[15]), "+f"(d[16]),
        "+f"(d[17]), "+f"(d[18]), "+f"(d[19]), "+f"(d[20]), "+f"(d[21]), "+f"(d[22]), "+f"(d[23]), "+f"(d[24]),
        "+f"(d[25]), "+f"(d[26]), "+f"(d[27]), "+f"(d[28]), "+f"(d[29]), "+f"(d[30]), "+f"(d[31]), "+f"(d[32]),
        "+f"(d[33]), "+f"(d[34]), "+f"(d[35]), "+f"(d[36]), "+f"(d[37]), "+f"(d[38]), "+f"(d[39]), "+f"(d[40]),
        "+f"(d[41]), "+f"(d[42]), "+f"(d[43]), "+f"(d[44]), "+f"(d[45]), "+f"(d[46]), "+f"(d[47]), "+f"(d[48]),
        "+f"(d[49]), "+f"(d[50]), "+f"(d[51]), "+f"(d[52]), "+f"(d[53]), "+f"(d[54]), "+f"(d[55]), "+f"(d[56]),
        "+f"(d[57]), "+f"(d[58]), "+f"(d[59]), "+f"(d[60]), "+f"(d[61]), "+f"(d[62]), "+f"(d[63])
      : "l"(da), "l"(db), "r"(sd), "n"(TA), "n"(TB));
}
template <int TA, int TB>
__device__ __forceinline__ void wgmma_ss_n64(float (&d)[32], uint64_t da, uint64_t db, int sd) {
  asm volatile("{\n.reg .pred p;\nsetp.ne.b32 p, %34, 0;\n"
      "wgmma.mma_async.sync.aligned.m64n64k16.f32.bf16.bf16 {"
      "%0, %1, %2, %3, %4, %5, %6, %7, %8, %9, %10, %11, %12, %13, %14, %15, %16, %17, %18, %19, %20, %21, %22, %23, "
      "%24, %25, %26, %27, %28, %29, %30, %31"
      "}, %32, %33, p, 1, 1, %35, %36;\n}\n"
      : "+f"(d[0]), "+f"(d[1]), "+f"(d[2]), "+f"(d[3]), "+f"(d[4]), "+f"(d[5]), "+f"(d[6]), "+f"(d[7]), "+f"(d[8]),
        "+f"(d[9]), "+f"(d[10]), "+f"(d[11]), "+f"(d[12]), "+f"(d[13]), "+f"(d[14]), "+f"(d[15]), "+f"(d[16]),
        "+f"(d[17]), "+f"(d[18]), "+f"(d[19]), "+f"(d[20]), "+f"(d[21]), "+f"(d[22]), "+f"(d[23]), "+f"(d[24]),
        "+f"(d[25]), "+f"(d[26]), "+f"(d[27]), "+f"(d[28]), "+f"(d[29]), "+f"(d[30]), "+f"(d[31])
      : "l"(da), "l"(db), "r"(sd), "n"(TA), "n"(TB));
}
template <int SA, int TB>
__device__ __forceinline__ void wgmma_rs_n64(float (&d)[32], uint32_t a0, uint32_t a1, uint32_t a2, uint32_t a3, uint64_t db, int sd) {
  asm volatile("{\n.reg .pred p;\nsetp.ne.b32 p, %37, 0;\n"
      "wgmma.mma_async.sync.aligned.m64n64k16.f32.bf16.bf16 {"
      "%0, %1, %2, %3, %4, %5, %6, %7, %8, %9, %10, %11, %12, %13, %14, %15, %16, %17, %18, %19, %20, %21, %22, %23, "
      "%24, %25, %26, %27, %28, %29, %30, %31"
      "}, {%32, %33, %34, %35}, %36, p, %38, 1, %39;\n}\n"
      : "+f"(d[0]), "+f"(d[1]), "+f"(d[2]), "+f"(d[3]), "+f"(d[4]), "+f"(d[5]), "+f"(d[6]), "+f"(d[7]), "+f"(d[8]),
        "+f"(d[9]), "+f"(d[10]), "+f"(d[11]), "+f"(d[12]), "+f"(d[13]), "+f"(d[14]), "+f"(d[15]), "+f"(d[16]),
        "+f"(d[17]), "+f"(d[18]), "+f"(d[19]), "+f"(d[20]), "+f"(d[21]), "+f"(d[22]), "+f"(d[23]), "+f"(d[24]),
        "+f"(d[25]), "+f"(d[26]), "+f"(d[27]), "+f"(d[28]), "+f"(d[29]), "+f"(d[30]), "+f"(d[31])
      : "r"(a0), "r"(a1), "r"(a2), "r"(a3), "l"(db), "r"(sd), "n"(SA), "n"(TB));
}

__device__ __forceinline__ uint32_t BAR_FULL(uint32_t sb, int i) { return sb + SM_BAR + 8 * i; }
__device__ __forceinline__ uint32_t BAR_EMPTY(uint32_t sb, int i) { return sb + SM_BAR + 64 + 8 * i; }
__device__ __forceinline__ uint32_t BAR_X(uint32_t sb, int i) { return sb + SM_BAR + 128 + 8 * i; }
__device__ __forceinline__ uint32_t BAR_Y(uint32_t sb, int i) { return sb + SM_BAR + 192 + 8 * i; }
__device__ __forceinline__ uint32_t BAR_XFREE(uint32_t sb) { return sb + SM_BAR + 256; }

__device__ __forceinline__ uint32_t BAR_E2(uint32_t sb, int i) { return sb + SM_BAR + 264 + 8 * i; }
#define CMASK 0xd4u
#define XORDER 0, 1, 11, 2, 3, 12, 13, 4, 5, 14, 6, 15, 16
#define XSPREAD 2
#define PFAT 3
#define SKEW 3
#define EQW 99
#define EQA 99
#define SPREAD 1
#define WUN 2
constexpr int WUNR = WUN;
#define EPF 1
#define GL1 0
#define GS0 2
#define GL2 6
#define GS1 4
constexpr int Q_G1B = 18, Q_G2 = 32, Q_XR = 39, Q_P3 = 46, Q_END = 50;

__device__ __forceinline__ uint32_t y_addr(int kb) { return kb < 3 ? SM_RING + (kb + (Q_G2 + 4) % NSTAGE) * STAGE_BYTES : SM_X + (kb - 3) * 16384; }
static_assert((Q_G2 + 4) % NSTAGE + 2 < NSTAGE, "");

struct Ring {
  uint32_t slot, phase;
  __device__ __forceinline__ void next() { if (++slot == NSTAGE) { slot = 0; phase ^= 1; } }
};

__device__ __forceinline__ void release_slot(uint32_t sb, uint32_t slot, int tid, int times) {
  if (tid < 2 * times) mbar_arrive_cluster(BAR_EMPTY(sb, slot), tid & 1);
}

__device__ __forceinline__ void ffn_consumer(uint32_t sb, const uint8_t* smem, const Params& p, int bid, int wg, int tid, int mt, int jj) {
  const int lane = tid & 31, warp = tid >> 5, q = lane & 3, r0 = 16 * warp + (lane >> 2);
  uint32_t* const my_epoch = &p.s->epoch[blockIdx.x * 12 + (threadIdx.x >> 5)];
  const uint32_t epoch = ld_relaxed(my_epoch) + 1;
  Ring rg{0, 0};
  uint32_t u[64];
  float acc[128];
  uint32_t prev = NSTAGE, prev2 = NSTAGE, cmask = CMASK;
  int st = 0;
  auto g1_stage = [&](uint32_t slot, int s) {
    const uint64_t da = mk_desc(sb + SM_X + (s >> 1) * 16384 + wg * 8192 + (s & 1) * 64, 16, 1024, 1);
    const uint64_t db = mk_desc(sb + SM_RING + slot * STAGE_BYTES, 4096, 1024, 1);
    wg_fence();
    wgmma_ss_n256<0, 1>(acc, da, db, s != 0);
    wgmma_ss_n256<0, 1>(acc, da + 2, db + 128, 1);
    wg_commit();
  };
  if (wg == 1) {
    float ap[64];
    constexpr int QX = 32 - __builtin_clz(CMASK);
    constexpr int NPRE = QX + XSPREAD;
    uint4* const x1dst = p.s->x1t + ((64 * jj + r0 + 8) >> 2) * 1024 + (r0 & 3) * 128 + 8 * mt + (q ^ (mt & 3));
    const int x1lo = 64 * jj + r0 == 1 ? 110 * 1024 - 128 : -2048;
#pragma unroll
    for (int qi = 0; qi < NPRE; qi++) {
      const int slot = qi % NSTAGE, nc = __builtin_popcount(CMASK & ((1u << qi) - 1));
      if (qi == 0) TL(60);
      mbar_wait(BAR_FULL(sb, slot), (qi / NSTAGE) & 1);
      if (qi == 0) TL(61);
      if ((CMASK >> qi) & 1) {
#pragma unroll
        for (int kb = 2 * nc; kb < 2 * nc + 2 && kb < 7; kb++) {
          const uint64_t da = mk_desc(sb + SM_RING + slot * STAGE_BYTES + (kb & 1) * 8192, 8192, 1024, 1);
          const uint64_t db = mk_desc(sb + SM_X + kb * 16384, 16, 1024, 1);
          mbar_wait(BAR_X(sb, kb), 0);
          TL(16 + kb);
          wg_fence();
#pragma unroll
          for (int kk = 0; kk < 4; kk++) wgmma_ss_n128<1, 0>(ap, da + kk * 128, db + kk * 2, (kb | kk) != 0);
          wg_commit();
        }
      } else {
        if (((qi - nc) & 1) == 0 && qi - nc >= 4 * nc) mbar_wait(BAR_X(sb, (qi - nc) >> 1), 0);
        TL(32 + qi - nc);
        g1_stage(slot, qi - nc);
      }
      if (qi > 0) {
        wg_wait<1>();
        release_slot(sb, (qi - 1) % NSTAGE, tid, ((CMASK >> (qi - 1)) & 1) ? 2 : 1);
      }
      if (qi >= QX) {
        if (qi == QX) { fence_regs(ap); TL(2); }
#pragma unroll
        for (int t = (qi - QX) * (4 / XSPREAD); t < (qi - QX + 1) * (4 / XSPREAD); t++)
#pragma unroll
        for (int h = 0; h < 2; h++)
          x1dst[(h ? 0 : x1lo) + 512 * (t & 1) + 4 * (t >> 1)] = make_uint4((pack2(ap[16 * t + 2 * h], ap[16 * t + 2 * h + 1]) & ~1u) | (epoch & 1), pack2(ap[16 * t + 4 + 2 * h], ap[16 * t + 5 + 2 * h]),
                                             pack2(ap[16 * t + 8 + 2 * h], ap[16 * t + 9 + 2 * h]), pack2(ap[16 * t + 12 + 2 * h], ap[16 * t + 13 + 2 * h]));
      }
    }
    bar_arrive(7, 160);
    st = NPRE - 4; cmask = 0; prev = (NPRE - 1) % NSTAGE;
    rg.slot = NPRE % NSTAGE; rg.phase = (NPRE / NSTAGE) & 1;
  }
#pragma unroll 1
  for (int pass = 0; pass < 2; pass++) {
#pragma unroll 1
    for (; st < 14; st++) {
      while (cmask & 1) { cmask >>= 1; rg.next(); }
      cmask >>= 1;
      if (pass == 0 && (st & 1) == 0) mbar_wait(BAR_X(sb, st >> 1), 0);
      if (st == 14 - SKEW && wg == 1) bar_sync(9 + pass, 256);
      mbar_wait(BAR_FULL(sb, rg.slot), rg.phase);
      TL(32 + 14 * pass + st);
      g1_stage(rg.slot, st);
      wg_wait<2>();
      if (prev2 < NSTAGE) release_slot(sb, prev2, tid, 1);
      prev2 = prev;
      prev = rg.slot;
      rg.next();
    }
    st = 0;
    if (wg == 0) bar_arrive(9 + pass, 256);
    wg_wait<1>();
    release_slot(sb, prev2, tid, 1);
    wg_wait<0>();
    fence_regs(acc);
    release_slot(sb, prev, tid, 1);
    prev = prev2 = NSTAGE;
    TL(3 + 2 * pass);
#pragma unroll
    for (int i = 0; i < 32; i++) {
      const float g0 = 0.5f * acc[2 * i], g1 = 0.5f * acc[2 * i + 1];
      const float s0 = fmaf(g0, tanh_fast(g0), g0), s1 = fmaf(g1, tanh_fast(g1), g1);
      u[32 + i] = pack2(s0 * acc[64 + 2 * i], s1 * acc[64 + 2 * i + 1]);
    }
    if (pass == 0) {
#pragma unroll
      for (int i = 0; i < 32; i++) u[i] = u[32 + i];
    }
    TL(4 + 2 * pass);
  }
  fence_regs(u);
  float accA[32], accB[32];
  auto stage = [&](float (&acc)[32], int qi) {
    const int st = qi & 1;
    if (qi == EQW && wg == 0) bar_sync(1, 256);
    if (qi < Q_XR) mbar_wait(BAR_FULL(sb, qi % NSTAGE), (qi / NSTAGE) & 1);
    else mbar_wait(BAR_X(sb, qi - Q_XR), 1);
    const uint64_t db = mk_desc(sb + (qi < Q_XR ? SM_RING + (qi % NSTAGE) * STAGE_BYTES : SM_X + (qi - Q_XR) * 16384), 8192, 1024, 1);
    wg_fence();
#pragma unroll
    for (int kk = 0; kk < 8; kk++) {
      const uint32_t* a = u + 32 * st + 4 * kk;
      wgmma_rs_n64<1, 1>(acc, a[0], a[1], a[2], a[3], db + kk * 128, (st | kk) != 0);
    }
    wg_commit();
    if (qi == EQA && wg == 1) bar_arrive(1, 256);
  };
  auto retire = [&](int qi) {
    wg_wait<1>();
    if (qi >= Q_G2 && qi < Q_G2 + 4) release_slot(sb, qi % NSTAGE, tid, 1);
    else if (qi >= Q_G2 + 4 && qi < Q_G2 + 11 && tid == 0) mbar_arrive(BAR_E2(sb, qi - Q_G2 - 4));
  };
  const uint32_t par = epoch & 1;
  auto put = [&](float (&acc)[32], int c) {
    fence_regs(acc);
    int o = jj + 1 + c;
    if (o >= 7) o -= 7;
    uint4* dst = p.s->part + ((((mt * 7 + o) * 6 + c) * 2 + wg) * 4) * 128 + tid;
#pragma unroll
    for (int v = 0; v < 4; v++) {
      const float* a = acc + 8 * v;
      st_relaxed(dst + v * 128, make_uint4((pack2(a[0], a[1]) & ~1u) | par, pack2(a[2], a[3]), pack2(a[4], a[5]), pack2(a[6], a[7])));
    }
  };
  const uint4* const src = p.s->part + (((mt * 7 + jj) * 6 * 2 + wg) * 4) * 128 + tid;
  auto gload = [&](uint4 (&pv)[8], int c) {
#pragma unroll
    for (int i = 0; i < 8; i++) pv[i] = ld_relaxed(src + ((2 * c + (i >> 2)) * 8 + (i & 3)) * 128);
  };
  auto gload1 = [&](uint4 (&pv)[8], int c) {
#pragma unroll
    for (int i = 0; i < 4; i++) pv[4 * (c & 1) + i] = ld_relaxed(src + (c * 8 + i) * 128);
  };
  auto gsum = [&](uint4 (&pv)[8], int c) {
#pragma unroll 1
    for (uint32_t n = 0; n < SPIN_LIMIT; n++) {
      uint32_t bad = 0;
#pragma unroll
      for (int i = 0; i < 8; i++) bad |= pv[i].x ^ par;
      if (!__any_sync(0xffffffffu, bad & 1)) break;
      gload(pv, c);
    }
    TL(24 + c);
#pragma unroll
    for (int i = 0; i < 8; i++) {
      const float t[8] = {bf_lo(pv[i].x), bf_hi(pv[i].x), bf_lo(pv[i].y), bf_hi(pv[i].y), bf_lo(pv[i].z), bf_hi(pv[i].z), bf_lo(pv[i].w), bf_hi(pv[i].w)};
#pragma unroll
      for (int k = 0; k < 8; k++) accA[8 * (i & 3) + k] += t[k];
    }
  };
  uint4 pv0[8], pv1[8], pv2[8];
  const int row = 128 * mt + 64 * wg + r0;
  uint32_t gt0, gt1;
#pragma unroll
  for (int c2 = 0; c2 < 4; c2++) {
    const int qi = Q_G2 + 4 * c2;
    stage(accA, qi);
    retire(qi - 1);
    stage(accA, qi + 1);
    if (c2 == 3) TL(27);
    if (c2 > 0) put(accB, 2 * c2 - 1);
    if (c2 == 2) gload1(pv0, 1);
    if (c2 == 3) gload1(pv1, 3);
    TL(7 + c2);
    if (c2 == 3) break;
    retire(qi);
    stage(accB, qi + 2);
    retire(qi + 1);
    stage(accB, qi + 3);
    put(accA, 2 * c2);
    if (c2 == 1) gload1(pv0, 0);
    if (c2 == 2) gload1(pv1, 2);
    if (c2 == 0) { gt0 = ld_relaxed(&p.s->gate[row]); gt1 = ld_relaxed(&p.s->gate[row + 8]); }
    retire(qi + 2);
  }
#pragma unroll
  for (int kb = 0; kb < 7; kb++) {
    const int k1 = kb ? kb - 1 : 6, y0 = kb >> 1, y1 = kb ? 4 + (k1 >> 1) : 3;
    const int qa = Q_XR + (kb >> 1), qb = Q_XR + (k1 >> 1);
    mbar_wait(BAR_FULL(sb, wg ? qb % NSTAGE : qa % NSTAGE), wg ? (qb / NSTAGE) & 1 : (qa / NSTAGE) & 1);
    mbar_wait(BAR_Y(sb, wg ? y1 : y0), 0);
    const uint64_t da = mk_desc(sb + (wg ? y_addr(y1) + (kb ? k1 & 1 : 1) * 8192 : y_addr(y0) + (kb & 1) * 8192), 8192, 1024, 1);
    const uint64_t db = mk_desc(sb + SM_RING + (wg ? (qb % NSTAGE) * STAGE_BYTES + (k1 & 1) * 8192 : (qa % NSTAGE) * STAGE_BYTES + (kb & 1) * 8192), 16, 1024, 1);
    wg_fence();
#pragma unroll
    for (int kk = 0; kk < 4; kk++) wgmma_ss_n64<1, 0>(accB, da + kk * 128, db + kk * 2, (kb | kk) != 0);
    wg_commit();
    if (kb == 1) { wg_wait<2>(); fence_regs(accA); TL(15); }
    if (kb == GS0) gsum(pv0, 0);
    if (kb == GL2) gload(pv2, 2);
    if (kb == GS1) gsum(pv1, 1);
  }
  TL(11);
  for (uint32_t n = 0; (((gt0 ^ epoch) | (gt1 ^ epoch)) & 0xffffu) && n < SPIN_LIMIT; n++) {
    gt0 = ld_relaxed(&p.s->gate[row]); gt1 = ld_relaxed(&p.s->gate[row + 8]);
  }
  gsum(pv2, 2);
  const float ga0 = bf_hi(gt0), ga1 = bf_hi(gt1);
  TL(12);
  wg_wait<0>();
  fence_regs(accB);
  TL(13);
  const float gb0 = bf_round(1.f - ga0), gb1 = bf_round(1.f - ga1);
  const float gs0 = ga0 * (2.f / (float)(S_ * D_)), gs1 = ga1 * (2.f / (float)(S_ * D_));
  uint4* const o = reinterpret_cast<uint4*>(p.out + (size_t)row * D_ + 64 * jj + 8 * q);
#pragma unroll
  for (int h = 0; h < 2; h++) {
    const float gs = h ? gs1 : gs0, gb = h ? gb1 : gb0;
#pragma unroll
    for (int k = 0; k < 2; k++) {
      uint32_t w[4];
#pragma unroll
      for (int j = 0; j < 4; j++) {
        const int i = 16 * k + 4 * j + 2 * h;
        w[j] = pack2(fmaf(gs, accB[i], gb * accA[i]), fmaf(gs, accB[i + 1], gb * accA[i + 1]));
      }
      const bool o1 = q & 1, o2 = q & 2;
      uint32_t a = __shfl_xor_sync(0xffffffffu, o1 ? w[0] : w[1], 1), b = __shfl_xor_sync(0xffffffffu, o1 ? w[2] : w[3], 1);
      if (o1) { w[0] = a; w[2] = b; } else { w[1] = a; w[3] = b; }
      a = __shfl_xor_sync(0xffffffffu, o2 ? w[0] : w[2], 2); b = __shfl_xor_sync(0xffffffffu, o2 ? w[1] : w[3], 2);
      if (o2) { w[0] = a; w[1] = b; } else { w[2] = a; w[3] = b; }
      o[h * D_ + 4 * k] = make_uint4(w[0], w[1], w[2], w[3]);
    }
  }
  if (lane == 0) *my_epoch = epoch;
  TL(14);
}

__device__ __forceinline__ void ring_issue(uint32_t sb, const Params& p, int qi, uint32_t slot, bool wait, uint32_t phase, int jj, uint32_t rank) {
  const CUtensorMap* m;
  int c0, c1, c2 = 0;
  bool half = false, is3d = false;
  if (qi < Q_G2) {
    const int nc = __popc(CMASK & ((1u << qi) - 1));
    if ((CMASK >> qi) & 1) {
      m = &p.ct; c0 = 64 * jj; c1 = 128 * nc + 64 * rank; half = nc == 3;
    } else {
      const int pass = qi >= Q_G1B;
      m = rank ? &p.wu : &p.wg; c0 = 0; c1 = 32 * (qi - nc - 14 * pass); c2 = 4 * jj + 2 * pass; is3d = true;
    }
  } else if (qi < Q_P3) {
    int o = jj + 1 + ((qi - Q_G2) >> 1);
    if (o >= 7) o -= 7;
    m = &p.wd; c0 = 64 * o; c1 = 256 * jj + 128 * (qi & 1) + 64 * rank;
  } else {
    m = &p.ct; c0 = 128 * (qi - Q_P3) + 64 * rank; c1 = 64 * jj; half = qi == Q_END - 1;
  }
  uint32_t bar = BAR_FULL(sb, slot), dst = sb + SM_RING + slot * STAGE_BYTES + rank * 8192;
  if (qi >= Q_XR && qi < Q_P3) {
    bar = BAR_X(sb, qi - Q_XR); dst = sb + SM_X + (qi - Q_XR) * 16384 + rank * 8192;
    if (qi == Q_XR) mbar_wait_cluster(BAR_XFREE(sb), 0);
  } else {
    if (wait) mbar_wait_cluster(BAR_EMPTY(sb, slot), phase ^ (qi >= Q_P3));
    mbar_expect_tx(bar, half ? 8192 : 16384);
  }
  if (is3d) tma3d_mc(dst, m, c0, c1, c2, bar);
  else if (!(half && rank)) tma2d_mc(dst, m, c0, c1, bar);
}

__device__ __forceinline__ void ffn_producer(uint32_t sb, const uint8_t* smem, int bid, const Params& p, int warp, int lane, int mt, int jj, uint32_t rank) {
  if (warp < 2) {
    if (lane == 0) {
      uint32_t slot = warp, phase = 0;
#pragma unroll 1
      for (int qi = NSTAGE + warp; qi < Q_END; qi += 2) {
        if (qi < Q_XR || qi >= Q_P3) ring_issue(sb, p, qi, slot, true, phase, jj, rank);
        if (warp == 1 && qi >= Q_G1B + 8 && qi < Q_XR) ring_issue(sb, p, Q_XR + ((qi - Q_G1B - 8) >> 1), 0, false, 0, jj, rank);
        TL(10 + qi);
        slot += 2;
        if (slot >= NSTAGE) { slot -= NSTAGE; phase ^= 1; }
      }
    }
  } else {
    const int wg = warp - 2;
    uint32_t* const my_epoch = &p.s->epoch[blockIdx.x * 12 + 8 + warp];
    const uint32_t epoch = ld_relaxed(my_epoch) + 1;
    if (wg == 0) {
      if (lane == 0) { prefetch_tmap(&p.wd); prefetch_tmap(&p.yt); prefetch_tmap(&p.yt2); }
      {
        const uint4* gw4 = reinterpret_cast<const uint4*>(p.gate_w);
        const uint4 ga = __ldg(gw4 + lane), gb = lane < 24 ? __ldg(gw4 + 32 + lane) : make_uint4(0, 0, 0, 0);
        if (lane < 7) { mbar_wait(BAR_X(sb, lane), 0); mbar_expect_tx(BAR_X(sb, lane), 16384); mbar_expect_tx(BAR_Y(sb, lane), 16384); }
        __syncwarp();
        float mine = 0.f;
#pragma unroll 1
        for (int u = 0; u < 19; u++) {
          const int r = min(19 * jj + u, 127);
          const uint8_t* xr = smem + SM_X + (lane >> 3) * 16384 + r * 128 + (((lane ^ r) & 7) << 4);
          const uint4 xa = *reinterpret_cast<const uint4*>(xr);
          const uint4 xb = lane < 24 ? *reinterpret_cast<const uint4*>(xr + 65536) : make_uint4(0, 0, 0, 0);
          float s = 0.f;
          auto dot2 = [&](uint32_t a, uint32_t b) {
            const uint32_t pr = mul2(a, b);
            s += bf_lo(pr) + bf_hi(pr);
          };
          dot2(xa.x, ga.x); dot2(xa.y, ga.y); dot2(xa.z, ga.z); dot2(xa.w, ga.w);
          dot2(xb.x, gb.x); dot2(xb.y, gb.y); dot2(xb.z, gb.z); dot2(xb.w, gb.w);
#pragma unroll
          for (int o = 16; o > 0; o >>= 1) s += __shfl_xor_sync(0xffffffffu, s, o);
          if (lane == u) mine = s;
        }
        if (lane < 19 && 19 * jj + lane < 128)
          st_relaxed(&p.s->gate[128 * mt + 19 * jj + lane], pack2(0.f, 1.f / (1.f + __expf(-bf_round(mine)))) | (epoch & 0xffffu));
      }
      TL(9);
      if (lane < 2) mbar_arrive_cluster(BAR_XFREE(sb), lane);
    } else {
      mbar_wait(BAR_X(sb, PFAT), 0);
      if (lane < 6) {
        int row = 176 + 3 * bid + (lane >> 1);
        if (row >= D_) row -= D_;
        l2_prefetch(((lane & 1) ? p.pwu : p.pwg) + row * F_, F_ * 2);
      }
      TL(2);
      bar_sync(7, 160);
      if (lane == 0) { red_add(&p.s->cnt_x1[jj * 32], 1);
        l2_prefetch(p.pwd + bid * 16 * D_, 32 * D_); }
      TL(5);
    }
    mbar_wait(BAR_E2(sb, 0), 0);
    TL(3);
    const int yb = 2 * lane + wg, kb = 2 * (yb & 3);
    bool todo = yb < 7, ready = false;
    uint32_t n = 0;
    while (__any_sync(0xffffffffu, todo)) {
      if (todo) {
        uint32_t ok;
        if (!ready) {
          const uint32_t v1 = ld_relaxed(&p.s->cnt_y[min(kb + 1, 6) * 32]);
          asm volatile("ld.acquire.gpu.global.u32 %0, [%1];" : "=r"(ok) : "l"(&p.s->cnt_y[kb * 32]) : "memory");
          ready = (int32_t)(ok - epoch * (kb ? 16 : 17)) >= 0 && (int32_t)(v1 - epoch * 16) >= 0;
        }
        asm volatile("{\n.reg .pred p;\nmbarrier.test_wait.parity.shared::cta.b64 p, [%1], 0;\nselp.u32 %0, 1, 0, p;\n}"
                     : "=r"(ok) : "r"(BAR_E2(sb, yb)) : "memory");
        if ((ok && ready) || ++n > SPIN_LIMIT) {
          tma3d(sb + y_addr(yb), yb == 3 ? &p.yt : &p.yt2, 0, 64 * kb, 2 * mt + (yb >> 2), BAR_Y(sb, yb));
          todo = false;
        }
      }
      __nanosleep(40);
    }
    TL(4);
    if (lane == 0) *my_epoch = epoch;
  }
}

__device__ __forceinline__ void spectral_cta(uint32_t sb, uint8_t* smem, const Params& p, int sc, int wg) {
  const int t384 = threadIdx.x, lane = t384 & 31, warp12 = t384 >> 5, tid = t384 & 127;
  const int warp = tid >> 5, q = lane & 3;
  const int sl0 = 6 * sc + min(sc, 8), nsl = sc < 8 ? 7 : 6;
  if (t384 == 320) {
#pragma unroll 1
    for (int i = 0; i < nsl; i++) {
      mbar_expect_tx(BAR_X(sb, i), 2 * SLAB_BYTES);
      const int row = 128 * ((sl0 + i) >> 3) + 8 * ((sl0 + i) & 7);
      const uint32_t dst = sb + SP_Z + 2 * i * SLAB_BYTES;
      bulk_g2s(dst, p.w_r + row * DF_, SLAB_BYTES / 2, BAR_X(sb, i));
      bulk_g2s(dst + SLAB_BYTES / 2, p.w_r + (row + 64) * DF_, SLAB_BYTES / 2, BAR_X(sb, i));
      bulk_g2s(dst + SLAB_BYTES, p.w_i + row * DF_, SLAB_BYTES / 2, BAR_X(sb, i));
      bulk_g2s(dst + 3 * SLAB_BYTES / 2, p.w_i + (row + 64) * DF_, SLAB_BYTES / 2, BAR_X(sb, i));
    }
  } else if (t384 == 352 && sc < 19) {
    mbar_expect_tx(BAR_Y(sb, 6), 24576);
    bulk_g2s(sb + SP_TW, p.spec, 24576, BAR_Y(sb, 6));
  }
  uint32_t* const my_epoch = &p.s->epoch[blockIdx.x * 12 + warp12];
  const uint32_t epoch = ld_relaxed(my_epoch) + 1;
  uint32_t fe[16], tw[16];
#pragma unroll
  for (int i = 0; i < 4; i++) {
    const uint4 a = __ldg(reinterpret_cast<const uint4*>(p.spec->fe) + i * 128 + tid);
    const uint4 b = __ldg(reinterpret_cast<const uint4*>(p.spec->tw) + i * 128 + tid);
    fe[4 * i] = a.x; fe[4 * i + 1] = a.y; fe[4 * i + 2] = a.z; fe[4 * i + 3] = a.w;
    tw[4 * i] = b.x; tw[4 * i + 1] = b.y; tw[4 * i + 2] = b.z; tw[4 * i + 3] = b.w;
  }
  __syncwarp();
  asm volatile("barrier.cluster.wait.acquire.aligned;" ::: "memory");
#pragma unroll WUNR
  for (int un = wg; un < 8 * nsl; un += 3) {
    const int i = un >> 3, sl = sl0 + i, pr = 16 * (un & 7) + 4 * (lane >> 3) + warp, r = lane & 7;
    mbar_wait(BAR_X(sb, i), 0);
    if (pr < 113) {
      const uint16_t* w = reinterpret_cast<const uint16_t*>(smem + SP_Z + 2 * i * SLAB_BYTES) + r * DF_ + 2 * pr;
      const uint32_t m = pr < 112 ? 0xffffffffu : 0u;
      p.s->wt[pr * 1024 + sl * 8 + (r ^ ((sl >> 2) & 6))] =
          make_uint4(w[0] | ((uint32_t)w[8 * DF_] << 16), w[16 * DF_] | ((uint32_t)w[24 * DF_] << 16),
                     (w[1] | ((uint32_t)w[8 * DF_ + 1] << 16)) & m, (w[16 * DF_ + 1] | ((uint32_t)w[24 * DF_ + 1] << 16)) & m);
    }
  }
  __syncthreads();
  if (t384 == 352) { fence_gpu(); red_add(&p.s->cnt_w[0], 1); TL(2); }
  TL(1);
  if (sc == 19) return;
  const int nrnd = (sc == 18 && wg == 2) ? 1 : 2;
  auto fetch = [&]() {
    const int item = wg + 3 * lane, pr = 6 * sc + item;
    const uint32_t bar = warp ? BAR_Y(sb, item) : BAR_FULL(sb, item);
    mbar_expect_tx(bar, 16384);
    wait_counter(warp ? &p.s->cnt_w[0] : &p.s->cnt_x1[(pr < 112 ? pr >> 4 : 0) * 32], epoch * (warp ? NSPEC : 16));
    if (warp) fence_async();
    bulk_g2s(sb + (warp ? SP_W : SP_Z) + item * 16384, (warp ? p.s->wt : p.s->x1t) + pr * 1024, 16384, bar);
  };
  if (lane < nrnd && warp == 0) fetch();
  __syncwarp();
  fence_regs(fe); fence_regs(tw);
  mbar_wait(BAR_Y(sb, 6), 0);
  TL(3);
  const uint64_t dT_n = mk_desc(sb + SP_T, 8192, 1024, 1);
#pragma unroll 1
  for (int rnd = 0; rnd < nrnd; rnd++) {
    const int item = wg + 3 * rnd, pr = 6 * sc + item;
    const uint32_t z = sb + SP_Z + item * 16384;
    uint32_t fa[16], fb[16];
    auto load_frag = [&](int off) {
#pragma unroll
      for (int i = 0; i < 4; i++) {
        const uint4 a = *reinterpret_cast<const uint4*>(smem + SP_TW + off + i * 2048 + tid * 16);
        fa[4 * i] = a.x; fa[4 * i + 1] = a.y; fa[4 * i + 2] = a.z; fa[4 * i + 3] = a.w;
      }
      fence_regs(fa);
    };
    load_frag(0);
    {
      const uint32_t live = pr == 0 ? 0xddu : (pr == 112 ? 0x11u : 0xffu);
#pragma unroll 1
      for (uint32_t n = 0; n < 4096; n++) {
        mbar_wait(BAR_FULL(sb, item), n & 1);
        uint32_t bad = 0;
#pragma unroll
        for (int i = 0; i < 8; i++) bad |= ((*reinterpret_cast<const volatile uint32_t*>(smem + SP_Z + item * 16384 + i * 2048 + tid * 16) ^ epoch) & 1) << i;
        uint32_t again;
        asm volatile("{\n.reg .pred p, q;\nsetp.ne.u32 p, %1, 0;\nbarrier.red.or.pred q, %2, 128, p;\nselp.u32 %0, 1, 0, q;\n}"
                     : "=r"(again) : "r"(bad & live), "r"(1 + wg) : "memory");
        if (!again) break;
        TL(20);
        if (tid == 0) { mbar_expect_tx(BAR_FULL(sb, item), 16384); bulk_g2s(z, p.s->x1t + pr * 1024, 16384, BAR_FULL(sb, item)); }
      }
    }
    TL(4 + 8 * rnd);
    if (rnd == 0 && wg > 0) bar_sync(3 + wg, 256);
    float aR[32], aI[32];
    {
      const uint64_t de = mk_desc(z, 4096, 512, 2);
      wg_fence();
#pragma unroll
      for (int kk = 0; kk < 4; kk++) {
        wgmma_rs_n64<1, 1>(aR, fe[4 * kk], fe[4 * kk + 1], fe[4 * kk + 2], fe[4 * kk + 3], de + kk * 64, kk != 0);
        wgmma_rs_n64<1, 1>(aI, fa[4 * kk], fa[4 * kk + 1], fa[4 * kk + 2], fa[4 * kk + 3], de + 512 + kk * 64, kk != 0);
      }
      wg_commit();
      if (rnd == 0 && wg < 2) bar_arrive(4 + wg, 256);
      if (rnd == 0 && lane < nrnd && warp == 1) fetch();
      __syncwarp();
      wg_wait<0>();
      fence_regs(aR); fence_regs(aI);
    }
    TL(5 + 8 * rnd);
#pragma unroll
    for (int v = 0; v < 8; v++) {
      uint32_t* f = (v < 4 ? fa : fb) + 2 * (v & 3);
      const uint32_t* t = tw + 2 * (v & 3);
      const float *e = aR + 4 * v, *o = aI + 4 * v;
      const uint32_t er = pack2(e[0], e[1]), ei = pack2(e[2], e[3]), qr = pack2(o[0], o[1]), qi = pack2(o[2], o[3]);
      const uint32_t u0r = add2(er, qr), u0i = add2(ei, qi), u1r = sub2(er, qr), u1i = sub2(ei, qi);
      f[0] = fma2(u0r, t[0], mul2(u0i, t[8]));
      f[8] = fms2(u0i, t[0], mul2(u0r, t[8]));
      f[1] = fma2(u1r, t[1], mul2(u1i, t[9]));
      f[9] = fms2(u1i, t[1], mul2(u1r, t[9]));
    }
    fence_regs(fa); fence_regs(fb);
    wg_fence();
#pragma unroll
    for (int kk = 0; kk < 4; kk++) {
      wgmma_rs_n64<1, 1>(aR, fa[4 * kk], fa[4 * kk + 1], fa[4 * kk + 2], fa[4 * kk + 3], dT_n + kk * 128, kk != 0);
      wgmma_rs_n64<1, 1>(aI, fb[4 * kk], fb[4 * kk + 1], fb[4 * kk + 2], fb[4 * kk + 3], dT_n + kk * 128, kk != 0);
    }
    wg_commit();
    mbar_wait(BAR_Y(sb, item), 0);
    wg_wait<0>();
    fence_regs(aR); fence_regs(aI);
    TL(6 + 8 * rnd);
    {
      const uint8_t* wp = smem + SP_W + item * 16384 + q * 1024 + warp * 128 + (((lane >> 2) ^ (2 * q)) << 4);
#pragma unroll
      for (int jb = 0; jb < 4; jb++) {
#pragma unroll
        for (int h = 0; h < 2; h++) {
          const uint4 w = *reinterpret_cast<const uint4*>(wp + jb * 4096 + h * 512);
          const int i = 4 * jb + 2 * h;
          const uint32_t ar = pack2(aR[i], aR[i + 1]), ai = pack2(aR[16 + i], aR[17 + i]);
          const uint32_t br = pack2(aI[i], aI[i + 1]), bi = pack2(aI[16 + i], aI[17 + i]);
          fa[2 * jb + h] = fms2(ar, w.x, mul2(ai, w.y));
          fa[8 + 2 * jb + h] = fma2(ar, w.y, mul2(ai, w.x));
          fb[2 * jb + h] = fms2(br, w.z, mul2(bi, w.w));
          fb[8 + 2 * jb + h] = fma2(br, w.w, mul2(bi, w.z));
        }
      }
    }
    fence_regs(fa); fence_regs(fb);
    wg_fence();
#pragma unroll
    for (int kk = 0; kk < 4; kk++) {
      wgmma_rs_n64<1, 0>(aR, fa[4 * kk], fa[4 * kk + 1], fa[4 * kk + 2], fa[4 * kk + 3], dT_n + kk * 2, kk != 0);
      wgmma_rs_n64<1, 0>(aI, fb[4 * kk], fb[4 * kk + 1], fb[4 * kk + 2], fb[4 * kk + 3], dT_n + kk * 2, kk != 0);
    }
    wg_commit();
    wg_wait<0>();
    fence_regs(aR); fence_regs(aI);
    TL(7 + 8 * rnd);
#pragma unroll
    for (int v = 0; v < 8; v++) {
      const float* a = (v < 4 ? aR : aI) + 4 * (v & 3);
      const uint32_t* t = tw + 2 * (v & 3);
      const uint32_t u0r = pack2(a[0], a[1]), u1r = pack2(a[2], a[3]), u0i = pack2(a[16], a[17]), u1i = pack2(a[18], a[19]);
      const uint32_t t0r = fms2(u0r, t[0], mul2(u0i, t[8])), t0i = fma2(u0i, t[0], mul2(u0r, t[8]));
      const uint32_t t1r = fms2(u1r, t[1], mul2(u1i, t[9])), t1i = fma2(u1i, t[1], mul2(u1r, t[9]));
      fa[v] = add2(t0i, t1i); fa[8 + v] = add2(t0r, t1r);
      fb[v] = sub2(t0i, t1i); fb[8 + v] = sub2(t0r, t1r);
    }
    bar_sync(1 + wg, 128);
#pragma unroll
    for (int u = 0; u < 4; u++) {
      const uint32_t a = z + (32 * (u >> 1) + 8 * warp + (lane & 7)) * 128 + (((4 * (u & 1) + (lane >> 3)) ^ (lane & 7)) << 4);
      stmatrix_x4(a, fa[4 * u], fa[4 * u + 1], fa[4 * u + 2], fa[4 * u + 3]);
      stmatrix_x4(a + 8192, fb[4 * u], fb[4 * u + 1], fb[4 * u + 2], fb[4 * u + 3]);
    }
    load_frag(8192);
    fence_async_smem();
    bar_sync(1 + wg, 128);
    TL(8 + 8 * rnd);
    {
      const uint64_t de = mk_desc(z, 8192, 1024, 1);
      wg_fence();
#pragma unroll
      for (int kk = 0; kk < 4; kk++) {
        wgmma_rs_n64<1, 1>(aR, fe[4 * kk], fe[4 * kk + 1], fe[4 * kk + 2], fe[4 * kk + 3], de + kk * 128, kk != 0);
        wgmma_rs_n64<1, 1>(aI, fa[4 * kk], fa[4 * kk + 1], fa[4 * kk + 2], fa[4 * kk + 3], de + 512 + kk * 128, kk != 0);
      }
      wg_commit();
      wg_wait<0>();
      fence_regs(aR); fence_regs(aI);
    }
    TL(9 + 8 * rnd);
    const bool edge = pr == 0 || pr == 112;
    if (edge) {
#pragma unroll
      for (int i = 0; i < 16; i++) { aR[i] *= 0.5f; aI[i] *= 0.5f; }
    }
#pragma unroll
    for (int i = 0; i < 8; i++) {
      const float* a = ((i & 1) ? aI : aR) + 16 * (i >> 2) + 2 - (i & 2);
      *reinterpret_cast<uint4*>(smem + SP_W + item * 16384 + (i >> 1) * 4096 + (i & 1) * 64 + (tid >> 2) * 128 + q * 16) =
          make_uint4(pack2(a[0], a[1]), pack2(a[4], a[5]), pack2(a[8], a[9]), pack2(a[12], a[13]));
    }
    fence_async_smem();
    bar_sync(1 + wg, 128);
    if (tid == 0) {
      const uint32_t src = sb + SP_W + item * 16384;
      __nv_bfloat16* dst = p.s->yt + (size_t)(pr < 112 ? 4 * pr : 1) * S_;
      bulk_s2g(dst, src, edge ? 4096 : 16384);
      if (pr == 0) bulk_s2g(dst + 2 * S_, src + 8192, 8192);
      asm volatile("cp.async.bulk.commit_group;" ::: "memory");
      if (rnd == nrnd - 1) {
        asm volatile("cp.async.bulk.wait_group 0;" ::: "memory");
        TL(11);
        red_add(&p.s->cnt_y[(pr < 112 ? pr >> 4 : 0) * 32], 1);
        if (rnd) red_add(&p.s->cnt_y[((pr - 3) >> 4) * 32], 1);
      }
    }
    __syncwarp();
    TL(10 + 8 * rnd);
  }
  if (lane == 0) *my_epoch = epoch;
}

__global__ void __cluster_dims__(2, 1, 1) __launch_bounds__(384, 1)
fused_kernel(const __grid_constant__ Params p) {
  extern __shared__ __align__(1024) uint8_t smem[];
  const uint32_t sb = smem_u32(smem);
  TL(0);
  const uint32_t rank = blockIdx.x & 1;
  const int hc = blockIdx.x >> 1;
  int grp, jj;
  if (hc < 4) { grp = 8; jj = hc; }
  else if (hc < 36) { grp = (hc - 4) & 7; jj = (hc - 4) >> 3; }
  else if (hc < 57) { jj = (hc - 36) / 7; grp = 1 + (hc - 36) - 7 * jj; jj += 4; }
  else if (hc < 60) { grp = 0; jj = hc - 53; }
  else { grp = 8; jj = hc - 56; }
  const int mt = 2 * grp + rank, bid = 2 * (7 * grp + jj) + rank;
  if (threadIdx.x == 256) {
#pragma unroll
    for (int i = 0; i < NSTAGE; i++) { mbar_init(BAR_FULL(sb, i), 1); mbar_init(BAR_EMPTY(sb, i), 4); }
    asm volatile("fence.mbarrier_init.release.cluster;" ::: "memory");
  } else if (threadIdx.x == 320) {
    mbar_init(BAR_X(sb, 0), 1);
    if (bid < NFFN) {
      mbar_expect_tx(BAR_X(sb, 0), 16384);
      tma2d(sb + SM_X, &p.x, 0, 128 * mt, BAR_X(sb, 0));
    }
#pragma unroll
    for (int i = 1; i < NSTAGE; i++) mbar_init(BAR_X(sb, i), 1);
    mbar_init(BAR_XFREE(sb), 2);
    asm volatile("fence.mbarrier_init.release.cluster;" ::: "memory");
  } else if (threadIdx.x == 352) {
#pragma unroll
    for (int i = 0; i < NSTAGE; i++) { mbar_init(BAR_Y(sb, i), 1); mbar_init(BAR_E2(sb, i), 2); }
    asm volatile("fence.mbarrier_init.release.cluster;" ::: "memory");
  } else if (threadIdx.x == 288 && bid < NFFN) {
#pragma unroll
    for (int i = 0; i < EPF; i++)
      asm volatile("cp.async.bulk.prefetch.tensor.3d.L2.global [%0, {%1, %2, %3}];" ::"l"(rank ? &p.wu : &p.wg), "r"(0), "r"(32 * i), "r"(4 * jj) : "memory");
    prefetch_tmap(rank ? &p.wu : &p.wg); prefetch_tmap(&p.ct);
  }
  __syncwarp();
  asm volatile("barrier.cluster.arrive.relaxed.aligned;" ::: "memory");
  const int wg = __shfl_sync(0xffffffffu, threadIdx.x >> 7, 0);
  if (bid >= NFFN) {
    spectral_cta(sb, smem, p, bid - NFFN, wg);
  } else if (wg < 2) {
    asm volatile("setmaxnreg.inc.sync.aligned.u32 232;");
    asm volatile("barrier.cluster.wait.acquire.aligned;" ::: "memory");
    TL(1);
    ffn_consumer(sb, smem, p, bid, wg, threadIdx.x & 127, mt, jj);
  } else {
    asm volatile("setmaxnreg.dec.sync.aligned.u32 40;");
    asm volatile("barrier.cluster.wait.acquire.aligned;" ::: "memory");
    TL(1);
    if (threadIdx.x == 320) {
      constexpr int order[13] = {XORDER};
#pragma unroll
      for (int i = 0; i < 13; i++) {
        if (order[i] < 8) {
          ring_issue(sb, p, order[i], order[i], false, 0, jj, rank);
        } else {
          const int kb = order[i] - 10;
          mbar_expect_tx(BAR_X(sb, kb), 16384);
          tma2d(sb + SM_X + kb * 16384, &p.x, 64 * kb, 128 * mt, BAR_X(sb, kb));
        }
      }
      TL(2);
    }
    __syncwarp();
    ffn_producer(sb, smem, bid, p, (threadIdx.x >> 5) & 3, threadIdx.x & 31, mt, jj, rank);
  }
}

typedef CUresult (*EncodeFn)(CUtensorMap*, CUtensorMapDataType, cuuint32_t, void*, const cuuint64_t*, const cuuint64_t*,
                             const cuuint32_t*, const cuuint32_t*, CUtensorMapInterleave, CUtensorMapSwizzle,
                             CUtensorMapL2promotion, CUtensorMapFloatOOBfill);

void make_map(EncodeFn fn, CUtensorMap* m, const void* base, int rank, const cuuint64_t* dims, const cuuint64_t* strides,
              const cuuint32_t* box, CUtensorMapSwizzle sw) {
  const cuuint32_t es[4] = {1, 1, 1, 1};
  fn(m, CU_TENSOR_MAP_DATA_TYPE_BFLOAT16, rank, const_cast<void*>(base), dims, strides, box, es,
     CU_TENSOR_MAP_INTERLEAVE_NONE, sw, CU_TENSOR_MAP_L2_PROMOTION_L2_256B, CU_TENSOR_MAP_FLOAT_OOB_FILL_NONE);
}

}

extern "C" void kernel_launch(void* const* d_in, const int* in_sizes, int n_in, void* d_out, int out_size) {
  const __nv_bfloat16* x = (const __nv_bfloat16*)d_in[0];
  const __nv_bfloat16* w_r = (const __nv_bfloat16*)d_in[1];
  const __nv_bfloat16* w_i = (const __nv_bfloat16*)d_in[2];
  const __nv_bfloat16* wg = (const __nv_bfloat16*)d_in[4];
  const __nv_bfloat16* wu = (const __nv_bfloat16*)d_in[5];
  const __nv_bfloat16* wd = (const __nv_bfloat16*)d_in[6];
  const __nv_bfloat16* gate_w = (const __nv_bfloat16*)d_in[7];

  void* fnp = nullptr;
  cudaDriverEntryPointQueryResult qr;
  cudaGetDriverEntryPoint("cuTensorMapEncodeTiled", &fnp, cudaEnableDefault, &qr);
  EncodeFn fn = (EncodeFn)fnp;
  void *ctab, *spec, *scr;
  cudaGetSymbolAddress(&ctab, g_ctab);
  cudaGetSymbolAddress(&spec, g_spec);
  cudaGetSymbolAddress(&scr, g_scratch);
  const void* yt = (const char*)scr + offsetof(Scratch, yt);
  Params p;
  p.s = (Scratch*)scr; p.out = (__nv_bfloat16*)d_out;
  p.px = x; p.w_r = w_r; p.w_i = w_i; p.gate_w = gate_w; p.pwg = wg; p.pwu = wu; p.pwd = wd;
  p.ctab = (const tab::Table*)ctab; p.spec = (const tab::Spec*)spec;
  {
    const cuuint64_t d[2] = {D_, S_}, s[1] = {D_ * 2};
    const cuuint32_t b[2] = {64, 128};
    make_map(fn, &p.x, x, 2, d, s, b, CU_TENSOR_MAP_SWIZZLE_128B);
  }
  {
    const cuuint64_t d[3] = {64, D_, F_ / 64}, s[2] = {F_ * 2, 128};
    const cuuint32_t b[3] = {64, 32, 2};
    make_map(fn, &p.wg, wg, 3, d, s, b, CU_TENSOR_MAP_SWIZZLE_128B);
    make_map(fn, &p.wu, wu, 3, d, s, b, CU_TENSOR_MAP_SWIZZLE_128B);
  }
  {
    const cuuint64_t d[2] = {D_, F_}, s[1] = {D_ * 2};
    const cuuint32_t b[2] = {64, 64};
    make_map(fn, &p.wd, wd, 2, d, s, b, CU_TENSOR_MAP_SWIZZLE_128B);
  }
  {
    const cuuint64_t d[2] = {D_, D_}, s[1] = {D_ * 2};
    const cuuint32_t b[2] = {64, 64};
    make_map(fn, &p.ct, ctab, 2, d, s, b, CU_TENSOR_MAP_SWIZZLE_128B);
  }
  {
    const cuuint64_t d[3] = {64, D_, S_ / 64}, s[2] = {S_ * 2, 128};
    const cuuint32_t b[3] = {64, 64, 2};
    const cuuint32_t b2[3] = {64, 128, 1};
    make_map(fn, &p.yt, yt, 3, d, s, b, CU_TENSOR_MAP_SWIZZLE_128B);
    make_map(fn, &p.yt2, yt, 3, d, s, b2, CU_TENSOR_MAP_SWIZZLE_128B);
  }
  cudaFuncSetAttribute(fused_kernel, cudaFuncAttributeMaxDynamicSharedMemorySize, SM_TOTAL);
  fused_kernel<<<NCTA, 384, SM_TOTAL, cudaStreamPerThread>>>(p, x, w_r, w_i, gate_w, wd, (__nv_bfloat16*)d_out);
}
```

```cpp
#include <cuda_runtime.h>
#include <cuda_bf16.h>
#include <cuda.h>
#include <stdint.h>
#include <stddef.h>

namespace {

constexpr int S_ = 2048, D_ = 448, F_ = 1792, DF_ = 225;
constexpr int NFFN = 112, NSPEC = 20, NCTA = NFFN + NSPEC;
constexpr int NSTAGE = 7, STAGE_BYTES = 16384;
constexpr int SM_X = 0, SM_RING = 114688, SM_BAR = 229376, SM_TOTAL = SM_BAR + 512;
constexpr int SP_Z = 0, SP_W = 98304, SP_TW = 198656, SP_T = 215040, SLAB_BYTES = 16 * DF_ * 2;
constexpr uint32_t SPIN_LIMIT = 1u << 20;

namespace tab {
constexpr double PI = 3.14159265358979323846264338327950288;
constexpr double csin(double x) {
  double t = x, s = x;
  for (int i = 1; i < 20; i++) { t = -t * x * x / ((2 * i) * (2 * i + 1)); s += t; }
  return s;
}
constexpr double ccos(double x) {
  double t = 1, s = 1;
  for (int i = 1; i < 20; i++) { t = -t * x * x / ((2 * i - 1) * (2 * i)); s += t; }
  return s;
}
constexpr uint32_t to_bf16(double v) {
  uint32_t sign = v < 0 ? 0x8000u : 0u;
  double a = v < 0 ? -v : v;
  if (a < 1e-12) return 0;
  int e = 0;
  while (a >= 2.0) { a /= 2; e++; }
  while (a < 1.0) { a *= 2; e--; }
  double m = a * 128.0;
  int mi = (int)m;
  double fr = m - mi;
  if (fr > 0.5 || (fr == 0.5 && (mi & 1))) mi++;
  if (mi == 256) { mi = 128; e++; }
  return sign | (uint32_t)((e + 127) << 7) | (uint32_t)(mi - 128);
}
struct Base { uint32_t v[448]; };
constexpr Base make_base() {
  Base b{};
  for (int m = 0; m < 448; m++) {
    int mm = m > 224 ? m - 448 : m;
    double ang = 2 * PI * mm / 448.0;
    b.v[m] = to_bf16(ccos(ang)) | (to_bf16(-csin(ang)) << 16);
  }
  return b;
}
constexpr Base base = make_base();
struct Row { uint32_t v[224]; };
constexpr Row make_row(int d) {
  Row r{};
  r.v[0] = 0x3f80u | ((d & 1) ? 0xbf800000u : 0x3f800000u);
  int m = 0;
  for (int c = 1; c < 224; c++) { m += d; if (m >= 448) m -= 448; r.v[c] = base.v[m]; }
  return r;
}
struct Table { Row r[448]; };
constexpr Table make_table() {
  Table t{};
  for (int d = 0; d < 448; d++) t.r[d] = make_row(d);
  return t;
}
struct Cs { double c[2048], s[2048]; };
constexpr Cs make_cs() {
  Cs t{};
  for (int m = 0; m <= 256; m++) {
    const double a = 2 * PI * m / 2048.0, c = ccos(a), s = csin(a);
    t.c[m] = c; t.s[m] = s;
    t.c[512 - m] = s; t.s[512 - m] = c;
  }
  for (int m = 513; m < 2048; m++) { t.c[m] = -t.s[m - 512]; t.s[m] = t.c[m - 512]; }
  return t;
}
constexpr Cs cs = make_cs();
struct Spec {
  uint32_t fo[2048], fot[2048];
  uint16_t t32[4096];
  uint32_t fe[2048];
  uint32_t tw[2048];
};
constexpr uint32_t blk(int h, int c, int a) { return to_bf16(h == c ? cs.c[a & 2047] : (h ? -cs.s[a & 2047] : cs.s[a & 2047])); }
constexpr Spec make_spec() {
  Spec t{};
  for (int row = 0; row < 64; row++)
    for (int col = 0; col < 64; col++) {
      const int c = row & 31, k2 = col & 31, n2 = 8 * ((c >> 1) & 3) + 2 * (c >> 3) + (c & 1), m = 64 * ((n2 * k2) & 31);
      const double v = (row >> 5) == (col >> 5) ? cs.c[m] : (row < 32 ? -cs.s[m] : cs.s[m]);
      t.t32[row * 64 + (((col >> 3) ^ (row & 7)) << 3) + (col & 7)] = (uint16_t)to_bf16(v);
    }
  for (int th = 0; th < 128; th++)
    for (int i = 0; i < 16; i++) {
      const int r = 8 * (th >> 5) + ((th & 31) >> 2), h = i & 1, c = i >> 3, m = 8 * ((i >> 1) & 3) + 2 * (th & 3);
      const int o = ((i >> 2) * 128 + th) * 4 + (i & 3);
      t.fe[o] = blk(h, c, 64 * m * r) | (blk(h, c, 64 * (m + 1) * r) << 16);
      t.fo[o] = blk(h, c, 32 * (2 * m + 1) * r) | (blk(h, c, 32 * (2 * m + 3) * r) << 16);
      t.fot[o] = blk(h, c, 32 * (2 * r + 1) * m) | (blk(h, c, 32 * (2 * r + 1) * (m + 1)) << 16);
      const int k1 = r + 32 * h, n2 = 8 * (th & 3) + 2 * ((i >> 1) & 3);
      t.tw[o] = blk(0, c, n2 * k1) | (blk(0, c, (n2 + 1) * k1) << 16);
    }
  return t;
}
}
}

__device__ __align__(1024) const tab::Table g_ctab = tab::make_table();
__device__ __align__(1024) const tab::Spec g_spec = tab::make_spec();

struct Scratch {
  uint32_t cnt_w[32];
  uint32_t cnt_x1[7 * 32];
  uint32_t cnt_y[7 * 32];
  uint32_t epoch[NCTA * 12 + 240 + 256];
  uint32_t gate[S_];
  uint4 x1t[113 * 1024];
  __nv_bfloat16 yt[D_ * S_];
  uint4 wt[114 * 1024];
  uint4 part[16 * 7 * 6 * 2 * 4 * 128];
};
static_assert(offsetof(Scratch, x1t) % 1024 == 0, "alignment");
__device__ __align__(1024) Scratch g_scratch;
#define TL(i)

namespace {

struct Params {
  Scratch* s;
  __nv_bfloat16* out;
  const __nv_bfloat16 *px, *w_r, *w_i, *gate_w, *pwg, *pwu, *pwd;
  const tab::Table* ctab;
  const tab::Spec* spec;
  CUtensorMap x, wg, wu, wd, ct, yt, yt2;
};

__device__ __forceinline__ uint32_t smem_u32(const void* p) { return (uint32_t)__cvta_generic_to_shared(p); }
__device__ __forceinline__ void mbar_init(uint32_t bar, uint32_t cnt) {
  asm volatile("mbarrier.init.shared::cta.b64 [%0], %1;" ::"r"(bar), "r"(cnt) : "memory");
}
__device__ __forceinline__ void mbar_expect_tx(uint32_t bar, uint32_t bytes) {
  asm volatile("mbarrier.arrive.expect_tx.shared::cta.b64 _, [%0], %1;" ::"r"(bar), "r"(bytes) : "memory");
}
__device__ __forceinline__ void mbar_arrive(uint32_t bar) {
  asm volatile("mbarrier.arrive.shared::cta.b64 _, [%0];" ::"r"(bar) : "memory");
}
__device__ __forceinline__ void mbar_arrive_cluster(uint32_t bar, uint32_t cta) {
  asm volatile("{\n.reg .b32 ra;\nmapa.shared::cluster.u32 ra, %0, %1;\n"
               "mbarrier.arrive.shared::cluster.b64 _, [ra];\n}" ::"r"(bar), "r"(cta) : "memory");
}
__device__ __forceinline__ void mbar_wait(uint32_t bar, uint32_t parity) {
  uint32_t ok, n = 0;
  do {
    asm volatile("{\n.reg .pred p;\nmbarrier.try_wait.parity.shared::cta.b64 p, [%1], %2;\nselp.u32 %0, 1, 0, p;\n}"
                 : "=r"(ok) : "r"(bar), "r"(parity) : "memory");
  } while (!ok && ++n < SPIN_LIMIT);
}
__device__ __forceinline__ void mbar_wait_cluster(uint32_t bar, uint32_t parity) {
  uint32_t ok, n = 0;
  do {
    asm volatile("{\n.reg .pred p;\nmbarrier.try_wait.parity.acquire.cluster.shared::cta.b64 p, [%1], %2;\nselp.u32 %0, 1, 0, p;\n}"
                 : "=r"(ok) : "r"(bar), "r"(parity) : "memory");
  } while (!ok && ++n < SPIN_LIMIT);
}
__device__ __forceinline__ void tma2d(uint32_t dst, const CUtensorMap* m, int c0, int c1, uint32_t bar) {
  asm volatile("cp.async.bulk.tensor.2d.shared::cluster.global.mbarrier::complete_tx::bytes [%0], [%1, {%3, %4}], [%2];"
               ::"r"(dst), "l"(m), "r"(bar), "r"(c0), "r"(c1) : "memory");
}
__device__ __forceinline__ void tma3d(uint32_t dst, const CUtensorMap* m, int c0, int c1, int c2, uint32_t bar) {
  asm volatile("cp.async.bulk.tensor.3d.shared::cluster.global.mbarrier::complete_tx::bytes [%0], [%1, {%3, %4, %5}], [%2];"
               ::"r"(dst), "l"(m), "r"(bar), "r"(c0), "r"(c1), "r"(c2) : "memory");
}
__device__ __forceinline__ void tma2d_mc(uint32_t dst, const CUtensorMap* m, int c0, int c1, uint32_t bar) {
  asm volatile("cp.async.bulk.tensor.2d.shared::cluster.global.mbarrier::complete_tx::bytes.multicast::cluster [%0], [%1, {%3, %4}], [%2], %5;"
               ::"r"(dst), "l"(m), "r"(bar), "r"(c0), "r"(c1), "h"((uint16_t)3) : "memory");
}
__device__ __forceinline__ void tma3d_mc(uint32_t dst, const CUtensorMap* m, int c0, int c1, int c2, uint32_t bar) {
  asm volatile("cp.async.bulk.tensor.3d.shared::cluster.global.mbarrier::complete_tx::bytes.multicast::cluster [%0], [%1, {%3, %4, %5}], [%2], %6;"
               ::"r"(dst), "l"(m), "r"(bar), "r"(c0), "r"(c1), "r"(c2), "h"((uint16_t)3) : "memory");
}
__device__ __forceinline__ void bulk_g2s(uint32_t dst, const void* src, uint32_t bytes, uint32_t bar) {
  asm volatile("cp.async.bulk.shared::cluster.global.mbarrier::complete_tx::bytes [%0], [%1], %2, [%3];"
               ::"r"(dst), "l"(src), "r"(bytes), "r"(bar) : "memory");
}
__device__ __forceinline__ void bulk_s2g(void* dst, uint32_t src, uint32_t bytes) {
  asm volatile("cp.async.bulk.global.shared::cta.bulk_group [%0], [%1], %2;" ::"l"(dst), "r"(src), "r"(bytes) : "memory");
}
__device__ __forceinline__ void prefetch_tmap(const CUtensorMap* m) {
  asm volatile("prefetch.tensormap [%0];" ::"l"(m) : "memory");
}
__device__ __forceinline__ void l2_prefetch(const void* p, uint32_t bytes) {
  asm volatile("cp.async.bulk.prefetch.L2.global [%0], %1;" ::"l"(p), "r"(bytes) : "memory");
}
__device__ __forceinline__ void wg_fence() { asm volatile("wgmma.fence.sync.aligned;" ::: "memory"); }
__device__ __forceinline__ void wg_commit() { asm volatile("wgmma.commit_group.sync.aligned;" ::: "memory"); }
template <int N> __device__ __forceinline__ void wg_wait() { asm volatile("wgmma.wait_group.sync.aligned %0;" ::"n"(N) : "memory"); }
template <int N> __device__ __forceinline__ void fence_regs(float (&d)[N]) {
#pragma unroll
  for (int i = 0; i < N; i++) asm volatile("" : "+f"(d[i])::"memory");
}
template <int N> __device__ __forceinline__ void fence_regs(uint32_t (&d)[N]) {
#pragma unroll
  for (int i = 0; i < N; i++) asm volatile("" : "+r"(d[i])::"memory");
}
__device__ __forceinline__ void bar_sync(int id, int n) { asm volatile("bar.sync %0, %1;" ::"r"(id), "r"(n) : "memory"); }
__device__ __forceinline__ void bar_arrive(int id, int n) { asm volatile("bar.arrive %0, %1;" ::"r"(id), "r"(n) : "memory"); }
__device__ __forceinline__ void fence_gpu() { asm volatile("fence.acq_rel.gpu;" ::: "memory"); }
__device__ __forceinline__ void fence_async() { asm volatile("fence.proxy.async;" ::: "memory"); }
__device__ __forceinline__ void fence_async_smem() { asm volatile("fence.proxy.async.shared::cta;" ::: "memory"); }
__device__ __forceinline__ void red_add(uint32_t* p, uint32_t v) {
  asm volatile("red.relaxed.gpu.global.add.u32 [%0], %1;" ::"l"(p), "r"(v) : "memory");
}
__device__ __forceinline__ uint32_t ld_relaxed(const uint32_t* p) {
  uint32_t v;
  asm volatile("ld.relaxed.gpu.global.u32 %0, [%1];" : "=r"(v) : "l"(p) : "memory");
  return v;
}
__device__ __forceinline__ void wait_counter(const uint32_t* p, uint32_t target) {
  uint32_t v, n = 0;
  while (true) {
    asm volatile("ld.acquire.gpu.global.u32 %0, [%1];" : "=r"(v) : "l"(p) : "memory");
    if ((int32_t)(v - target) >= 0 || ++n > SPIN_LIMIT) break;
  }
}
__device__ __forceinline__ uint4 ld_relaxed(const uint4* p) {
  uint4 v;
  asm volatile("ld.relaxed.gpu.global.v4.u32 {%0, %1, %2, %3}, [%4];" : "=r"(v.x), "=r"(v.y), "=r"(v.z), "=r"(v.w) : "l"(p) : "memory");
  return v;
}
__device__ __forceinline__ void st_relaxed(uint4* p, uint4 v) {
  asm volatile("st.relaxed.gpu.global.v4.u32 [%0], {%1, %2, %3, %4};" ::"l"(p), "r"(v.x), "r"(v.y), "r"(v.z), "r"(v.w) : "memory");
}
__device__ __forceinline__ void st_relaxed(uint32_t* p, uint32_t v) {
  asm volatile("st.relaxed.gpu.global.u32 [%0], %1;" ::"l"(p), "r"(v) : "memory");
}
__device__ __forceinline__ uint32_t pack2(float lo, float hi) {
  uint32_t r;
  asm("cvt.rn.bf16x2.f32 %0, %1, %2;" : "=r"(r) : "f"(hi), "f"(lo));
  return r;
}
__device__ __forceinline__ uint32_t mul2(uint32_t a, uint32_t b) {
  uint32_t r;
  asm("mul.rn.bf16x2 %0, %1, %2;" : "=r"(r) : "r"(a), "r"(b));
  return r;
}
__device__ __forceinline__ uint32_t fma2(uint32_t a, uint32_t b, uint32_t c) {
  uint32_t r;
  asm("fma.rn.bf16x2 %0, %1, %2, %3;" : "=r"(r) : "r"(a), "r"(b), "r"(c));
  return r;
}
__device__ __forceinline__ uint32_t add2(uint32_t a, uint32_t b) {
  uint32_t r;
  asm("add.rn.bf16x2 %0, %1, %2;" : "=r"(r) : "r"(a), "r"(b));
  return r;
}
__device__ __forceinline__ uint32_t sub2(uint32_t a, uint32_t b) {
  uint32_t r;
  asm("sub.rn.bf16x2 %0, %1, %2;" : "=r"(r) : "r"(a), "r"(b));
  return r;
}
__device__ __forceinline__ uint32_t fms2(uint32_t a, uint32_t b, uint32_t c) {
  uint32_t r;
  asm("{\n.reg .b32 n;\nneg.bf16x2 n, %3;\nfma.rn.bf16x2 %0, %1, %2, n;\n}" : "=r"(r) : "r"(a), "r"(b), "r"(c));
  return r;
}
__device__ __forceinline__ float bf_lo(uint32_t v) { return __uint_as_float(v << 16); }
__device__ __forceinline__ float bf_hi(uint32_t v) { return __uint_as_float(v & 0xffff0000u); }
__device__ __forceinline__ float bf_round(float v) { return bf_lo(pack2(v, 0.f)); }
__device__ __forceinline__ float tanh_fast(float v) {
  float r;
  asm("tanh.approx.f32 %0, %1;" : "=f"(r) : "f"(v));
  return r;
}
__device__ __forceinline__ uint64_t mk_desc(uint32_t addr, uint32_t lbo, uint32_t sbo, uint32_t mode) {
  return (uint64_t)((addr & 0x3FFFF) >> 4) | ((uint64_t)(lbo >> 4) << 16) | ((uint64_t)(sbo >> 4) << 32) | ((uint64_t)mode << 62);
}
__device__ __forceinline__ void stmatrix_x4(uint32_t addr, uint32_t r0, uint32_t r1, uint32_t r2, uint32_t r3) {
  asm volatile("stmatrix.sync.aligned.m8n8.x4.shared.b16 [%0], {%1, %2, %3, %4};" ::"r"(addr), "r"(r0), "r"(r1), "r"(r2), "r"(r3) : "memory");
}

template <int TA, int TB>
__device__ __forceinline__ void wgmma_ss_n256(float (&d)[128], uint64_t da, uint64_t db, int sd) {
  asm volatile("{\n.reg .pred p;\nsetp.ne.b32 p, %130, 0;\n"
      "wgmma.mma_async.sync.aligned.m64n256k16.f32.bf16.bf16 {"
      "%0, %1, %2, %3, %4, %5, %6, %7, %8, %9, %10, %11, %12, %13, %14, %15, %16, %17, %18, %19, %20, %21, %22, %23, "
      "%24, %25, %26, %27, %28, %29, %30, %31, %32, %33, %34, %35, %36, %37, %38, %39, %40, %41, %42, %43, %44, %45, "
      "%46, %47, %48, %49, %50, %51, %52, %53, %54, %55, %56, %57, %58, %59, %60, %61, %62, %63, %64, %65, %66, %67, "
      "%68, %69, %70, %71, %72, %73, %74, %75, %76, %77, %78, %79, %80, %81, %82, %83, %84, %85, %86, %87, %88, %89, "
      "%90, %91, %92, %93, %94, %95, %96, %97, %98, %99, %100, %101, %102, %103, %104, %105, %106, %107, %108, %109, "
      "%110, %111, %112, %113, %114, %115, %116, %117, %118, %119, %120, %121, %122, %123, %124, %125, %126, %127"
      "}, %128, %129, p, 1, 1, %131, %132;\n}\n"
      : "+f"(d[0]), "+f"(d[1]), "+f"(d[2]), "+f"(d[3]), "+f"(d[4]), "+f"(d[5]), "+f"(d[6]), "+f"(d[7]), "+f"(d[8]),
        "+f"(d[9]), "+f"(d[10]), "+f"(d[11]), "+f"(d[12]), "+f"(d[13]), "+f"(d[14]), "+f"(d[15]), "+f"(d[16]),
        "+f"(d[17]), "+f"(d[18]), "+f"(d[19]), "+f"(d[20]), "+f"(d[21]), "+f"(d[22]), "+f"(d[23]), "+f"(d[24]),
        "+f"(d[25]), "+f"(d[26]), "+f"(d[27]), "+f"(d[28]), "+f"(d[29]), "+f"(d[30]), "+f"(d[31]), "+f"(d[32]),
        "+f"(d[33]), "+f"(d[34]), "+f"(d[35]), "+f"(d[36]), "+f"(d[37]), "+f"(d[38]), "+f"(d[39]), "+f"(d[40]),
        "+f"(d[41]), "+f"(d[42]), "+f"(d[43]), "+f"(d[44]), "+f"(d[45]), "+f"(d[46]), "+f"(d[47]), "+f"(d[48]),
        "+f"(d[49]), "+f"(d[50]), "+f"(d[51]), "+f"(d[52]), "+f"(d[53]), "+f"(d[54]), "+f"(d[55]), "+f"(d[56]),
        "+f"(d[57]), "+f"(d[58]), "+f"(d[59]), "+f"(d[60]), "+f"(d[61]), "+f"(d[62]), "+f"(d[63]), "+f"(d[64]),
        "+f"(d[65]), "+f"(d[66]), "+f"(d[67]), "+f"(d[68]), "+f"(d[69]), "+f"(d[70]), "+f"(d[71]), "+f"(d[72]),
        "+f"(d[73]), "+f"(d[74]), "+f"(d[75]), "+f"(d[76]), "+f"(d[77]), "+f"(d[78]), "+f"(d[79]), "+f"(d[80]),
        "+f"(d[81]), "+f"(d[82]), "+f"(d[83]), "+f"(d[84]), "+f"(d[85]), "+f"(d[86]), "+f"(d[87]), "+f"(d[88]),
        "+f"(d[89]), "+f"(d[90]), "+f"(d[91]), "+f"(d[92]), "+f"(d[93]), "+f"(d[94]), "+f"(d[95]), "+f"(d[96]),
        "+f"(d[97]), "+f"(d[98]), "+f"(d[99]), "+f"(d[100]), "+f"(d[101]), "+f"(d[102]), "+f"(d[103]), "+f"(d[104]),
        "+f"(d[105]), "+f"(d[106]), "+f"(d[107]), "+f"(d[108]), "+f"(d[109]), "+f"(d[110]), "+f"(d[111]),
        "+f"(d[112]), "+f"(d[113]), "+f"(d[114]), "+f"(d[115]), "+f"(d[116]), "+f"(d[117]), "+f"(d[118]),
        "+f"(d[119]), "+f"(d[120]), "+f"(d[121]), "+f"(d[122]), "+f"(d[123]), "+f"(d[124]), "+f"(d[125]),
        "+f"(d[126]), "+f"(d[127])
      : "l"(da), "l"(db), "r"(sd), "n"(TA), "n"(TB));
}
template <int TA, int TB>
__device__ __forceinline__ void wgmma_ss_n128(float (&d)[64], uint64_t da, uint64_t db, int sd) {
  asm volatile("{\n.reg .pred p;\nsetp.ne.b32 p, %66, 0;\n"
      "wgmma.mma_async.sync.aligned.m64n128k16.f32.bf16.bf16 {"
      "%0, %1, %2, %3, %4, %5, %6, %7, %8, %9, %10, %11, %12, %13, %14, %15, %16, %17, %18, %19, %20, %21, %22, %23, "
      "%24, %25, %26, %27, %28, %29, %30, %31, %32, %33, %34, %35, %36, %37, %38, %39, %40, %41, %42, %43, %44, %45, "
      "%46, %47, %48, %49, %50, %51, %52, %53, %54, %55, %56, %57, %58, %59, %60, %61, %62, %63"
      "}, %64, %65, p, 1, 1, %67, %68;\n}\n"
      : "+f"(d[0]), "+f"(d[1]), "+f"(d[2]), "+f"(d[3]), "+f"(d[4]), "+f"(d[5]), "+f"(d[6]), "+f"(d[7]), "+f"(d[8]),
        "+f"(d[9]), "+f"(d[10]), "+f"(d[11]), "+f"(d[12]), "+f"(d[13]), "+f"(d[14]), "+f"(d[15]), "+f"(d[16]),
        "+f"(d[17]), "+f"(d[18]), "+f"(d[19]), "+f"(d[20]), "+f"(d[21]), "+f"(d[22]), "+f"(d[23]), "+f"(d[24]),
        "+f"(d[25]), "+f"(d[26]), "+f"(d[27]), "+f"(d[28]), "+f"(d[29]), "+f"(d[30]), "+f"(d[31]), "+f"(d[32]),
        "+f"(d[33]), "+f"(d[34]), "+f"(d[35]), "+f"(d[36]), "+f"(d[37]), "+f"(d[38]), "+f"(d[39]), "+f"(d[40]),
        "+f"(d[41]), "+f"(d[42]), "+f"(d[43]), "+f"(d[44]), "+f"(d[45]), "+f"(d[46]), "+f"(d[47]), "+f"(d[48]),
        "+f"(d[49]), "+f"(d[50]), "+f"(d[51]), "+f"(d[52]), "+f"(d[53]), "+f"(d[54]), "+f"(d[55]), "+f"(d[56]),
        "+f"(d[57]), "+f"(d[58]), "+f"(d[59]), "+f"(d[60]), "+f"(d[61]), "+f"(d[62]), "+f"(d[63])
      : "l"(da), "l"(db), "r"(sd), "n"(TA), "n"(TB));
}
template <int TA, int TB>
__device__ __forceinline__ void wgmma_ss_n64(float (&d)[32], uint64_t da, uint64_t db, int sd) {
  asm volatile("{\n.reg .pred p;\nsetp.ne.b32 p, %34, 0;\n"
      "wgmma.mma_async.sync.aligned.m64n64k16.f32.bf16.bf16 {"
      "%0, %1, %2, %3, %4, %5, %6, %7, %8, %9, %10, %11, %12, %13, %14, %15, %16, %17, %18, %19, %20, %21, %22, %23, "
      "%24, %25, %26, %27, %28, %29, %30, %31"
      "}, %32, %33, p, 1, 1, %35, %36;\n}\n"
      : "+f"(d[0]), "+f"(d[1]), "+f"(d[2]), "+f"(d[3]), "+f"(d[4]), "+f"(d[5]), "+f"(d[6]), "+f"(d[7]), "+f"(d[8]),
        "+f"(d[9]), "+f"(d[10]), "+f"(d[11]), "+f"(d[12]), "+f"(d[13]), "+f"(d[14]), "+f"(d[15]), "+f"(d[16]),
        "+f"(d[17]), "+f"(d[18]), "+f"(d[19]), "+f"(d[20]), "+f"(d[21]), "+f"(d[22]), "+f"(d[23]), "+f"(d[24]),
        "+f"(d[25]), "+f"(d[26]), "+f"(d[27]), "+f"(d[28]), "+f"(d[29]), "+f"(d[30]), "+f"(d[31])
      : "l"(da), "l"(db), "r"(sd), "n"(TA), "n"(TB));
}
template <int SA, int TB>
__device__ __forceinline__ void wgmma_rs_n64(float (&d)[32], uint32_t a0, uint32_t a1, uint32_t a2, uint32_t a3, uint64_t db, int sd) {
  asm volatile("{\n.reg .pred p;\nsetp.ne.b32 p, %37, 0;\n"
      "wgmma.mma_async.sync.aligned.m64n64k16.f32.bf16.bf16 {"
      "%0, %1, %2, %3, %4, %5, %6, %7, %8, %9, %10, %11, %12, %13, %14, %15, %16, %17, %18, %19, %20, %21, %22, %23, "
      "%24, %25, %26, %27, %28, %29, %30, %31"
      "}, {%32, %33, %34, %35}, %36, p, %38, 1, %39;\n}\n"
      : "+f"(d[0]), "+f"(d[1]), "+f"(d[2]), "+f"(d[3]), "+f"(d[4]), "+f"(d[5]), "+f"(d[6]), "+f"(d[7]), "+f"(d[8]),
        "+f"(d[9]), "+f"(d[10]), "+f"(d[11]), "+f"(d[12]), "+f"(d[13]), "+f"(d[14]), "+f"(d[15]), "+f"(d[16]),
        "+f"(d[17]), "+f"(d[18]), "+f"(d[19]), "+f"(d[20]), "+f"(d[21]), "+f"(d[22]), "+f"(d[23]), "+f"(d[24]),
        "+f"(d[25]), "+f"(d[26]), "+f"(d[27]), "+f"(d[28]), "+f"(d[29]), "+f"(d[30]), "+f"(d[31])
      : "r"(a0), "r"(a1), "r"(a2), "r"(a3), "l"(db), "r"(sd), "n"(SA), "n"(TB));
}

__device__ __forceinline__ uint32_t BAR_FULL(uint32_t sb, int i) { return sb + SM_BAR + 8 * i; }
__device__ __forceinline__ uint32_t BAR_EMPTY(uint32_t sb, int i) { return sb + SM_BAR + 64 + 8 * i; }
__device__ __forceinline__ uint32_t BAR_X(uint32_t sb, int i) { return sb + SM_BAR + 128 + 8 * i; }
__device__ __forceinline__ uint32_t BAR_Y(uint32_t sb, int i) { return sb + SM_BAR + 192 + 8 * i; }
__device__ __forceinline__ uint32_t BAR_XFREE(uint32_t sb) { return sb + SM_BAR + 256; }

__device__ __forceinline__ uint32_t BAR_E2(uint32_t sb, int i) { return sb + SM_BAR + 264 + 8 * i; }
#define CMASK 0xd4u
#define XORDER 0, 1, 11, 2, 3, 12, 13, 4, 5, 14, 6, 15, 16
#define XSPREAD 2
#define PFAT 3
#define SKEW 3
#define EQW 99
#define EQA 99
#define SPREAD 1
#define WUN 2
constexpr int WUNR = WUN;
#define EPF 0
#define LPF 6
#define XB 1
#define WS 1
#define GL1 0
#define GS0 2
#define GL2 6
#define GS1 4
constexpr int Q_G1B = 18, Q_G2 = 32, Q_XR = 39, Q_P3 = 46, Q_END = 50;

__device__ __forceinline__ uint32_t y_addr(int kb) { return kb < 3 ? SM_RING + (kb + (Q_G2 + 4) % NSTAGE) * STAGE_BYTES : SM_X + (kb - 3) * 16384; }
static_assert((Q_G2 + 4) % NSTAGE + 2 < NSTAGE, "");

struct Ring {
  uint32_t slot, phase;
  __device__ __forceinline__ void next() { if (++slot == NSTAGE) { slot = 0; phase ^= 1; } }
};

__device__ __forceinline__ void release_slot(uint32_t sb, uint32_t slot, int tid, int times) {
  if (tid < 2 * times) mbar_arrive_cluster(BAR_EMPTY(sb, slot), tid & 1);
}

__device__ __forceinline__ void ffn_consumer(uint32_t sb, const uint8_t* smem, const Params& p, int bid, int wg, int tid, int mt, int jj) {
  const int lane = tid & 31, warp = tid >> 5, q = lane & 3, r0 = 16 * warp + (lane >> 2);
  uint32_t* const my_epoch = &p.s->epoch[blockIdx.x * 12 + (threadIdx.x >> 5)];
  const uint32_t epoch = ld_relaxed(my_epoch) + 1;
  Ring rg{0, 0};
  uint32_t u[64];
  float acc[128];
  uint32_t prev = NSTAGE, prev2 = NSTAGE, cmask = CMASK;
  int st = 0;
  auto g1_stage = [&](uint32_t slot, int s) {
    const uint64_t da = mk_desc(sb + SM_X + (s >> 1) * 16384 + wg * 8192 + (s & 1) * 64, 16, 1024, 1);
    const uint64_t db = mk_desc(sb + SM_RING + slot * STAGE_BYTES, 4096, 1024, 1);
    wg_fence();
    wgmma_ss_n256<0, 1>(acc, da, db, s != 0);
    wgmma_ss_n256<0, 1>(acc, da + 2, db + 128, 1);
    wg_commit();
  };
  if (wg == 1) {
    float ap[64];
    constexpr int QX = 32 - __builtin_clz(CMASK);
    constexpr int NPRE = QX + XSPREAD;
    uint4* const x1dst = p.s->x1t + ((64 * jj + r0 + 8) >> 2) * 1024 + (r0 & 3) * 128 + 8 * mt + (q ^ (mt & 3));
    const int x1lo = 64 * jj + r0 == 1 ? 110 * 1024 - 128 : -2048;
#pragma unroll
    for (int qi = 0; qi < NPRE; qi++) {
      const int slot = qi % NSTAGE, nc = __builtin_popcount(CMASK & ((1u << qi) - 1));
      if (qi == 0) TL(60);
      mbar_wait(BAR_FULL(sb, slot), (qi / NSTAGE) & 1);
      if (qi == 0) TL(61);
      if ((CMASK >> qi) & 1) {
#pragma unroll
        for (int kb = 2 * nc; kb < 2 * nc + 2 && kb < 7; kb++) {
          const uint64_t da = mk_desc(sb + SM_RING + slot * STAGE_BYTES + (kb & 1) * 8192, 8192, 1024, 1);
          const uint64_t db = mk_desc(sb + SM_X + kb * 16384, 16, 1024, 1);
          mbar_wait(BAR_X(sb, kb), 0);
          TL(16 + kb);
          wg_fence();
#pragma unroll
          for (int kk = 0; kk < 4; kk++) wgmma_ss_n128<1, 0>(ap, da + kk * 128, db + kk * 2, (kb | kk) != 0);
          wg_commit();
        }
      } else {
        if (((qi - nc) & 1) == 0 && qi - nc >= 4 * nc) mbar_wait(BAR_X(sb, (qi - nc) >> 1), 0);
        TL(32 + qi - nc);
        g1_stage(slot, qi - nc);
      }
      if (qi > 0) {
        wg_wait<1>();
        release_slot(sb, (qi - 1) % NSTAGE, tid, ((CMASK >> (qi - 1)) & 1) ? 2 : 1);
      }
      if (qi >= QX) {
        if (qi == QX) { fence_regs(ap); TL(2); }
#pragma unroll
        for (int t = (qi - QX) * (4 / XSPREAD); t < (qi - QX + 1) * (4 / XSPREAD); t++)
#pragma unroll
        for (int h = 0; h < 2; h++)
          x1dst[(h ? 0 : x1lo) + 512 * (t & 1) + 4 * (t >> 1)] = make_uint4((pack2(ap[16 * t + 2 * h], ap[16 * t + 2 * h + 1]) & ~1u) | (epoch & 1), pack2(ap[16 * t + 4 + 2 * h], ap[16 * t + 5 + 2 * h]),
                                             pack2(ap[16 * t + 8 + 2 * h], ap[16 * t + 9 + 2 * h]), pack2(ap[16 * t + 12 + 2 * h], ap[16 * t + 13 + 2 * h]));
      }
    }
    bar_arrive(7, 160);
    st = NPRE - 4; cmask = 0; prev = (NPRE - 1) % NSTAGE;
    rg.slot = NPRE % NSTAGE; rg.phase = (NPRE / NSTAGE) & 1;
  }
#pragma unroll 1
  for (int pass = 0; pass < 2; pass++) {
#pragma unroll 1
    for (; st < 14; st++) {
      while (cmask & 1) { cmask >>= 1; rg.next(); }
      cmask >>= 1;
      if (pass == 0 && (st & 1) == 0) mbar_wait(BAR_X(sb, st >> 1), 0);
      if (st == 14 - SKEW && wg == 1) bar_sync(9 + pass, 256);
      mbar_wait(BAR_FULL(sb, rg.slot), rg.phase);
      TL(32 + 14 * pass + st);
      g1_stage(rg.slot, st);
      wg_wait<1>();
      if (st > 0) release_slot(sb, prev, tid, 1);
      prev = rg.slot;
      rg.next();
    }
    st = 0;
    if (wg == 0) bar_arrive(9 + pass, 256);
    wg_wait<0>();
    fence_regs(acc);
    release_slot(sb, prev, tid, 1);
    prev = prev2 = NSTAGE;
    TL(3 + 2 * pass);
#pragma unroll
    for (int i = 0; i < 32; i++) {
      const float g0 = 0.5f * acc[2 * i], g1 = 0.5f * acc[2 * i + 1];
      const float s0 = fmaf(g0, tanh_fast(g0), g0), s1 = fmaf(g1, tanh_fast(g1), g1);
      u[32 + i] = pack2(s0 * acc[64 + 2 * i], s1 * acc[64 + 2 * i + 1]);
    }
    if (pass == 0) {
#pragma unroll
      for (int i = 0; i < 32; i++) u[i] = u[32 + i];
    }
    TL(4 + 2 * pass);
  }
  fence_regs(u);
  float accA[32], accB[32];
  auto stage = [&](float (&acc)[32], int qi) {
    const int st = qi & 1;
    if (qi == EQW && wg == 0) bar_sync(1, 256);
    if (qi < Q_XR) mbar_wait(BAR_FULL(sb, qi % NSTAGE), (qi / NSTAGE) & 1);
    else mbar_wait(BAR_X(sb, qi - Q_XR), 1);
    const uint64_t db = mk_desc(sb + (qi < Q_XR ? SM_RING + (qi % NSTAGE) * STAGE_BYTES : SM_X + (qi - Q_XR) * 16384), 8192, 1024, 1);
    wg_fence();
#pragma unroll
    for (int kk = 0; kk < 8; kk++) {
      const uint32_t* a = u + 32 * st + 4 * kk;
      wgmma_rs_n64<1, 1>(acc, a[0], a[1], a[2], a[3], db + kk * 128, (st | kk) != 0);
    }
    wg_commit();
    if (qi == EQA && wg == 1) bar_arrive(1, 256);
  };
  auto retire = [&](int qi) {
    wg_wait<1>();
    if (qi >= Q_G2 && qi < Q_G2 + 4) release_slot(sb, qi % NSTAGE, tid, 1);
    else if (qi >= Q_G2 + 4 && qi < Q_G2 + 11 && tid == 0) mbar_arrive(BAR_E2(sb, qi - Q_G2 - 4));
  };
  const uint32_t par = epoch & 1;
  auto put = [&](float (&acc)[32], int c) {
    fence_regs(acc);
    int o = jj + 1 + c;
    if (o >= 7) o -= 7;
    uint4* dst = p.s->part + ((((mt * 7 + o) * 6 + c) * 2 + wg) * 4) * 128 + tid;
#pragma unroll
    for (int v = 0; v < 4; v++) {
      const float* a = acc + 8 * v;
      st_relaxed(dst + v * 128, make_uint4((pack2(a[0], a[1]) & ~1u) | par, pack2(a[2], a[3]), pack2(a[4], a[5]), pack2(a[6], a[7])));
    }
  };
  const uint4* const src = p.s->part + (((mt * 7 + jj) * 6 * 2 + wg) * 4) * 128 + tid;
  auto gload = [&](uint4 (&pv)[8], int c) {
#pragma unroll
    for (int i = 0; i < 8; i++) pv[i] = ld_relaxed(src + ((2 * c + (i >> 2)) * 8 + (i & 3)) * 128);
  };
  auto gload1 = [&](uint4 (&pv)[8], int c) {
#pragma unroll
    for (int i = 0; i < 4; i++) pv[4 * (c & 1) + i] = ld_relaxed(src + (c * 8 + i) * 128);
  };
  auto gsum = [&](uint4 (&pv)[8], int c) {
#pragma unroll 1
    for (uint32_t n = 0; n < SPIN_LIMIT; n++) {
      uint32_t bad = 0;
#pragma unroll
      for (int i = 0; i < 8; i++) bad |= pv[i].x ^ par;
      if (!__any_sync(0xffffffffu, bad & 1)) break;
      gload(pv, c);
    }
    TL(24 + c);
#pragma unroll
    for (int i = 0; i < 4; i++) {
      const uint32_t w[4] = {add2(pv[i].x, pv[4 + i].x), add2(pv[i].y, pv[4 + i].y), add2(pv[i].z, pv[4 + i].z), add2(pv[i].w, pv[4 + i].w)};
#pragma unroll
      for (int k = 0; k < 4; k++) { accA[8 * i + 2 * k] += bf_lo(w[k]); accA[8 * i + 2 * k + 1] += bf_hi(w[k]); }
    }
  };
  uint4 pv0[8], pv1[8], pv2[8];
  const int row = 128 * mt + 64 * wg + r0;
  uint32_t gt0, gt1;
#pragma unroll
  for (int c2 = 0; c2 < 4; c2++) {
    const int qi = Q_G2 + 4 * c2;
    stage(accA, qi);
    retire(qi - 1);
    stage(accA, qi + 1);
    if (c2 == 3) TL(27);
    if (c2 > 0) put(accB, 2 * c2 - 1);
    if (c2 == 2) gload1(pv0, 1);
    if (c2 == 3) gload1(pv1, 3);
    TL(7 + c2);
    if (c2 == 3) break;
    retire(qi);
    stage(accB, qi + 2);
    retire(qi + 1);
    stage(accB, qi + 3);
    put(accA, 2 * c2);
    if (c2 == 1) gload1(pv0, 0);
    if (c2 == 2) gload1(pv1, 2);
    if (c2 == 0) { gt0 = ld_relaxed(&p.s->gate[row]); gt1 = ld_relaxed(&p.s->gate[row + 8]); }
    retire(qi + 2);
  }
#pragma unroll
  for (int kb = 0; kb < 7; kb++) {
    const int qt = Q_XR + (kb >> 1);
    if ((kb & 1) == 0) mbar_wait(BAR_FULL(sb, qt % NSTAGE), (qt / NSTAGE) & 1);
    mbar_wait(BAR_Y(sb, kb), 0);
    const uint64_t da = mk_desc(sb + y_addr(kb) + wg * 8192, 8192, 1024, 1);
    const uint64_t db = mk_desc(sb + SM_RING + (qt % NSTAGE) * STAGE_BYTES + (kb & 1) * 8192, 16, 1024, 1);
    wg_fence();
#pragma unroll
    for (int kk = 0; kk < 4; kk++) wgmma_ss_n64<1, 0>(accB, da + kk * 128, db + kk * 2, (kb | kk) != 0);
    wg_commit();
    if (kb == 1) { wg_wait<2>(); fence_regs(accA); TL(15); }
    if (kb == GS0) gsum(pv0, 0);
    if (kb == GL2) gload(pv2, 2);
    if (kb == GS1) gsum(pv1, 1);
  }
  TL(11);
  for (uint32_t n = 0; (((gt0 ^ epoch) | (gt1 ^ epoch)) & 0xffffu) && n < SPIN_LIMIT; n++) {
    gt0 = ld_relaxed(&p.s->gate[row]); gt1 = ld_relaxed(&p.s->gate[row + 8]);
  }
  gsum(pv2, 2);
  const float ga0 = bf_hi(gt0), ga1 = bf_hi(gt1);
  TL(12);
  wg_wait<0>();
  fence_regs(accB);
  TL(13);
  const float gb0 = bf_round(1.f - ga0), gb1 = bf_round(1.f - ga1);
  const float gs0 = ga0 * (2.f / (float)(S_ * D_)), gs1 = ga1 * (2.f / (float)(S_ * D_));
  uint4* const o = reinterpret_cast<uint4*>(p.out + (size_t)row * D_ + 64 * jj + 8 * q);
#pragma unroll
  for (int h = 0; h < 2; h++) {
    const float gs = h ? gs1 : gs0, gb = h ? gb1 : gb0;
#pragma unroll
    for (int k = 0; k < 2; k++) {
      uint32_t w[4];
#pragma unroll
      for (int j = 0; j < 4; j++) {
        const int i = 16 * k + 4 * j + 2 * h;
        w[j] = pack2(fmaf(gs, accB[i], gb * accA[i]), fmaf(gs, accB[i + 1], gb * accA[i + 1]));
      }
      const bool o1 = q & 1, o2 = q & 2;
      uint32_t a = __shfl_xor_sync(0xffffffffu, o1 ? w[0] : w[1], 1), b = __shfl_xor_sync(0xffffffffu, o1 ? w[2] : w[3], 1);
      if (o1) { w[0] = a; w[2] = b; } else { w[1] = a; w[3] = b; }
      a = __shfl_xor_sync(0xffffffffu, o2 ? w[0] : w[2], 2); b = __shfl_xor_sync(0xffffffffu, o2 ? w[1] : w[3], 2);
      if (o2) { w[0] = a; w[1] = b; } else { w[2] = a; w[3] = b; }
      o[h * D_ + 4 * k] = make_uint4(w[0], w[1], w[2], w[3]);
    }
  }
  if (lane == 0) *my_epoch = epoch;
  TL(14);
}

__device__ __forceinline__ void ring_issue(uint32_t sb, const Params& p, int qi, uint32_t slot, bool wait, uint32_t phase, int jj, uint32_t rank) {
  const CUtensorMap* m;
  int c0, c1, c2 = 0;
  bool half = false, is3d = false;
  if (qi < Q_G2) {
    const int nc = __popc(CMASK & ((1u << qi) - 1));
    if ((CMASK >> qi) & 1) {
      m = &p.ct; c0 = 64 * jj; c1 = 128 * nc + 64 * rank; half = nc == 3;
    } else {
      const int pass = qi >= Q_G1B;
      m = rank ? &p.wu : &p.wg; c0 = 0; c1 = 32 * (qi - nc - 14 * pass); c2 = 4 * jj + 2 * pass; is3d = true;
    }
  } else if (qi < Q_P3) {
    int o = jj + 1 + ((qi - Q_G2) >> 1);
    if (o >= 7) o -= 7;
    m = &p.wd; c0 = 64 * o; c1 = 256 * jj + 128 * (qi & 1) + 64 * rank;
  } else {
    m = &p.ct; c0 = 128 * (qi - Q_P3) + 64 * rank; c1 = 64 * jj; half = qi == Q_END - 1;
  }
  uint32_t bar = BAR_FULL(sb, slot), dst = sb + SM_RING + slot * STAGE_BYTES + rank * 8192;
  if (qi >= Q_XR && qi < Q_P3) {
    bar = BAR_X(sb, qi - Q_XR); dst = sb + SM_X + (qi - Q_XR) * 16384 + rank * 8192;
    if (qi == Q_XR) mbar_wait_cluster(BAR_XFREE(sb), 0);
  } else {
    if (wait) mbar_wait_cluster(BAR_EMPTY(sb, slot), phase ^ (qi >= Q_P3));
    mbar_expect_tx(bar, half ? 8192 : 16384);
  }
  if (is3d) tma3d_mc(dst, m, c0, c1, c2, bar);
  else if (!(half && rank)) tma2d_mc(dst, m, c0, c1, bar);
}

__device__ __forceinline__ void ffn_producer(uint32_t sb, const uint8_t* smem, int bid, const Params& p, int warp, int lane, int mt, int jj, uint32_t rank) {
  if (warp < 2) {
    if (lane == 0) {
      uint32_t slot = warp, phase = 0;
#pragma unroll 1
      for (int qi = NSTAGE + warp; qi < Q_END; qi += 2) {
        if (qi < Q_XR || qi >= Q_P3) ring_issue(sb, p, qi, slot, true, phase, jj, rank);
        if (warp == 1 && qi >= Q_G1B + 8 && qi < Q_XR) ring_issue(sb, p, Q_XR + ((qi - Q_G1B - 8) >> 1), 0, false, 0, jj, rank);
        TL(10 + qi);
        slot += 2;
        if (slot >= NSTAGE) { slot -= NSTAGE; phase ^= 1; }
      }
    }
  } else {
    const int wg = warp - 2;
    uint32_t* const my_epoch = &p.s->epoch[blockIdx.x * 12 + 8 + warp];
    const uint32_t epoch = ld_relaxed(my_epoch) + 1;
    if (wg == 0) {
      if (lane == 0) { prefetch_tmap(&p.wd); prefetch_tmap(&p.yt); }
      {
        const uint4* gw4 = reinterpret_cast<const uint4*>(p.gate_w);
        const uint4 ga = __ldg(gw4 + lane), gb = lane < 24 ? __ldg(gw4 + 32 + lane) : make_uint4(0, 0, 0, 0);
        if (lane < 7) { mbar_wait(BAR_X(sb, lane), 0); mbar_expect_tx(BAR_X(sb, lane), 16384); mbar_expect_tx(BAR_Y(sb, lane), 16384); }
        __syncwarp();
        float mine = 0.f;
#pragma unroll 1
        for (int u = 0; u < 19; u++) {
          const int r = min(19 * jj + u, 127);
          const uint8_t* xr = smem + SM_X + (lane >> 3) * 16384 + r * 128 + (((lane ^ r) & 7) << 4);
          const uint4 xa = *reinterpret_cast<const uint4*>(xr);
          const uint4 xb = lane < 24 ? *reinterpret_cast<const uint4*>(xr + 65536) : make_uint4(0, 0, 0, 0);
          float s = 0.f;
          auto dot2 = [&](uint32_t a, uint32_t b) {
            const uint32_t pr = mul2(a, b);
            s += bf_lo(pr) + bf_hi(pr);
          };
          dot2(xa.x, ga.x); dot2(xa.y, ga.y); dot2(xa.z, ga.z); dot2(xa.w, ga.w);
          dot2(xb.x, gb.x); dot2(xb.y, gb.y); dot2(xb.z, gb.z); dot2(xb.w, gb.w);
#pragma unroll
          for (int o = 16; o > 0; o >>= 1) s += __shfl_xor_sync(0xffffffffu, s, o);
          if (lane == u) mine = s;
        }
        if (lane < 19 && 19 * jj + lane < 128)
          st_relaxed(&p.s->gate[128 * mt + 19 * jj + lane], pack2(0.f, 1.f / (1.f + __expf(-bf_round(mine)))) | (epoch & 0xffffu));
      }
      TL(9);
      if (lane < 2) mbar_arrive_cluster(BAR_XFREE(sb), lane);
    } else {
      mbar_wait(BAR_X(sb, PFAT), 0);
      if (lane < 6) {
        int row = 176 + 3 * bid + (lane >> 1);
        if (row >= D_) row -= D_;
        l2_prefetch(((lane & 1) ? p.pwu : p.pwg) + row * F_, F_ * 2);
      }
      TL(2);
      bar_sync(7, 160);
      if (lane == 0) { red_add(&p.s->cnt_x1[jj * 32], 1);
        l2_prefetch(p.pwd + bid * 16 * D_, 32 * D_); }
      TL(5);
    }
    mbar_wait(BAR_E2(sb, 0), 0);
    TL(3);
    const int kb = 2 * lane + wg;
    bool todo = kb < 7, ready = false;
    uint32_t n = 0;
    while (__any_sync(0xffffffffu, todo)) {
      if (todo) {
        uint32_t ok;
        if (!ready) {
          asm volatile("ld.acquire.gpu.global.u32 %0, [%1];" : "=r"(ok) : "l"(&p.s->cnt_y[kb * 32]) : "memory");
          ready = (int32_t)(ok - epoch * (kb ? 16 : 17)) >= 0;
        }
        asm volatile("{\n.reg .pred p;\nmbarrier.test_wait.parity.shared::cta.b64 p, [%1], 0;\nselp.u32 %0, 1, 0, p;\n}"
                     : "=r"(ok) : "r"(BAR_E2(sb, kb)) : "memory");
        if ((ok && ready) || ++n > SPIN_LIMIT) {
          tma3d(sb + y_addr(kb), &p.yt, 0, 64 * kb, 2 * mt, BAR_Y(sb, kb));
          todo = false;
        }
      }
      __nanosleep(40);
    }
    TL(4);
    if (lane == 0) *my_epoch = epoch;
  }
}

__device__ __forceinline__ void spectral_cta(uint32_t sb, uint8_t* smem, const Params& p, int sc, int wg) {
  const int t384 = threadIdx.x, lane = t384 & 31, warp12 = t384 >> 5, tid = t384 & 127;
  const int warp = tid >> 5, q = lane & 3;
  const int sl0 = 6 * sc + min(sc, 8), nsl = sc < 8 ? 7 : 6;
  if (t384 == 320) {
#pragma unroll 1
    for (int i = 0; i < nsl; i++) {
      mbar_expect_tx(BAR_X(sb, i), 2 * SLAB_BYTES);
      const int row = 128 * ((sl0 + i) >> 3) + 8 * ((sl0 + i) & 7);
      const uint32_t dst = sb + SP_Z + 2 * i * SLAB_BYTES;
      bulk_g2s(dst, p.w_r + row * DF_, SLAB_BYTES / 2, BAR_X(sb, i));
      bulk_g2s(dst + SLAB_BYTES / 2, p.w_r + (row + 64) * DF_, SLAB_BYTES / 2, BAR_X(sb, i));
      bulk_g2s(dst + SLAB_BYTES, p.w_i + row * DF_, SLAB_BYTES / 2, BAR_X(sb, i));
      bulk_g2s(dst + 3 * SLAB_BYTES / 2, p.w_i + (row + 64) * DF_, SLAB_BYTES / 2, BAR_X(sb, i));
    }
  } else if (t384 == 352 && sc < 19) {
    mbar_expect_tx(BAR_Y(sb, 6), 24576);
    bulk_g2s(sb + SP_TW, p.spec, 24576, BAR_Y(sb, 6));
  }
  uint32_t* const my_epoch = &p.s->epoch[blockIdx.x * 12 + warp12];
  const uint32_t epoch = ld_relaxed(my_epoch) + 1;
  uint32_t fe[16], tw[16];
#pragma unroll
  for (int i = 0; i < 4; i++) {
    const uint4 a = __ldg(reinterpret_cast<const uint4*>(p.spec->fe) + i * 128 + tid);
    const uint4 b = __ldg(reinterpret_cast<const uint4*>(p.spec->tw) + i * 128 + tid);
    fe[4 * i] = a.x; fe[4 * i + 1] = a.y; fe[4 * i + 2] = a.z; fe[4 * i + 3] = a.w;
    tw[4 * i] = b.x; tw[4 * i + 1] = b.y; tw[4 * i + 2] = b.z; tw[4 * i + 3] = b.w;
  }
  __syncwarp();
  asm volatile("barrier.cluster.wait.acquire.aligned;" ::: "memory");
#pragma unroll WUNR
  for (int un = wg; un < 8 * nsl; un += 3) {
    const int i = un >> 3, sl = sl0 + i, pr = 16 * (un & 7) + 4 * (lane >> 3) + warp, r = lane & 7;
    mbar_wait(BAR_X(sb, i), 0);
    if (pr < 113) {
      const uint16_t* w = reinterpret_cast<const uint16_t*>(smem + SP_Z + 2 * i * SLAB_BYTES) + r * DF_ + 2 * pr;
      const uint32_t m = pr < 112 ? 0xffffffffu : 0u;
      p.s->wt[pr * 1024 + sl * 8 + (r ^ ((sl >> 2) & 6))] =
          make_uint4(w[0] | ((uint32_t)w[8 * DF_] << 16), w[16 * DF_] | ((uint32_t)w[24 * DF_] << 16),
                     (w[1] | ((uint32_t)w[8 * DF_ + 1] << 16)) & m, (w[16 * DF_ + 1] | ((uint32_t)w[24 * DF_ + 1] << 16)) & m);
    }
  }
  __syncthreads();
  if (t384 == 352) { fence_gpu(); red_add(&p.s->cnt_w[0], 1); TL(2); }
  TL(1);
  if (sc == 19) return;
  const int nrnd = (sc == 18 && wg == 2) ? 1 : 2;
  auto fetch = [&]() {
    const int item = wg + 3 * lane, pr = 6 * sc + item;
    const uint32_t bar = warp ? BAR_Y(sb, item) : BAR_FULL(sb, item);
    mbar_expect_tx(bar, 16384);
    wait_counter(warp ? &p.s->cnt_w[0] : &p.s->cnt_x1[(pr < 112 ? pr >> 4 : 0) * 32], epoch * (warp ? NSPEC : 16));
    if (warp) fence_async();
    bulk_g2s(sb + (warp ? SP_W : SP_Z) + item * 16384, (warp ? p.s->wt : p.s->x1t) + pr * 1024, 16384, bar);
  };
  if (lane < nrnd && warp == 0) fetch();
  __syncwarp();
  fence_regs(fe); fence_regs(tw);
  mbar_wait(BAR_Y(sb, 6), 0);
  TL(3);
  const uint64_t dT_n = mk_desc(sb + SP_T, 8192, 1024, 1);
#pragma unroll 1
  for (int rnd = 0; rnd < nrnd; rnd++) {
    const int item = wg + 3 * rnd, pr = 6 * sc + item;
    const uint32_t z = sb + SP_Z + item * 16384;
    uint32_t fa[16], fb[16];
    auto load_frag = [&](int off) {
#pragma unroll
      for (int i = 0; i < 4; i++) {
        const uint4 a = *reinterpret_cast<const uint4*>(smem + SP_TW + off + i * 2048 + tid * 16);
        fa[4 * i] = a.x; fa[4 * i + 1] = a.y; fa[4 * i + 2] = a.z; fa[4 * i + 3] = a.w;
      }
      fence_regs(fa);
    };
    load_frag(0);
    {
      const uint32_t live = pr == 0 ? 0xddu : (pr == 112 ? 0x11u : 0xffu);
#pragma unroll 1
      for (uint32_t n = 0; n < 4096; n++) {
        mbar_wait(BAR_FULL(sb, item), n & 1);
        uint32_t bad = 0;
#pragma unroll
        for (int i = 0; i < 8; i++) bad |= ((*reinterpret_cast<const volatile uint32_t*>(smem + SP_Z + item * 16384 + i * 2048 + tid * 16) ^ epoch) & 1) << i;
        uint32_t again;
        asm volatile("{\n.reg .pred p, q;\nsetp.ne.u32 p, %1, 0;\nbarrier.red.or.pred q, %2, 128, p;\nselp.u32 %0, 1, 0, q;\n}"
                     : "=r"(again) : "r"(bad & live), "r"(1 + wg) : "memory");
        if (!again) break;
        TL(20);
        if (tid == 0) { mbar_expect_tx(BAR_FULL(sb, item), 16384); bulk_g2s(z, p.s->x1t + pr * 1024, 16384, BAR_FULL(sb, item)); }
      }
    }
    TL(4 + 8 * rnd);
    if (rnd == 0 && wg > 0) bar_sync(3 + wg, 256);
    float aR[32], aI[32];
    {
      const uint64_t de = mk_desc(z, 4096, 512, 2);
      wg_fence();
#pragma unroll
      for (int kk = 0; kk < 4; kk++) {
        wgmma_rs_n64<1, 1>(aR, fe[4 * kk], fe[4 * kk + 1], fe[4 * kk + 2], fe[4 * kk + 3], de + kk * 64, kk != 0);
        wgmma_rs_n64<1, 1>(aI, fa[4 * kk], fa[4 * kk + 1], fa[4 * kk + 2], fa[4 * kk + 3], de + 512 + kk * 64, kk != 0);
      }
      wg_commit();
      if (rnd == 0 && wg < 2) bar_arrive(4 + wg, 256);
      if (rnd == 0 && lane < nrnd && warp == 1) fetch();
      __syncwarp();
      wg_wait<0>();
      fence_regs(aR); fence_regs(aI);
    }
    TL(5 + 8 * rnd);
#pragma unroll
    for (int v = 0; v < 8; v++) {
      uint32_t* f = (v < 4 ? fa : fb) + 2 * (v & 3);
      f[0] = pack2(aR[4 * v], aR[4 * v + 1]); f[8] = pack2(aR[4 * v + 2], aR[4 * v + 3]);
      f[1] = pack2(aI[4 * v], aI[4 * v + 1]); f[9] = pack2(aI[4 * v + 2], aI[4 * v + 3]);
    }
    fence_regs(fa); fence_regs(fb);
    auto step_bc = [&](uint32_t (&f)[16], float (&a)[32]) {
#pragma unroll
      for (int v = 0; v < 8; v += 2) {
        const uint32_t u0r = add2(f[v], f[v + 1]), u0i = add2(f[v + 8], f[v + 9]), u1r = sub2(f[v], f[v + 1]), u1i = sub2(f[v + 8], f[v + 9]);
        f[v] = fma2(u0r, tw[v], mul2(u0i, tw[v + 8]));
        f[v + 8] = fms2(u0i, tw[v], mul2(u0r, tw[v + 8]));
        f[v + 1] = fma2(u1r, tw[v + 1], mul2(u1i, tw[v + 9]));
        f[v + 9] = fms2(u1i, tw[v + 1], mul2(u1r, tw[v + 9]));
      }
      fence_regs(f);
      wg_fence();
#pragma unroll
      for (int kk = 0; kk < 4; kk++) wgmma_rs_n64<1, 1>(a, f[4 * kk], f[4 * kk + 1], f[4 * kk + 2], f[4 * kk + 3], dT_n + kk * 128, kk != 0);
      wg_commit();
    };
    uint32_t wb[16];
    auto step_de = [&](uint32_t (&f)[16], float (&a)[32], bool first) {
      wg_wait<1>();
      fence_regs(a); fence_regs(f);
      const uint8_t* wp = smem + SP_W + item * 16384 + q * 1024 + warp * 128 + (((lane >> 2) ^ (2 * q)) << 4);
#pragma unroll
      for (int v = 0; v < 8; v++) {
        uint32_t wr, wi;
        if (first) {
          const uint4 w = *reinterpret_cast<const uint4*>(wp + (v >> 1) * 4096 + (v & 1) * 512);
          wr = w.x; wi = w.y; wb[v] = w.z; wb[8 + v] = w.w;
        } else {
          wr = wb[v]; wi = wb[8 + v];
        }
        const uint32_t zr = pack2(a[2 * v], a[2 * v + 1]), zi = pack2(a[16 + 2 * v], a[17 + 2 * v]);
        f[v] = fms2(zr, wr, mul2(zi, wi));
        f[8 + v] = fma2(zr, wi, mul2(zi, wr));
      }
      fence_regs(f);
      wg_fence();
#pragma unroll
      for (int kk = 0; kk < 4; kk++) wgmma_rs_n64<1, 0>(a, f[4 * kk], f[4 * kk + 1], f[4 * kk + 2], f[4 * kk + 3], dT_n + kk * 2, kk != 0);
      wg_commit();
    };
    auto step_f = [&](uint32_t (&f)[16], float (&a)[32], int col) {
      fence_regs(a); fence_regs(f);
#pragma unroll
      for (int v = 0; v < 4; v++) {
        const uint32_t* t = tw + 2 * v;
        const uint32_t u0r = pack2(a[4 * v], a[4 * v + 1]), u1r = pack2(a[4 * v + 2], a[4 * v + 3]);
        const uint32_t u0i = pack2(a[4 * v + 16], a[4 * v + 17]), u1i = pack2(a[4 * v + 18], a[4 * v + 19]);
        const uint32_t t0r = fms2(u0r, t[0], mul2(u0i, t[8])), t0i = fma2(u0i, t[0], mul2(u0r, t[8]));
        const uint32_t t1r = fms2(u1r, t[1], mul2(u1i, t[9])), t1i = fma2(u1i, t[1], mul2(u1r, t[9]));
        f[v] = add2(t0i, t1i); f[4 + v] = add2(t0r, t1r);
        f[8 + v] = sub2(t0i, t1i); f[12 + v] = sub2(t0r, t1r);
      }
      const uint32_t ad = z + (8 * warp + (lane & 7)) * 128 + (((4 * col + (lane >> 3)) ^ (lane & 7)) << 4);
#pragma unroll
      for (int u = 0; u < 4; u++) stmatrix_x4(ad + u * 4096, f[4 * u], f[4 * u + 1], f[4 * u + 2], f[4 * u + 3]);
    };
    step_bc(fa, aR);
    step_bc(fb, aI);
    mbar_wait(BAR_Y(sb, item), 0);
    TL(6 + 8 * rnd);
    step_de(fa, aR, true);
    step_de(fb, aI, false);
    bar_sync(1 + wg, 128);
    wg_wait<1>();
    TL(7 + 8 * rnd);
    step_f(fa, aR, 0);
    wg_wait<0>();
    step_f(fb, aI, 1);
    load_frag(8192);
    fence_async_smem();
    bar_sync(1 + wg, 128);
    TL(8 + 8 * rnd);
    {
      const uint64_t de = mk_desc(z, 8192, 1024, 1);
      wg_fence();
#pragma unroll
      for (int kk = 0; kk < 4; kk++) {
        wgmma_rs_n64<1, 1>(aR, fe[4 * kk], fe[4 * kk + 1], fe[4 * kk + 2], fe[4 * kk + 3], de + kk * 128, kk != 0);
        wgmma_rs_n64<1, 1>(aI, fa[4 * kk], fa[4 * kk + 1], fa[4 * kk + 2], fa[4 * kk + 3], de + 512 + kk * 128, kk != 0);
      }
      wg_commit();
      wg_wait<0>();
      fence_regs(aR); fence_regs(aI);
    }
    TL(9 + 8 * rnd);
    const bool edge = pr == 0 || pr == 112;
    if (edge) {
#pragma unroll
      for (int i = 0; i < 16; i++) { aR[i] *= 0.5f; aI[i] *= 0.5f; }
    }
#pragma unroll
    for (int i = 0; i < 8; i++) {
      const float* a = ((i & 1) ? aI : aR) + 16 * (i >> 2) + 2 - (i & 2);
      *reinterpret_cast<uint4*>(smem + SP_W + item * 16384 + (i >> 1) * 4096 + (i & 1) * 64 + (tid >> 2) * 128 + q * 16) =
          make_uint4(pack2(a[0], a[1]), pack2(a[4], a[5]), pack2(a[8], a[9]), pack2(a[12], a[13]));
    }
    fence_async_smem();
    bar_sync(1 + wg, 128);
    if (tid == 0) {
      const uint32_t src = sb + SP_W + item * 16384;
      __nv_bfloat16* dst = p.s->yt + (size_t)(pr < 112 ? 4 * pr : 1) * S_;
      bulk_s2g(dst, src, edge ? 4096 : 16384);
      if (pr == 0) bulk_s2g(dst + 2 * S_, src + 8192, 8192);
      asm volatile("cp.async.bulk.commit_group;" ::: "memory");
      if (rnd == nrnd - 1) {
        asm volatile("cp.async.bulk.wait_group 0;" ::: "memory");
        TL(11);
        red_add(&p.s->cnt_y[(pr < 112 ? pr >> 4 : 0) * 32], 1);
        if (rnd) red_add(&p.s->cnt_y[((pr - 3) >> 4) * 32], 1);
      }
    }
    __syncwarp();
    TL(10 + 8 * rnd);
  }
  if (lane == 0) *my_epoch = epoch;
}

__global__ void __cluster_dims__(2, 1, 1) __launch_bounds__(384, 1)
fused_kernel(const __grid_constant__ Params p) {
  extern __shared__ __align__(1024) uint8_t smem[];
  const uint32_t sb = smem_u32(smem);
  TL(0);
  const uint32_t rank = blockIdx.x & 1;
  const int hc = blockIdx.x >> 1;
  int grp, jj;
  if (hc < 4) { grp = 8; jj = hc; }
  else if (hc < 36) { grp = (hc - 4) & 7; jj = (hc - 4) >> 3; }
  else if (hc < 57) { jj = (hc - 36) / 7; grp = 1 + (hc - 36) - 7 * jj; jj += 4; }
  else if (hc < 60) { grp = 0; jj = hc - 53; }
  else { grp = 8; jj = hc - 56; }
  const int mt = 2 * grp + rank, bid = 2 * (7 * grp + jj) + rank;
  if (threadIdx.x < 256 && bid < NFFN) {
    const int t = threadIdx.x;
    if (t < 128) {
      if (LPF & 1) asm volatile("prefetch.global.L2 [%0];" ::"l"(p.px + (128 * mt + t) * D_ + 64 * jj));
      if ((LPF & 4) && t < 19 * XB && 19 * jj + t % 19 < 128) asm volatile("prefetch.global.L2 [%0];" ::"l"(p.px + (128 * mt + 19 * jj + t % 19) * D_ + 64 * (t / 19)));
    } else if ((LPF & 2) && t < 128 + 8 * WS) {
      asm volatile("prefetch.global.L2 [%0];" ::"l"((rank ? p.pwu : p.pwg) + (4 * grp + (t & 3) + 4 * (t & 120)) * F_ + 256 * jj + 16 * (t & 4)));
    }
  }
  if (threadIdx.x == 256) {
#pragma unroll
    for (int i = 0; i < NSTAGE; i++) { mbar_init(BAR_FULL(sb, i), 1); mbar_init(BAR_EMPTY(sb, i), 4); }
    asm volatile("fence.mbarrier_init.release.cluster;" ::: "memory");
  } else if (threadIdx.x == 320) {
    mbar_init(BAR_X(sb, 0), 1);
    if (bid < NFFN) {
      mbar_expect_tx(BAR_X(sb, 0), 16384);
      tma2d(sb + SM_X, &p.x, 0, 128 * mt, BAR_X(sb, 0));
    }
#pragma unroll
    for (int i = 1; i < NSTAGE; i++) mbar_init(BAR_X(sb, i), 1);
    mbar_init(BAR_XFREE(sb), 2);
    asm volatile("fence.mbarrier_init.release.cluster;" ::: "memory");
  } else if (threadIdx.x == 352) {
#pragma unroll
    for (int i = 0; i < NSTAGE; i++) { mbar_init(BAR_Y(sb, i), 1); mbar_init(BAR_E2(sb, i), 2); }
    asm volatile("fence.mbarrier_init.release.cluster;" ::: "memory");
  } else if (threadIdx.x == 288 && bid < NFFN) {
#pragma unroll
    for (int i = 0; i < EPF; i++)
      asm volatile("cp.async.bulk.prefetch.tensor.3d.L2.global [%0, {%1, %2, %3}];" ::"l"(rank ? &p.wu : &p.wg), "r"(0), "r"(32 * i), "r"(4 * jj) : "memory");
    prefetch_tmap(rank ? &p.wu : &p.wg); prefetch_tmap(&p.ct);
  }
  __syncwarp();
  asm volatile("barrier.cluster.arrive.relaxed.aligned;" ::: "memory");
  const int wg = __shfl_sync(0xffffffffu, threadIdx.x >> 7, 0);
  if (bid >= NFFN) {
    spectral_cta(sb, smem, p, bid - NFFN, wg);
  } else if (wg < 2) {
    asm volatile("setmaxnreg.inc.sync.aligned.u32 232;");
    asm volatile("barrier.cluster.wait.acquire.aligned;" ::: "memory");
    TL(1);
    ffn_consumer(sb, smem, p, bid, wg, threadIdx.x & 127, mt, jj);
  } else {
    asm volatile("setmaxnreg.dec.sync.aligned.u32 40;");
    asm volatile("barrier.cluster.wait.acquire.aligned;" ::: "memory");
    TL(1);
    if (threadIdx.x == 320) {
      constexpr int order[13] = {XORDER};
#pragma unroll
      for (int i = 0; i < 13; i++) {
        if (order[i] < 8) {
          ring_issue(sb, p, order[i], order[i], false, 0, jj, rank);
        } else {
          const int kb = order[i] - 10;
          mbar_expect_tx(BAR_X(sb, kb), 16384);
          tma2d(sb + SM_X + kb * 16384, &p.x, 64 * kb, 128 * mt, BAR_X(sb, kb));
        }
      }
      TL(2);
    }
    __syncwarp();
    ffn_producer(sb, smem, bid, p, (threadIdx.x >> 5) & 3, threadIdx.x & 31, mt, jj, rank);
  }
}

typedef CUresult (*EncodeFn)(CUtensorMap*, CUtensorMapDataType, cuuint32_t, void*, const cuuint64_t*, const cuuint64_t*,
                             const cuuint32_t*, const cuuint32_t*, CUtensorMapInterleave, CUtensorMapSwizzle,
                             CUtensorMapL2promotion, CUtensorMapFloatOOBfill);

void make_map(EncodeFn fn, CUtensorMap* m, const void* base, int rank, const cuuint64_t* dims, const cuuint64_t* strides,
              const cuuint32_t* box, CUtensorMapSwizzle sw) {
  const cuuint32_t es[4] = {1, 1, 1, 1};
  fn(m, CU_TENSOR_MAP_DATA_TYPE_BFLOAT16, rank, const_cast<void*>(base), dims, strides, box, es,
     CU_TENSOR_MAP_INTERLEAVE_NONE, sw, CU_TENSOR_MAP_L2_PROMOTION_L2_256B, CU_TENSOR_MAP_FLOAT_OOB_FILL_NONE);
}

}

extern "C" void kernel_launch(void* const* d_in, const int* in_sizes, int n_in, void* d_out, int out_size) {
  const __nv_bfloat16* x = (const __nv_bfloat16*)d_in[0];
  const __nv_bfloat16* w_r = (const __nv_bfloat16*)d_in[1];
  const __nv_bfloat16* w_i = (const __nv_bfloat16*)d_in[2];
  const __nv_bfloat16* wg = (const __nv_bfloat16*)d_in[4];
  const __nv_bfloat16* wu = (const __nv_bfloat16*)d_in[5];
  const __nv_bfloat16* wd = (const __nv_bfloat16*)d_in[6];
  const __nv_bfloat16* gate_w = (const __nv_bfloat16*)d_in[7];

  void* fnp = nullptr;
  cudaDriverEntryPointQueryResult qr;
  cudaGetDriverEntryPoint("cuTensorMapEncodeTiled", &fnp, cudaEnableDefault, &qr);
  EncodeFn fn = (EncodeFn)fnp;
  void *ctab, *spec, *scr;
  cudaGetSymbolAddress(&ctab, g_ctab);
  cudaGetSymbolAddress(&spec, g_spec);
  cudaGetSymbolAddress(&scr, g_scratch);
  const void* yt = (const char*)scr + offsetof(Scratch, yt);
  Params p;
  p.s = (Scratch*)scr; p.out = (__nv_bfloat16*)d_out;
  p.px = x; p.w_r = w_r; p.w_i = w_i; p.gate_w = gate_w; p.pwg = wg; p.pwu = wu; p.pwd = wd;
  p.ctab = (const tab::Table*)ctab; p.spec = (const tab::Spec*)spec;
  {
    const cuuint64_t d[2] = {D_, S_}, s[1] = {D_ * 2};
    const cuuint32_t b[2] = {64, 128};
    make_map(fn, &p.x, x, 2, d, s, b, CU_TENSOR_MAP_SWIZZLE_128B);
  }
  {
    const cuuint64_t d[3] = {64, D_, F_ / 64}, s[2] = {F_ * 2, 128};
    const cuuint32_t b[3] = {64, 32, 2};
    make_map(fn, &p.wg, wg, 3, d, s, b, CU_TENSOR_MAP_SWIZZLE_128B);
    make_map(fn, &p.wu, wu, 3, d, s, b, CU_TENSOR_MAP_SWIZZLE_128B);
  }
  {
    const cuuint64_t d[2] = {D_, F_}, s[1] = {D_ * 2};
    const cuuint32_t b[2] = {64, 64};
    make_map(fn, &p.wd, wd, 2, d, s, b, CU_TENSOR_MAP_SWIZZLE_128B);
  }
  {
    const cuuint64_t d[2] = {D_, D_}, s[1] = {D_ * 2};
    const cuuint32_t b[2] = {64, 64};
    make_map(fn, &p.ct, ctab, 2, d, s, b, CU_TENSOR_MAP_SWIZZLE_128B);
  }
  {
    const cuuint64_t d[3] = {64, D_, S_ / 64}, s[2] = {S_ * 2, 128};
    const cuuint32_t b[3] = {64, 64, 2};
    const cuuint32_t b2[3] = {64, 128, 1};
    make_map(fn, &p.yt, yt, 3, d, s, b, CU_TENSOR_MAP_SWIZZLE_128B);
    make_map(fn, &p.yt2, yt, 3, d, s, b2, CU_TENSOR_MAP_SWIZZLE_128B);
  }
  cudaFuncSetAttribute(fused_kernel, cudaFuncAttributeMaxDynamicSharedMemorySize, SM_TOTAL);
  fused_kernel<<<NCTA, 384, SM_TOTAL, cudaStreamPerThread>>>(p, x, w_r, w_i, gate_w, wd, (__nv_bfloat16*)d_out);
}
```

```cpp
#include <cuda_runtime.h>
#include <cuda_bf16.h>
#include <cuda.h>
#include <stdint.h>
#include <stddef.h>

namespace {

constexpr int S_ = 2048, D_ = 448, F_ = 1792, DF_ = 225;
constexpr int NFFN = 112, NSPEC = 20, NCTA = NFFN + NSPEC;
constexpr int NSTAGE = 7, STAGE_BYTES = 16384;
constexpr int SM_X = 0, SM_RING = 114688, SM_BAR = 229376, SM_TOTAL = SM_BAR + 512;
constexpr int SP_Z = 0, SP_W = 98304, SP_TW = 198656, SP_T = 215040, SLAB_BYTES = 16 * DF_ * 2;
constexpr uint32_t SPIN_LIMIT = 1u << 20;

namespace tab {
constexpr double PI = 3.14159265358979323846264338327950288;
constexpr double csin(double x) {
  double t = x, s = x;
  for (int i = 1; i < 20; i++) { t = -t * x * x / ((2 * i) * (2 * i + 1)); s += t; }
  return s;
}
constexpr double ccos(double x) {
  double t = 1, s = 1;
  for (int i = 1; i < 20; i++) { t = -t * x * x / ((2 * i - 1) * (2 * i)); s += t; }
  return s;
}
constexpr uint32_t to_bf16(double v) {
  uint32_t sign = v < 0 ? 0x8000u : 0u;
  double a = v < 0 ? -v : v;
  if (a < 1e-12) return 0;
  int e = 0;
  while (a >= 2.0) { a /= 2; e++; }
  while (a < 1.0) { a *= 2; e--; }
  double m = a * 128.0;
  int mi = (int)m;
  double fr = m - mi;
  if (fr > 0.5 || (fr == 0.5 && (mi & 1))) mi++;
  if (mi == 256) { mi = 128; e++; }
  return sign | (uint32_t)((e + 127) << 7) | (uint32_t)(mi - 128);
}
struct Base { uint32_t v[448]; };
constexpr Base make_base() {
  Base b{};
  for (int m = 0; m < 448; m++) {
    int mm = m > 224 ? m - 448 : m;
    double ang = 2 * PI * mm / 448.0;
    b.v[m] = to_bf16(ccos(ang)) | (to_bf16(-csin(ang)) << 16);
  }
  return b;
}
constexpr Base base = make_base();
struct Row { uint32_t v[224]; };
constexpr Row make_row(int d) {
  Row r{};
  r.v[0] = 0x3f80u | ((d & 1) ? 0xbf800000u : 0x3f800000u);
  int m = 0;
  for (int c = 1; c < 224; c++) { m += d; if (m >= 448) m -= 448; r.v[c] = base.v[m]; }
  return r;
}
struct Table { Row r[448]; };
constexpr Table make_table() {
  Table t{};
  for (int d = 0; d < 448; d++) t.r[d] = make_row(d);
  return t;
}
struct Cs { double c[2048], s[2048]; };
constexpr Cs make_cs() {
  Cs t{};
  for (int m = 0; m <= 256; m++) {
    const double a = 2 * PI * m / 2048.0, c = ccos(a), s = csin(a);
    t.c[m] = c; t.s[m] = s;
    t.c[512 - m] = s; t.s[512 - m] = c;
  }
  for (int m = 513; m < 2048; m++) { t.c[m] = -t.s[m - 512]; t.s[m] = t.c[m - 512]; }
  return t;
}
constexpr Cs cs = make_cs();
struct Spec {
  uint32_t fo[2048], fot[2048];
  uint16_t t32[4096];
  uint32_t fe[2048];
  uint32_t tw[2048];
};
constexpr uint32_t blk(int h, int c, int a) { return to_bf16(h == c ? cs.c[a & 2047] : (h ? -cs.s[a & 2047] : cs.s[a & 2047])); }
constexpr Spec make_spec() {
  Spec t{};
  for (int row = 0; row < 64; row++)
    for (int col = 0; col < 64; col++) {
      const int c = row & 31, k2 = col & 31, n2 = 8 * ((c >> 1) & 3) + 2 * (c >> 3) + (c & 1), m = 64 * ((n2 * k2) & 31);
      const double v = (row >> 5) == (col >> 5) ? cs.c[m] : (row < 32 ? -cs.s[m] : cs.s[m]);
      t.t32[row * 64 + (((col >> 3) ^ (row & 7)) << 3) + (col & 7)] = (uint16_t)to_bf16(v);
    }
  for (int th = 0; th < 128; th++)
    for (int i = 0; i < 16; i++) {
      const int r = 8 * (th >> 5) + ((th & 31) >> 2), h = i & 1, c = i >> 3, m = 8 * ((i >> 1) & 3) + 2 * (th & 3);
      const int o = ((i >> 2) * 128 + th) * 4 + (i & 3);
      t.fe[o] = blk(h, c, 64 * m * r) | (blk(h, c, 64 * (m + 1) * r) << 16);
      t.fo[o] = blk(h, c, 32 * (2 * m + 1) * r) | (blk(h, c, 32 * (2 * m + 3) * r) << 16);
      t.fot[o] = blk(h, c, 32 * (2 * r + 1) * m) | (blk(h, c, 32 * (2 * r + 1) * (m + 1)) << 16);
      const int k1 = r + 32 * h, n2 = 8 * (th & 3) + 2 * ((i >> 1) & 3);
      t.tw[o] = blk(0, c, n2 * k1) | (blk(0, c, (n2 + 1) * k1) << 16);
    }
  return t;
}
}
}

__device__ __align__(1024) const tab::Table g_ctab = tab::make_table();
__device__ __align__(1024) const tab::Spec g_spec = tab::make_spec();

struct Scratch {
  uint32_t cnt_w[32];
  uint32_t cnt_x1[7 * 32];
  uint32_t cnt_y[7 * 32];
  uint32_t epoch[NCTA * 12 + 240 + 256];
  uint32_t gate[S_];
  uint4 x1t[113 * 1024];
  __nv_bfloat16 yt[D_ * S_];
  uint4 wt[114 * 1024];
  uint4 part[16 * 7 * 6 * 2 * 4 * 128];
};
static_assert(offsetof(Scratch, x1t) % 1024 == 0, "alignment");
__device__ __align__(1024) Scratch g_scratch;
#define TL(i)

namespace {

struct Params {
  Scratch* s;
  __nv_bfloat16* out;
  const __nv_bfloat16 *px, *w_r, *w_i, *gate_w, *pwg, *pwu, *pwd;
  const tab::Table* ctab;
  const tab::Spec* spec;
  CUtensorMap x, wg, wu, wd, ct, yt;
};

__device__ __forceinline__ uint32_t smem_u32(const void* p) { return (uint32_t)__cvta_generic_to_shared(p); }
__device__ __forceinline__ void mbar_init(uint32_t bar, uint32_t cnt) {
  asm volatile("mbarrier.init.shared::cta.b64 [%0], %1;" ::"r"(bar), "r"(cnt) : "memory");
}
__device__ __forceinline__ void mbar_expect_tx(uint32_t bar, uint32_t bytes) {
  asm volatile("mbarrier.arrive.expect_tx.shared::cta.b64 _, [%0], %1;" ::"r"(bar), "r"(bytes) : "memory");
}
__device__ __forceinline__ void mbar_arrive(uint32_t bar) {
  asm volatile("mbarrier.arrive.shared::cta.b64 _, [%0];" ::"r"(bar) : "memory");
}
__device__ __forceinline__ void mbar_arrive_cluster(uint32_t bar, uint32_t cta) {
  asm volatile("{\n.reg .b32 ra;\nmapa.shared::cluster.u32 ra, %0, %1;\n"
               "mbarrier.arrive.shared::cluster.b64 _, [ra];\n}" ::"r"(bar), "r"(cta) : "memory");
}
__device__ __forceinline__ void mbar_wait(uint32_t bar, uint32_t parity) {
  uint32_t ok, n = 0;
  do {
    asm volatile("{\n.reg .pred p;\nmbarrier.try_wait.parity.shared::cta.b64 p, [%1], %2;\nselp.u32 %0, 1, 0, p;\n}"
                 : "=r"(ok) : "r"(bar), "r"(parity) : "memory");
  } while (!ok && ++n < SPIN_LIMIT);
}
__device__ __forceinline__ void mbar_wait_cluster(uint32_t bar, uint32_t parity) {
  uint32_t ok, n = 0;
  do {
    asm volatile("{\n.reg .pred p;\nmbarrier.try_wait.parity.acquire.cluster.shared::cta.b64 p, [%1], %2;\nselp.u32 %0, 1, 0, p;\n}"
                 : "=r"(ok) : "r"(bar), "r"(parity) : "memory");
  } while (!ok && ++n < SPIN_LIMIT);
}
__device__ __forceinline__ void tma2d(uint32_t dst, const CUtensorMap* m, int c0, int c1, uint32_t bar) {
  asm volatile("cp.async.bulk.tensor.2d.shared::cluster.global.mbarrier::complete_tx::bytes [%0], [%1, {%3, %4}], [%2];"
               ::"r"(dst), "l"(m), "r"(bar), "r"(c0), "r"(c1) : "memory");
}
__device__ __forceinline__ void tma3d(uint32_t dst, const CUtensorMap* m, int c0, int c1, int c2, uint32_t bar) {
  asm volatile("cp.async.bulk.tensor.3d.shared::cluster.global.mbarrier::complete_tx::bytes [%0], [%1, {%3, %4, %5}], [%2];"
               ::"r"(dst), "l"(m), "r"(bar), "r"(c0), "r"(c1), "r"(c2) : "memory");
}
__device__ __forceinline__ void tma2d_mc(uint32_t dst, const CUtensorMap* m, int c0, int c1, uint32_t bar) {
  asm volatile("cp.async.bulk.tensor.2d.shared::cluster.global.mbarrier::complete_tx::bytes.multicast::cluster [%0], [%1, {%3, %4}], [%2], %5;"
               ::"r"(dst), "l"(m), "r"(bar), "r"(c0), "r"(c1), "h"((uint16_t)3) : "memory");
}
__device__ __forceinline__ void tma3d_mc(uint32_t dst, const CUtensorMap* m, int c0, int c1, int c2, uint32_t bar) {
  asm volatile("cp.async.bulk.tensor.3d.shared::cluster.global.mbarrier::complete_tx::bytes.multicast::cluster [%0], [%1, {%3, %4, %5}], [%2], %6;"
               ::"r"(dst), "l"(m), "r"(bar), "r"(c0), "r"(c1), "r"(c2), "h"((uint16_t)3) : "memory");
}
__device__ __forceinline__ void bulk_g2s(uint32_t dst, const void* src, uint32_t bytes, uint32_t bar) {
  asm volatile("cp.async.bulk.shared::cluster.global.mbarrier::complete_tx::bytes [%0], [%1], %2, [%3];"
               ::"r"(dst), "l"(src), "r"(bytes), "r"(bar) : "memory");
}
__device__ __forceinline__ void bulk_s2g(void* dst, uint32_t src, uint32_t bytes) {
  asm volatile("cp.async.bulk.global.shared::cta.bulk_group [%0], [%1], %2;" ::"l"(dst), "r"(src), "r"(bytes) : "memory");
}
__device__ __forceinline__ void prefetch_tmap(const CUtensorMap* m) {
  asm volatile("prefetch.tensormap [%0];" ::"l"(m) : "memory");
}
__device__ __forceinline__ void l2_prefetch(const void* p, uint32_t bytes) {
  asm volatile("cp.async.bulk.prefetch.L2.global [%0], %1;" ::"l"(p), "r"(bytes) : "memory");
}
__device__ __forceinline__ void wg_fence() { asm volatile("wgmma.fence.sync.aligned;" ::: "memory"); }
__device__ __forceinline__ void wg_commit() { asm volatile("wgmma.commit_group.sync.aligned;" ::: "memory"); }
template <int N> __device__ __forceinline__ void wg_wait() { asm volatile("wgmma.wait_group.sync.aligned %0;" ::"n"(N) : "memory"); }
template <int N> __device__ __forceinline__ void fence_regs(float (&d)[N]) {
#pragma unroll
  for (int i = 0; i < N; i++) asm volatile("" : "+f"(d[i])::"memory");
}
template <int N> __device__ __forceinline__ void fence_regs(uint32_t (&d)[N]) {
#pragma unroll
  for (int i = 0; i < N; i++) asm volatile("" : "+r"(d[i])::"memory");
}
__device__ __forceinline__ void bar_sync(int id, int n) { asm volatile("bar.sync %0, %1;" ::"r"(id), "r"(n) : "memory"); }
__device__ __forceinline__ void bar_arrive(int id, int n) { asm volatile("bar.arrive %0, %1;" ::"r"(id), "r"(n) : "memory"); }
__device__ __forceinline__ void fence_gpu() { asm volatile("fence.acq_rel.gpu;" ::: "memory"); }
__device__ __forceinline__ void fence_async() { asm volatile("fence.proxy.async;" ::: "memory"); }
__device__ __forceinline__ void fence_async_smem() { asm volatile("fence.proxy.async.shared::cta;" ::: "memory"); }
__device__ __forceinline__ void red_add(uint32_t* p, uint32_t v) {
  asm volatile("red.relaxed.gpu.global.add.u32 [%0], %1;" ::"l"(p), "r"(v) : "memory");
}
__device__ __forceinline__ uint32_t ld_relaxed(const uint32_t* p) {
  uint32_t v;
  asm volatile("ld.relaxed.gpu.global.u32 %0, [%1];" : "=r"(v) : "l"(p) : "memory");
  return v;
}
__device__ __forceinline__ void wait_counter(const uint32_t* p, uint32_t target) {
  uint32_t v, n = 0;
  while (true) {
    asm volatile("ld.acquire.gpu.global.u32 %0, [%1];" : "=r"(v) : "l"(p) : "memory");
    if ((int32_t)(v - target) >= 0 || ++n > SPIN_LIMIT) break;
  }
}
__device__ __forceinline__ uint4 ld_relaxed(const uint4* p) {
  uint4 v;
  asm volatile("ld.relaxed.gpu.global.v4.u32 {%0, %1, %2, %3}, [%4];" : "=r"(v.x), "=r"(v.y), "=r"(v.z), "=r"(v.w) : "l"(p) : "memory");
  return v;
}
__device__ __forceinline__ void st_relaxed(uint4* p, uint4 v) {
  asm volatile("st.relaxed.gpu.global.v4.u32 [%0], {%1, %2, %3, %4};" ::"l"(p), "r"(v.x), "r"(v.y), "r"(v.z), "r"(v.w) : "memory");
}
__device__ __forceinline__ void st_relaxed(uint32_t* p, uint32_t v) {
  asm volatile("st.relaxed.gpu.global.u32 [%0], %1;" ::"l"(p), "r"(v) : "memory");
}
__device__ __forceinline__ uint32_t pack2(float lo, float hi) {
  uint32_t r;
  asm("cvt.rn.bf16x2.f32 %0, %1, %2;" : "=r"(r) : "f"(hi), "f"(lo));
  return r;
}
__device__ __forceinline__ uint32_t mul2(uint32_t a, uint32_t b) {
  uint32_t r;
  asm("mul.rn.bf16x2 %0, %1, %2;" : "=r"(r) : "r"(a), "r"(b));
  return r;
}
__device__ __forceinline__ uint32_t fma2(uint32_t a, uint32_t b, uint32_t c) {
  uint32_t r;
  asm("fma.rn.bf16x2 %0, %1, %2, %3;" : "=r"(r) : "r"(a), "r"(b), "r"(c));
  return r;
}
__device__ __forceinline__ uint32_t add2(uint32_t a, uint32_t b) {
  uint32_t r;
  asm("add.rn.bf16x2 %0, %1, %2;" : "=r"(r) : "r"(a), "r"(b));
  return r;
}
__device__ __forceinline__ uint32_t sub2(uint32_t a, uint32_t b) {
  uint32_t r;
  asm("sub.rn.bf16x2 %0, %1, %2;" : "=r"(r) : "r"(a), "r"(b));
  return r;
}
__device__ __forceinline__ uint32_t fms2(uint32_t a, uint32_t b, uint32_t c) {
  uint32_t r;
  asm("{\n.reg .b32 n;\nneg.bf16x2 n, %3;\nfma.rn.bf16x2 %0, %1, %2, n;\n}" : "=r"(r) : "r"(a), "r"(b), "r"(c));
  return r;
}
__device__ __forceinline__ float bf_lo(uint32_t v) { return __uint_as_float(v << 16); }
__device__ __forceinline__ float bf_hi(uint32_t v) { return __uint_as_float(v & 0xffff0000u); }
__device__ __forceinline__ float bf_round(float v) { return bf_lo(pack2(v, 0.f)); }
__device__ __forceinline__ float tanh_fast(float v) {
  float r;
  asm("tanh.approx.f32 %0, %1;" : "=f"(r) : "f"(v));
  return r;
}
__device__ __forceinline__ uint64_t mk_desc(uint32_t addr, uint32_t lbo, uint32_t sbo, uint32_t mode) {
  return (uint64_t)((addr & 0x3FFFF) >> 4) | ((uint64_t)(lbo >> 4) << 16) | ((uint64_t)(sbo >> 4) << 32) | ((uint64_t)mode << 62);
}
__device__ __forceinline__ void stmatrix_x4(uint32_t addr, uint32_t r0, uint32_t r1, uint32_t r2, uint32_t r3) {
  asm volatile("stmatrix.sync.aligned.m8n8.x4.shared.b16 [%0], {%1, %2, %3, %4};" ::"r"(addr), "r"(r0), "r"(r1), "r"(r2), "r"(r3) : "memory");
}

template <int TA, int TB>
__device__ __forceinline__ void wgmma_ss_n256(float (&d)[128], uint64_t da, uint64_t db, int sd) {
  asm volatile("{\n.reg .pred p;\nsetp.ne.b32 p, %130, 0;\n"
      "wgmma.mma_async.sync.aligned.m64n256k16.f32.bf16.bf16 {"
      "%0, %1, %2, %3, %4, %5, %6, %7, %8, %9, %10, %11, %12, %13, %14, %15, %16, %17, %18, %19, %20, %21, %22, %23, "
      "%24, %25, %26, %27, %28, %29, %30, %31, %32, %33, %34, %35, %36, %37, %38, %39, %40, %41, %42, %43, %44, %45, "
      "%46, %47, %48, %49, %50, %51, %52, %53, %54, %55, %56, %57, %58, %59, %60, %61, %62, %63, %64, %65, %66, %67, "
      "%68, %69, %70, %71, %72, %73, %74, %75, %76, %77, %78, %79, %80, %81, %82, %83, %84, %85, %86, %87, %88, %89, "
      "%90, %91, %92, %93, %94, %95, %96, %97, %98, %99, %100, %101, %102, %103, %104, %105, %106, %107, %108, %109, "
      "%110, %111, %112, %113, %114, %115, %116, %117, %118, %119, %120, %121, %122, %123, %124, %125, %126, %127"
      "}, %128, %129, p, 1, 1, %131, %132;\n}\n"
      : "+f"(d[0]), "+f"(d[1]), "+f"(d[2]), "+f"(d[3]), "+f"(d[4]), "+f"(d[5]), "+f"(d[6]), "+f"(d[7]), "+f"(d[8]),
        "+f"(d[9]), "+f"(d[10]), "+f"(d[11]), "+f"(d[12]), "+f"(d[13]), "+f"(d[14]), "+f"(d[15]), "+f"(d[16]),
        "+f"(d[17]), "+f"(d[18]), "+f"(d[19]), "+f"(d[20]), "+f"(d[21]), "+f"(d[22]), "+f"(d[23]), "+f"(d[24]),
        "+f"(d[25]), "+f"(d[26]), "+f"(d[27]), "+f"(d[28]), "+f"(d[29]), "+f"(d[30]), "+f"(d[31]), "+f"(d[32]),
        "+f"(d[33]), "+f"(d[34]), "+f"(d[35]), "+f"(d[36]), "+f"(d[37]), "+f"(d[38]), "+f"(d[39]), "+f"(d[40]),
        "+f"(d[41]), "+f"(d[42]), "+f"(d[43]), "+f"(d[44]), "+f"(d[45]), "+f"(d[46]), "+f"(d[47]), "+f"(d[48]),
        "+f"(d[49]), "+f"(d[50]), "+f"(d[51]), "+f"(d[52]), "+f"(d[53]), "+f"(d[54]), "+f"(d[55]), "+f"(d[56]),
        "+f"(d[57]), "+f"(d[58]), "+f"(d[59]), "+f"(d[60]), "+f"(d[61]), "+f"(d[62]), "+f"(d[63]), "+f"(d[64]),
        "+f"(d[65]), "+f"(d[66]), "+f"(d[67]), "+f"(d[68]), "+f"(d[69]), "+f"(d[70]), "+f"(d[71]), "+f"(d[72]),
        "+f"(d[73]), "+f"(d[74]), "+f"(d[75]), "+f"(d[76]), "+f"(d[77]), "+f"(d[78]), "+f"(d[79]), "+f"(d[80]),
        "+f"(d[81]), "+f"(d[82]), "+f"(d[83]), "+f"(d[84]), "+f"(d[85]), "+f"(d[86]), "+f"(d[87]), "+f"(d[88]),
        "+f"(d[89]), "+f"(d[90]), "+f"(d[91]), "+f"(d[92]), "+f"(d[93]), "+f"(d[94]), "+f"(d[95]), "+f"(d[96]),
        "+f"(d[97]), "+f"(d[98]), "+f"(d[99]), "+f"(d[100]), "+f"(d[101]), "+f"(d[102]), "+f"(d[103]), "+f"(d[104]),
        "+f"(d[105]), "+f"(d[106]), "+f"(d[107]), "+f"(d[108]), "+f"(d[109]), "+f"(d[110]), "+f"(d[111]),
        "+f"(d[112]), "+f"(d[113]), "+f"(d[114]), "+f"(d[115]), "+f"(d[116]), "+f"(d[117]), "+f"(d[118]),
        "+f"(d[119]), "+f"(d[120]), "+f"(d[121]), "+f"(d[122]), "+f"(d[123]), "+f"(d[124]), "+f"(d[125]),
        "+f"(d[126]), "+f"(d[127])
      : "l"(da), "l"(db), "r"(sd), "n"(TA), "n"(TB));
}
template <int TA, int TB>
__device__ __forceinline__ void wgmma_ss_n128(float (&d)[64], uint64_t da, uint64_t db, int sd) {
  asm volatile("{\n.reg .pred p;\nsetp.ne.b32 p, %66, 0;\n"
      "wgmma.mma_async.sync.aligned.m64n128k16.f32.bf16.bf16 {"
      "%0, %1, %2, %3, %4, %5, %6, %7, %8, %9, %10, %11, %12, %13, %14, %15, %16, %17, %18, %19, %20, %21, %22, %23, "
      "%24, %25, %26, %27, %28, %29, %30, %31, %32, %33, %34, %35, %36, %37, %38, %39, %40, %41, %42, %43, %44, %45, "
      "%46, %47, %48, %49, %50, %51, %52, %53, %54, %55, %56, %57, %58, %59, %60, %61, %62, %63"
      "}, %64, %65, p, 1, 1, %67, %68;\n}\n"
      : "+f"(d[0]), "+f"(d[1]), "+f"(d[2]), "+f"(d[3]), "+f"(d[4]), "+f"(d[5]), "+f"(d[6]), "+f"(d[7]), "+f"(d[8]),
        "+f"(d[9]), "+f"(d[10]), "+f"(d[11]), "+f"(d[12]), "+f"(d[13]), "+f"(d[14]), "+f"(d[15]), "+f"(d[16]),
        "+f"(d[17]), "+f"(d[18]), "+f"(d[19]), "+f"(d[20]), "+f"(d[21]), "+f"(d[22]), "+f"(d[23]), "+f"(d[24]),
        "+f"(d[25]), "+f"(d[26]), "+f"(d[27]), "+f"(d[28]), "+f"(d[29]), "+f"(d[30]), "+f"(d[31]), "+f"(d[32]),
        "+f"(d[33]), "+f"(d[34]), "+f"(d[35]), "+f"(d[36]), "+f"(d[37]), "+f"(d[38]), "+f"(d[39]), "+f"(d[40]),
        "+f"(d[41]), "+f"(d[42]), "+f"(d[43]), "+f"(d[44]), "+f"(d[45]), "+f"(d[46]), "+f"(d[47]), "+f"(d[48]),
        "+f"(d[49]), "+f"(d[50]), "+f"(d[51]), "+f"(d[52]), "+f"(d[53]), "+f"(d[54]), "+f"(d[55]), "+f"(d[56]),
        "+f"(d[57]), "+f"(d[58]), "+f"(d[59]), "+f"(d[60]), "+f"(d[61]), "+f"(d[62]), "+f"(d[63])
      : "l"(da), "l"(db), "r"(sd), "n"(TA), "n"(TB));
}
template <int TA, int TB>
__device__ __forceinline__ void wgmma_ss_n64(float (&d)[32], uint64_t da, uint64_t db, int sd) {
  asm volatile("{\n.reg .pred p;\nsetp.ne.b32 p, %34, 0;\n"
      "wgmma.mma_async.sync.aligned.m64n64k16.f32.bf16.bf16 {"
      "%0, %1, %2, %3, %4, %5, %6, %7, %8, %9, %10, %11, %12, %13, %14, %15, %16, %17, %18, %19, %20, %21, %22, %23, "
      "%24, %25, %26, %27, %28, %29, %30, %31"
      "}, %32, %33, p, 1, 1, %35, %36;\n}\n"
      : "+f"(d[0]), "+f"(d[1]), "+f"(d[2]), "+f"(d[3]), "+f"(d[4]), "+f"(d[5]), "+f"(d[6]), "+f"(d[7]), "+f"(d[8]),
        "+f"(d[9]), "+f"(d[10]), "+f"(d[11]), "+f"(d[12]), "+f"(d[13]), "+f"(d[14]), "+f"(d[15]), "+f"(d[16]),
        "+f"(d[17]), "+f"(d[18]), "+f"(d[19]), "+f"(d[20]), "+f"(d[21]), "+f"(d[22]), "+f"(d[23]), "+f"(d[24]),
        "+f"(d[25]), "+f"(d[26]), "+f"(d[27]), "+f"(d[28]), "+f"(d[29]), "+f"(d[30]), "+f"(d[31])
      : "l"(da), "l"(db), "r"(sd), "n"(TA), "n"(TB));
}
template <int SA, int TB>
__device__ __forceinline__ void wgmma_rs_n64(float (&d)[32], uint32_t a0, uint32_t a1, uint32_t a2, uint32_t a3, uint64_t db, int sd) {
  asm volatile("{\n.reg .pred p;\nsetp.ne.b32 p, %37, 0;\n"
      "wgmma.mma_async.sync.aligned.m64n64k16.f32.bf16.bf16 {"
      "%0, %1, %2, %3, %4, %5, %6, %7, %8, %9, %10, %11, %12, %13, %14, %15, %16, %17, %18, %19, %20, %21, %22, %23, "
      "%24, %25, %26, %27, %28, %29, %30, %31"
      "}, {%32, %33, %34, %35}, %36, p, %38, 1, %39;\n}\n"
      : "+f"(d[0]), "+f"(d[1]), "+f"(d[2]), "+f"(d[3]), "+f"(d[4]), "+f"(d[5]), "+f"(d[6]), "+f"(d[7]), "+f"(d[8]),
        "+f"(d[9]), "+f"(d[10]), "+f"(d[11]), "+f"(d[12]), "+f"(d[13]), "+f"(d[14]), "+f"(d[15]), "+f"(d[16]),
        "+f"(d[17]), "+f"(d[18]), "+f"(d[19]), "+f"(d[20]), "+f"(d[21]), "+f"(d[22]), "+f"(d[23]), "+f"(d[24]),
        "+f"(d[25]), "+f"(d[26]), "+f"(d[27]), "+f"(d[28]), "+f"(d[29]), "+f"(d[30]), "+f"(d[31])
      : "r"(a0), "r"(a1), "r"(a2), "r"(a3), "l"(db), "r"(sd), "n"(SA), "n"(TB));
}

__device__ __forceinline__ uint32_t BAR_FULL(uint32_t sb, int i) { return sb + SM_BAR + 8 * i; }
__device__ __forceinline__ uint32_t BAR_EMPTY(uint32_t sb, int i) { return sb + SM_BAR + 64 + 8 * i; }
__device__ __forceinline__ uint32_t BAR_X(uint32_t sb, int i) { return sb + SM_BAR + 128 + 8 * i; }
__device__ __forceinline__ uint32_t BAR_Y(uint32_t sb, int i) { return sb + SM_BAR + 192 + 8 * i; }
__device__ __forceinline__ uint32_t BAR_XFREE(uint32_t sb) { return sb + SM_BAR + 256; }

__device__ __forceinline__ uint32_t BAR_E2(uint32_t sb, int i) { return sb + SM_BAR + 264 + 8 * i; }
#define CMASK 0xd4u
#define XORDER 0, 1, 11, 2, 3, 12, 13, 4, 5, 14, 6, 15, 16
#define XSPREAD 2
#define PFAT 3
#define SKEW 3
#define GS0 2
#define GL2 6
#define GS1 4
constexpr int Q_G1B = 18, Q_G2 = 32, Q_XR = 39, Q_P3 = 46, Q_END = 50;

__device__ __forceinline__ uint32_t y_addr(int kb) { return kb < 3 ? SM_RING + (kb + (Q_G2 + 4) % NSTAGE) * STAGE_BYTES : SM_X + (kb - 3) * 16384; }
static_assert((Q_G2 + 4) % NSTAGE + 2 < NSTAGE, "");

struct Ring {
  uint32_t slot, phase;
  __device__ __forceinline__ void next() { if (++slot == NSTAGE) { slot = 0; phase ^= 1; } }
};

__device__ __forceinline__ void release_slot(uint32_t sb, uint32_t slot, int tid, int times) {
  if (tid < 2 * times) mbar_arrive_cluster(BAR_EMPTY(sb, slot), tid & 1);
}

__device__ __forceinline__ void ffn_consumer(uint32_t sb, const uint8_t* smem, const Params& p, int bid, int wg, int tid, int mt, int jj) {
  const int lane = tid & 31, warp = tid >> 5, q = lane & 3, r0 = 16 * warp + (lane >> 2);
  uint32_t* const my_epoch = &p.s->epoch[blockIdx.x * 12 + (threadIdx.x >> 5)];
  const uint32_t epoch = ld_relaxed(my_epoch) + 1;
  Ring rg{0, 0};
  uint32_t u[64];
  float acc[128];
  uint32_t prev = 0, cmask = CMASK;
  int st = 0;
  auto g1_stage = [&](uint32_t slot, int s) {
    const uint64_t da = mk_desc(sb + SM_X + (s >> 1) * 16384 + wg * 8192 + (s & 1) * 64, 16, 1024, 1);
    const uint64_t db = mk_desc(sb + SM_RING + slot * STAGE_BYTES, 4096, 1024, 1);
    wg_fence();
    wgmma_ss_n256<0, 1>(acc, da, db, s != 0);
    wgmma_ss_n256<0, 1>(acc, da + 2, db + 128, 1);
    wg_commit();
  };
  if (wg == 1) {
    float ap[64];
    constexpr int QX = 32 - __builtin_clz(CMASK);
    constexpr int NPRE = QX + XSPREAD;
    uint4* const x1dst = p.s->x1t + ((64 * jj + r0 + 8) >> 2) * 1024 + (r0 & 3) * 128 + 8 * mt + (q ^ (mt & 3));
    const int x1lo = 64 * jj + r0 == 1 ? 110 * 1024 - 128 : -2048;
#pragma unroll
    for (int qi = 0; qi < NPRE; qi++) {
      const int slot = qi % NSTAGE, nc = __builtin_popcount(CMASK & ((1u << qi) - 1));
      if (qi == 0) TL(60);
      mbar_wait(BAR_FULL(sb, slot), (qi / NSTAGE) & 1);
      if (qi == 0) TL(61);
      if ((CMASK >> qi) & 1) {
#pragma unroll
        for (int kb = 2 * nc; kb < 2 * nc + 2 && kb < 7; kb++) {
          const uint64_t da = mk_desc(sb + SM_RING + slot * STAGE_BYTES + (kb & 1) * 8192, 8192, 1024, 1);
          const uint64_t db = mk_desc(sb + SM_X + kb * 16384, 16, 1024, 1);
          mbar_wait(BAR_X(sb, kb), 0);
          TL(16 + kb);
          wg_fence();
#pragma unroll
          for (int kk = 0; kk < 4; kk++) wgmma_ss_n128<1, 0>(ap, da + kk * 128, db + kk * 2, (kb | kk) != 0);
          wg_commit();
        }
      } else {
        if (((qi - nc) & 1) == 0 && qi - nc >= 4 * nc) mbar_wait(BAR_X(sb, (qi - nc) >> 1), 0);
        TL(32 + qi - nc);
        g1_stage(slot, qi - nc);
      }
      if (qi > 0) {
        wg_wait<1>();
        release_slot(sb, (qi - 1) % NSTAGE, tid, ((CMASK >> (qi - 1)) & 1) ? 2 : 1);
      }
      if (qi >= QX) {
        if (qi == QX) { fence_regs(ap); TL(2); }
#pragma unroll
        for (int t = (qi - QX) * (4 / XSPREAD); t < (qi - QX + 1) * (4 / XSPREAD); t++)
#pragma unroll
        for (int h = 0; h < 2; h++)
          x1dst[(h ? 0 : x1lo) + 512 * (t & 1) + 4 * (t >> 1)] = make_uint4((pack2(ap[16 * t + 2 * h], ap[16 * t + 2 * h + 1]) & ~1u) | (epoch & 1), pack2(ap[16 * t + 4 + 2 * h], ap[16 * t + 5 + 2 * h]),
                                             pack2(ap[16 * t + 8 + 2 * h], ap[16 * t + 9 + 2 * h]), pack2(ap[16 * t + 12 + 2 * h], ap[16 * t + 13 + 2 * h]));
      }
    }
    bar_arrive(7, 160);
    st = NPRE - 4; cmask = 0; prev = (NPRE - 1) % NSTAGE;
    rg.slot = NPRE % NSTAGE; rg.phase = (NPRE / NSTAGE) & 1;
  }
#pragma unroll 1
  for (int pass = 0; pass < 2; pass++) {
#pragma unroll 1
    for (; st < 14; st++) {
      while (cmask & 1) { cmask >>= 1; rg.next(); }
      cmask >>= 1;
      if (pass == 0 && (st & 1) == 0) mbar_wait(BAR_X(sb, st >> 1), 0);
      if (st == 14 - SKEW && wg == 1) bar_sync(9 + pass, 256);
      mbar_wait(BAR_FULL(sb, rg.slot), rg.phase);
      TL(32 + 14 * pass + st);
      g1_stage(rg.slot, st);
      wg_wait<1>();
      if (st > 0) release_slot(sb, prev, tid, 1);
      prev = rg.slot;
      rg.next();
    }
    st = 0;
    if (wg == 0) bar_arrive(9 + pass, 256);
    wg_wait<0>();
    fence_regs(acc);
    release_slot(sb, prev, tid, 1);
    TL(3 + 2 * pass);
#pragma unroll
    for (int i = 0; i < 32; i++) {
      const float g0 = 0.5f * acc[2 * i], g1 = 0.5f * acc[2 * i + 1];
      const float s0 = fmaf(g0, tanh_fast(g0), g0), s1 = fmaf(g1, tanh_fast(g1), g1);
      u[32 + i] = pack2(s0 * acc[64 + 2 * i], s1 * acc[64 + 2 * i + 1]);
    }
    if (pass == 0) {
#pragma unroll
      for (int i = 0; i < 32; i++) u[i] = u[32 + i];
    }
    TL(4 + 2 * pass);
  }
  fence_regs(u);
  float accA[32], accB[32];
  auto stage = [&](float (&acc)[32], int qi) {
    const int st = qi & 1;
    if (qi < Q_XR) mbar_wait(BAR_FULL(sb, qi % NSTAGE), (qi / NSTAGE) & 1);
    else mbar_wait(BAR_X(sb, qi - Q_XR), 1);
    const uint64_t db = mk_desc(sb + (qi < Q_XR ? SM_RING + (qi % NSTAGE) * STAGE_BYTES : SM_X + (qi - Q_XR) * 16384), 8192, 1024, 1);
    wg_fence();
#pragma unroll
    for (int kk = 0; kk < 8; kk++) {
      const uint32_t* a = u + 32 * st + 4 * kk;
      wgmma_rs_n64<1, 1>(acc, a[0], a[1], a[2], a[3], db + kk * 128, (st | kk) != 0);
    }
    wg_commit();
  };
  auto retire = [&](int qi) {
    wg_wait<1>();
    if (qi >= Q_G2 && qi < Q_G2 + 4) release_slot(sb, qi % NSTAGE, tid, 1);
    else if (qi >= Q_G2 + 4 && qi < Q_G2 + 11 && tid == 0) mbar_arrive(BAR_E2(sb, qi - Q_G2 - 4));
  };
  const uint32_t par = epoch & 1;
  auto put = [&](float (&acc)[32], int c) {
    fence_regs(acc);
    int o = jj + 1 + c;
    if (o >= 7) o -= 7;
    uint4* dst = p.s->part + ((((mt * 7 + o) * 6 + c) * 2 + wg) * 4) * 128 + tid;
#pragma unroll
    for (int v = 0; v < 4; v++) {
      const float* a = acc + 8 * v;
      st_relaxed(dst + v * 128, make_uint4((pack2(a[0], a[1]) & ~1u) | par, pack2(a[2], a[3]), pack2(a[4], a[5]), pack2(a[6], a[7])));
    }
  };
  const uint4* const src = p.s->part + (((mt * 7 + jj) * 6 * 2 + wg) * 4) * 128 + tid;
  auto gload = [&](uint4 (&pv)[8], int c) {
#pragma unroll
    for (int i = 0; i < 8; i++) pv[i] = ld_relaxed(src + ((2 * c + (i >> 2)) * 8 + (i & 3)) * 128);
  };
  auto gload1 = [&](uint4 (&pv)[8], int c) {
#pragma unroll
    for (int i = 0; i < 4; i++) pv[4 * (c & 1) + i] = ld_relaxed(src + (c * 8 + i) * 128);
  };
  auto gsum = [&](uint4 (&pv)[8], int c) {
#pragma unroll 1
    for (uint32_t n = 0; n < SPIN_LIMIT; n++) {
      uint32_t bad = 0;
#pragma unroll
      for (int i = 0; i < 8; i++) bad |= pv[i].x ^ par;
      if (!__any_sync(0xffffffffu, bad & 1)) break;
      gload(pv, c);
    }
    TL(24 + c);
#pragma unroll
    for (int i = 0; i < 4; i++) {
      const uint32_t w[4] = {add2(pv[i].x, pv[4 + i].x), add2(pv[i].y, pv[4 + i].y), add2(pv[i].z, pv[4 + i].z), add2(pv[i].w, pv[4 + i].w)};
#pragma unroll
      for (int k = 0; k < 4; k++) { accA[8 * i + 2 * k] += bf_lo(w[k]); accA[8 * i + 2 * k + 1] += bf_hi(w[k]); }
    }
  };
  uint4 pv0[8], pv1[8], pv2[8];
  const int row = 128 * mt + 64 * wg + r0;
  uint32_t gt0, gt1;
#pragma unroll
  for (int c2 = 0; c2 < 4; c2++) {
    const int qi = Q_G2 + 4 * c2;
    stage(accA, qi);
    retire(qi - 1);
    stage(accA, qi + 1);
    if (c2 == 3) TL(27);
    if (c2 > 0) put(accB, 2 * c2 - 1);
    if (c2 == 2) gload1(pv0, 1);
    if (c2 == 3) gload1(pv1, 3);
    TL(7 + c2);
    if (c2 == 3) break;
    retire(qi);
    stage(accB, qi + 2);
    retire(qi + 1);
    stage(accB, qi + 3);
    put(accA, 2 * c2);
    if (c2 == 1) gload1(pv0, 0);
    if (c2 == 2) gload1(pv1, 2);
    if (c2 == 0) { gt0 = ld_relaxed(&p.s->gate[row]); gt1 = ld_relaxed(&p.s->gate[row + 8]); }
    retire(qi + 2);
  }
#pragma unroll
  for (int kb = 0; kb < 7; kb++) {
    const int qt = Q_XR + (kb >> 1);
    if ((kb & 1) == 0) mbar_wait(BAR_FULL(sb, qt % NSTAGE), (qt / NSTAGE) & 1);
    mbar_wait(BAR_Y(sb, kb), 0);
    const uint64_t da = mk_desc(sb + y_addr(kb) + wg * 8192, 8192, 1024, 1);
    const uint64_t db = mk_desc(sb + SM_RING + (qt % NSTAGE) * STAGE_BYTES + (kb & 1) * 8192, 16, 1024, 1);
    wg_fence();
#pragma unroll
    for (int kk = 0; kk < 4; kk++) wgmma_ss_n64<1, 0>(accB, da + kk * 128, db + kk * 2, (kb | kk) != 0);
    wg_commit();
    if (kb == 1) { wg_wait<2>(); fence_regs(accA); TL(15); }
    if (kb == GS0) gsum(pv0, 0);
    if (kb == GL2) gload(pv2, 2);
    if (kb == GS1) gsum(pv1, 1);
  }
  TL(11);
  for (uint32_t n = 0; (((gt0 ^ epoch) | (gt1 ^ epoch)) & 0xffffu) && n < SPIN_LIMIT; n++) {
    gt0 = ld_relaxed(&p.s->gate[row]); gt1 = ld_relaxed(&p.s->gate[row + 8]);
  }
  gsum(pv2, 2);
  const float ga0 = bf_hi(gt0), ga1 = bf_hi(gt1);
  TL(12);
  wg_wait<0>();
  fence_regs(accB);
  TL(13);
  const float gb0 = bf_round(1.f - ga0), gb1 = bf_round(1.f - ga1);
  const float gs0 = ga0 * (2.f / (float)(S_ * D_)), gs1 = ga1 * (2.f / (float)(S_ * D_));
  uint4* const o = reinterpret_cast<uint4*>(p.out + (size_t)row * D_ + 64 * jj + 8 * q);
#pragma unroll
  for (int h = 0; h < 2; h++) {
    const float gs = h ? gs1 : gs0, gb = h ? gb1 : gb0;
#pragma unroll
    for (int k = 0; k < 2; k++) {
      uint32_t w[4];
#pragma unroll
      for (int j = 0; j < 4; j++) {
        const int i = 16 * k + 4 * j + 2 * h;
        w[j] = pack2(fmaf(gs, accB[i], gb * accA[i]), fmaf(gs, accB[i + 1], gb * accA[i + 1]));
      }
      const bool o1 = q & 1, o2 = q & 2;
      uint32_t a = __shfl_xor_sync(0xffffffffu, o1 ? w[0] : w[1], 1), b = __shfl_xor_sync(0xffffffffu, o1 ? w[2] : w[3], 1);
      if (o1) { w[0] = a; w[2] = b; } else { w[1] = a; w[3] = b; }
      a = __shfl_xor_sync(0xffffffffu, o2 ? w[0] : w[2], 2); b = __shfl_xor_sync(0xffffffffu, o2 ? w[1] : w[3], 2);
      if (o2) { w[0] = a; w[1] = b; } else { w[2] = a; w[3] = b; }
      o[h * D_ + 4 * k] = make_uint4(w[0], w[1], w[2], w[3]);
    }
  }
  if (lane == 0) *my_epoch = epoch;
  TL(14);
}

__device__ __forceinline__ void ring_issue(uint32_t sb, const Params& p, int qi, uint32_t slot, bool wait, uint32_t phase, int jj, uint32_t rank) {
  const CUtensorMap* m;
  int c0, c1, c2 = 0;
  bool half = false, is3d = false;
  if (qi < Q_G2) {
    const int nc = __popc(CMASK & ((1u << qi) - 1));
    if ((CMASK >> qi) & 1) {
      m = &p.ct; c0 = 64 * jj; c1 = 128 * nc + 64 * rank; half = nc == 3;
    } else {
      const int pass = qi >= Q_G1B;
      m = rank ? &p.wu : &p.wg; c0 = 0; c1 = 32 * (qi - nc - 14 * pass); c2 = 4 * jj + 2 * pass; is3d = true;
    }
  } else if (qi < Q_P3) {
    int o = jj + 1 + ((qi - Q_G2) >> 1);
    if (o >= 7) o -= 7;
    m = &p.wd; c0 = 64 * o; c1 = 256 * jj + 128 * (qi & 1) + 64 * rank;
  } else {
    m = &p.ct; c0 = 128 * (qi - Q_P3) + 64 * rank; c1 = 64 * jj; half = qi == Q_END - 1;
  }
  uint32_t bar = BAR_FULL(sb, slot), dst = sb + SM_RING + slot * STAGE_BYTES + rank * 8192;
  if (qi >= Q_XR && qi < Q_P3) {
    bar = BAR_X(sb, qi - Q_XR); dst = sb + SM_X + (qi - Q_XR) * 16384 + rank * 8192;
    if (qi == Q_XR) mbar_wait_cluster(BAR_XFREE(sb), 0);
  } else {
    if (wait) mbar_wait_cluster(BAR_EMPTY(sb, slot), phase ^ (qi >= Q_P3));
    mbar_expect_tx(bar, half ? 8192 : 16384);
  }
  if (is3d) tma3d_mc(dst, m, c0, c1, c2, bar);
  else if (!(half && rank)) tma2d_mc(dst, m, c0, c1, bar);
}

__device__ __forceinline__ void ffn_producer(uint32_t sb, const uint8_t* smem, int bid, const Params& p, int warp, int lane, int mt, int jj, uint32_t rank) {
  if (warp < 2) {
    if (lane == 0) {
      uint32_t slot = warp, phase = 0;
#pragma unroll 1
      for (int qi = NSTAGE + warp; qi < Q_END; qi += 2) {
        if (qi < Q_XR || qi >= Q_P3) ring_issue(sb, p, qi, slot, true, phase, jj, rank);
        if (warp == 1 && qi >= Q_G1B + 8 && qi < Q_XR) ring_issue(sb, p, Q_XR + ((qi - Q_G1B - 8) >> 1), 0, false, 0, jj, rank);
        TL(10 + qi);
        slot += 2;
        if (slot >= NSTAGE) { slot -= NSTAGE; phase ^= 1; }
      }
    }
  } else {
    const int wg = warp - 2;
    uint32_t* const my_epoch = &p.s->epoch[blockIdx.x * 12 + 8 + warp];
    const uint32_t epoch = ld_relaxed(my_epoch) + 1;
    if (wg == 0) {
      if (lane == 0) { prefetch_tmap(&p.wd); prefetch_tmap(&p.yt); }
      {
        const uint4* gw4 = reinterpret_cast<const uint4*>(p.gate_w);
        const uint4 ga = __ldg(gw4 + lane), gb = lane < 24 ? __ldg(gw4 + 32 + lane) : make_uint4(0, 0, 0, 0);
        if (lane < 7) { mbar_wait(BAR_X(sb, lane), 0); mbar_expect_tx(BAR_X(sb, lane), 16384); mbar_expect_tx(BAR_Y(sb, lane), 16384); }
        __syncwarp();
        float mine = 0.f;
#pragma unroll 1
        for (int u = 0; u < 19; u++) {
          const int r = min(19 * jj + u, 127);
          const uint8_t* xr = smem + SM_X + (lane >> 3) * 16384 + r * 128 + (((lane ^ r) & 7) << 4);
          const uint4 xa = *reinterpret_cast<const uint4*>(xr);
          const uint4 xb = lane < 24 ? *reinterpret_cast<const uint4*>(xr + 65536) : make_uint4(0, 0, 0, 0);
          float s = 0.f;
          auto dot2 = [&](uint32_t a, uint32_t b) {
            const uint32_t pr = mul2(a, b);
            s += bf_lo(pr) + bf_hi(pr);
          };
          dot2(xa.x, ga.x); dot2(xa.y, ga.y); dot2(xa.z, ga.z); dot2(xa.w, ga.w);
          dot2(xb.x, gb.x); dot2(xb.y, gb.y); dot2(xb.z, gb.z); dot2(xb.w, gb.w);
#pragma unroll
          for (int o = 16; o > 0; o >>= 1) s += __shfl_xor_sync(0xffffffffu, s, o);
          if (lane == u) mine = s;
        }
        if (lane < 19 && 19 * jj + lane < 128)
          st_relaxed(&p.s->gate[128 * mt + 19 * jj + lane], pack2(0.f, 1.f / (1.f + __expf(-bf_round(mine)))) | (epoch & 0xffffu));
      }
      TL(9);
      if (lane < 2) mbar_arrive_cluster(BAR_XFREE(sb), lane);
    } else {
      mbar_wait(BAR_X(sb, PFAT), 0);
      if (lane < 6) {
        int row = 176 + 3 * bid + (lane >> 1);
        if (row >= D_) row -= D_;
        l2_prefetch(((lane & 1) ? p.pwu : p.pwg) + row * F_, F_ * 2);
      }
      TL(2);
      bar_sync(7, 160);
      if (lane == 0) { red_add(&p.s->cnt_x1[jj * 32], 1);
        l2_prefetch(p.pwd + bid * 16 * D_, 32 * D_); }
      TL(5);
    }
    mbar_wait(BAR_E2(sb, 0), 0);
    TL(3);
    const int kb = 2 * lane + wg;
    bool todo = kb < 7, ready = false;
    uint32_t n = 0;
    while (__any_sync(0xffffffffu, todo)) {
      if (todo) {
        uint32_t ok;
        if (!ready) {
          asm volatile("ld.acquire.gpu.global.u32 %0, [%1];" : "=r"(ok) : "l"(&p.s->cnt_y[kb * 32]) : "memory");
          ready = (int32_t)(ok - epoch * (kb ? 16 : 17)) >= 0;
        }
        asm volatile("{\n.reg .pred p;\nmbarrier.test_wait.parity.shared::cta.b64 p, [%1], 0;\nselp.u32 %0, 1, 0, p;\n}"
                     : "=r"(ok) : "r"(BAR_E2(sb, kb)) : "memory");
        if ((ok && ready) || ++n > SPIN_LIMIT) {
          tma3d(sb + y_addr(kb), &p.yt, 0, 64 * kb, 2 * mt, BAR_Y(sb, kb));
          todo = false;
        }
      }
      __nanosleep(40);
    }
    TL(4);
    if (lane == 0) *my_epoch = epoch;
  }
}

__device__ __forceinline__ void spectral_cta(uint32_t sb, uint8_t* smem, const Params& p, int sc, int wg) {
  const int t384 = threadIdx.x, lane = t384 & 31, warp12 = t384 >> 5, tid = t384 & 127;
  const int warp = tid >> 5, q = lane & 3;
  const int sl0 = 6 * sc + min(sc, 8), nsl = sc < 8 ? 7 : 6;
  if (t384 == 320) {
#pragma unroll 1
    for (int i = 0; i < nsl; i++) {
      mbar_expect_tx(BAR_X(sb, i), 2 * SLAB_BYTES);
      const int row = 128 * ((sl0 + i) >> 3) + 8 * ((sl0 + i) & 7);
      const uint32_t dst = sb + SP_Z + 2 * i * SLAB_BYTES;
      bulk_g2s(dst, p.w_r + row * DF_, SLAB_BYTES / 2, BAR_X(sb, i));
      bulk_g2s(dst + SLAB_BYTES / 2, p.w_r + (row + 64) * DF_, SLAB_BYTES / 2, BAR_X(sb, i));
      bulk_g2s(dst + SLAB_BYTES, p.w_i + row * DF_, SLAB_BYTES / 2, BAR_X(sb, i));
      bulk_g2s(dst + 3 * SLAB_BYTES / 2, p.w_i + (row + 64) * DF_, SLAB_BYTES / 2, BAR_X(sb, i));
    }
  } else if (t384 == 352 && sc < 19) {
    mbar_expect_tx(BAR_Y(sb, 6), 24576);
    bulk_g2s(sb + SP_TW, p.spec, 24576, BAR_Y(sb, 6));
  }
  uint32_t* const my_epoch = &p.s->epoch[blockIdx.x * 12 + warp12];
  const uint32_t epoch = ld_relaxed(my_epoch) + 1;
  uint32_t fe[16], tw[16];
#pragma unroll
  for (int i = 0; i < 4; i++) {
    const uint4 a = __ldg(reinterpret_cast<const uint4*>(p.spec->fe) + i * 128 + tid);
    const uint4 b = __ldg(reinterpret_cast<const uint4*>(p.spec->tw) + i * 128 + tid);
    fe[4 * i] = a.x; fe[4 * i + 1] = a.y; fe[4 * i + 2] = a.z; fe[4 * i + 3] = a.w;
    tw[4 * i] = b.x; tw[4 * i + 1] = b.y; tw[4 * i + 2] = b.z; tw[4 * i + 3] = b.w;
  }
  __syncwarp();
  asm volatile("barrier.cluster.wait.acquire.aligned;" ::: "memory");
#pragma unroll 2
  for (int un = wg; un < 8 * nsl; un += 3) {
    const int i = un >> 3, sl = sl0 + i, pr = 16 * (un & 7) + 4 * (lane >> 3) + warp, r = lane & 7;
    mbar_wait(BAR_X(sb, i), 0);
    if (pr < 113) {
      const uint16_t* w = reinterpret_cast<const uint16_t*>(smem + SP_Z + 2 * i * SLAB_BYTES) + r * DF_ + 2 * pr;
      const uint32_t m = pr < 112 ? 0xffffffffu : 0u;
      p.s->wt[pr * 1024 + sl * 8 + (r ^ ((sl >> 2) & 6))] =
          make_uint4(w[0] | ((uint32_t)w[8 * DF_] << 16), w[16 * DF_] | ((uint32_t)w[24 * DF_] << 16),
                     (w[1] | ((uint32_t)w[8 * DF_ + 1] << 16)) & m, (w[16 * DF_ + 1] | ((uint32_t)w[24 * DF_ + 1] << 16)) & m);
    }
  }
  __syncthreads();
  if (t384 == 352) { fence_gpu(); red_add(&p.s->cnt_w[0], 1); TL(2); }
  TL(1);
  if (sc == 19) return;
  const int nrnd = (sc == 18 && wg == 2) ? 1 : 2;
  auto pair_of = [&](int r) { const int i = 3 * sc + wg + 57 * r; return i ? i - 1 : 112; };
  auto fetch = [&]() {
    const int item = wg + 3 * lane, pr = pair_of(lane);
    const uint32_t bar = warp ? BAR_Y(sb, item) : BAR_FULL(sb, item);
    mbar_expect_tx(bar, 16384);
    wait_counter(warp ? &p.s->cnt_w[0] : &p.s->cnt_x1[(pr < 112 ? pr >> 4 : 0) * 32], epoch * (warp ? NSPEC : 16));
    if (warp) fence_async();
    bulk_g2s(sb + (warp ? SP_W : SP_Z) + item * 16384, (warp ? p.s->wt : p.s->x1t) + pr * 1024, 16384, bar);
  };
  if (lane < nrnd && warp == 0) fetch();
  __syncwarp();
  fence_regs(fe); fence_regs(tw);
  mbar_wait(BAR_Y(sb, 6), 0);
  TL(3);
  const uint64_t dT_n = mk_desc(sb + SP_T, 8192, 1024, 1);
#pragma unroll 1
  for (int rnd = 0; rnd < nrnd; rnd++) {
    const int item = wg + 3 * rnd, pr = pair_of(rnd);
    const uint32_t z = sb + SP_Z + item * 16384;
    uint32_t fa[16], fb[16];
    auto load_frag = [&](int off) {
#pragma unroll
      for (int i = 0; i < 4; i++) {
        const uint4 a = *reinterpret_cast<const uint4*>(smem + SP_TW + off + i * 2048 + tid * 16);
        fa[4 * i] = a.x; fa[4 * i + 1] = a.y; fa[4 * i + 2] = a.z; fa[4 * i + 3] = a.w;
      }
      fence_regs(fa);
    };
    load_frag(0);
    {
      const uint32_t live = pr == 0 ? 0xddu : (pr == 112 ? 0x11u : 0xffu);
#pragma unroll 1
      for (uint32_t n = 0; n < 4096; n++) {
        mbar_wait(BAR_FULL(sb, item), n & 1);
        uint32_t bad = 0;
#pragma unroll
        for (int i = 0; i < 8; i++) bad |= ((*reinterpret_cast<const volatile uint32_t*>(smem + SP_Z + item * 16384 + i * 2048 + tid * 16) ^ epoch) & 1) << i;
        uint32_t again;
        asm volatile("{\n.reg .pred p, q;\nsetp.ne.u32 p, %1, 0;\nbarrier.red.or.pred q, %2, 128, p;\nselp.u32 %0, 1, 0, q;\n}"
                     : "=r"(again) : "r"(bad & live), "r"(1 + wg) : "memory");
        if (!again) break;
        TL(20);
        if (tid == 0) { mbar_expect_tx(BAR_FULL(sb, item), 16384); bulk_g2s(z, p.s->x1t + pr * 1024, 16384, BAR_FULL(sb, item)); }
      }
    }
    TL(4 + 8 * rnd);
    if (rnd == 0 && wg > 0) bar_sync(3 + wg, 256);
    float aR[32], aI[32];
    {
      const uint64_t de = mk_desc(z, 4096, 512, 2);
      wg_fence();
#pragma unroll
      for (int kk = 0; kk < 4; kk++) {
        wgmma_rs_n64<1, 1>(aR, fe[4 * kk], fe[4 * kk + 1], fe[4 * kk + 2], fe[4 * kk + 3], de + kk * 64, kk != 0);
        wgmma_rs_n64<1, 1>(aI, fa[4 * kk], fa[4 * kk + 1], fa[4 * kk + 2], fa[4 * kk + 3], de + 512 + kk * 64, kk != 0);
      }
      wg_commit();
      if (rnd == 0 && wg < 2) bar_arrive(4 + wg, 256);
      if (rnd == 0 && lane < nrnd && warp == 1) fetch();
      __syncwarp();
      wg_wait<0>();
      fence_regs(aR); fence_regs(aI);
    }
    TL(5 + 8 * rnd);
#pragma unroll
    for (int v = 0; v < 8; v++) {
      uint32_t* f = (v < 4 ? fa : fb) + 2 * (v & 3);
      const uint32_t* t = tw + 2 * (v & 3);
      const float *e = aR + 4 * v, *o = aI + 4 * v;
      const uint32_t er = pack2(e[0], e[1]), ei = pack2(e[2], e[3]), qr = pack2(o[0], o[1]), qi = pack2(o[2], o[3]);
      const uint32_t u0r = add2(er, qr), u0i = add2(ei, qi), u1r = sub2(er, qr), u1i = sub2(ei, qi);
      f[0] = fma2(u0r, t[0], mul2(u0i, t[8]));
      f[8] = fms2(u0i, t[0], mul2(u0r, t[8]));
      f[1] = fma2(u1r, t[1], mul2(u1i, t[9]));
      f[9] = fms2(u1i, t[1], mul2(u1r, t[9]));
    }
    fence_regs(fa); fence_regs(fb);
    wg_fence();
#pragma unroll
    for (int kk = 0; kk < 4; kk++) {
      wgmma_rs_n64<1, 1>(aR, fa[4 * kk], fa[4 * kk + 1], fa[4 * kk + 2], fa[4 * kk + 3], dT_n + kk * 128, kk != 0);
      wgmma_rs_n64<1, 1>(aI, fb[4 * kk], fb[4 * kk + 1], fb[4 * kk + 2], fb[4 * kk + 3], dT_n + kk * 128, kk != 0);
    }
    wg_commit();
    if (rnd == 1 && tid == 0) {
      asm volatile("cp.async.bulk.wait_group 0;" ::: "memory");
      red_add(&p.s->cnt_y[(max(pr - 57, 0) >> 4) * 32], 1);
    }
    __syncwarp();
    mbar_wait(BAR_Y(sb, item), 0);
    wg_wait<0>();
    fence_regs(aR); fence_regs(aI);
    TL(6 + 8 * rnd);
    {
      const uint8_t* wp = smem + SP_W + item * 16384 + q * 1024 + warp * 128 + (((lane >> 2) ^ (2 * q)) << 4);
#pragma unroll
      for (int jb = 0; jb < 4; jb++) {
#pragma unroll
        for (int h = 0; h < 2; h++) {
          const uint4 w = *reinterpret_cast<const uint4*>(wp + jb * 4096 + h * 512);
          const int i = 4 * jb + 2 * h;
          const uint32_t ar = pack2(aR[i], aR[i + 1]), ai = pack2(aR[16 + i], aR[17 + i]);
          const uint32_t br = pack2(aI[i], aI[i + 1]), bi = pack2(aI[16 + i], aI[17 + i]);
          fa[2 * jb + h] = fms2(ar, w.x, mul2(ai, w.y));
          fa[8 + 2 * jb + h] = fma2(ar, w.y, mul2(ai, w.x));
          fb[2 * jb + h] = fms2(br, w.z, mul2(bi, w.w));
          fb[8 + 2 * jb + h] = fma2(br, w.w, mul2(bi, w.z));
        }
      }
    }
    fence_regs(fa); fence_regs(fb);
    wg_fence();
#pragma unroll
    for (int kk = 0; kk < 4; kk++) {
      wgmma_rs_n64<1, 0>(aR, fa[4 * kk], fa[4 * kk + 1], fa[4 * kk + 2], fa[4 * kk + 3], dT_n + kk * 2, kk != 0);
      wgmma_rs_n64<1, 0>(aI, fb[4 * kk], fb[4 * kk + 1], fb[4 * kk + 2], fb[4 * kk + 3], dT_n + kk * 2, kk != 0);
    }
    wg_commit();
    wg_wait<0>();
    fence_regs(aR); fence_regs(aI);
    TL(7 + 8 * rnd);
#pragma unroll
    for (int v = 0; v < 8; v++) {
      const float* a = (v < 4 ? aR : aI) + 4 * (v & 3);
      const uint32_t* t = tw + 2 * (v & 3);
      const uint32_t u0r = pack2(a[0], a[1]), u1r = pack2(a[2], a[3]), u0i = pack2(a[16], a[17]), u1i = pack2(a[18], a[19]);
      const uint32_t t0r = fms2(u0r, t[0], mul2(u0i, t[8])), t0i = fma2(u0i, t[0], mul2(u0r, t[8]));
      const uint32_t t1r = fms2(u1r, t[1], mul2(u1i, t[9])), t1i = fma2(u1i, t[1], mul2(u1r, t[9]));
      fa[v] = add2(t0i, t1i); fa[8 + v] = add2(t0r, t1r);
      fb[v] = sub2(t0i, t1i); fb[8 + v] = sub2(t0r, t1r);
    }
    bar_sync(1 + wg, 128);
#pragma unroll
    for (int u = 0; u < 4; u++) {
      const uint32_t a = z + (32 * (u >> 1) + 8 * warp + (lane & 7)) * 128 + (((4 * (u & 1) + (lane >> 3)) ^ (lane & 7)) << 4);
      stmatrix_x4(a, fa[4 * u], fa[4 * u + 1], fa[4 * u + 2], fa[4 * u + 3]);
      stmatrix_x4(a + 8192, fb[4 * u], fb[4 * u + 1], fb[4 * u + 2], fb[4 * u + 3]);
    }
    load_frag(8192);
    fence_async_smem();
    bar_sync(1 + wg, 128);
    TL(8 + 8 * rnd);
    {
      const uint64_t de = mk_desc(z, 8192, 1024, 1);
      wg_fence();
#pragma unroll
      for (int kk = 0; kk < 4; kk++) {
        wgmma_rs_n64<1, 1>(aR, fe[4 * kk], fe[4 * kk + 1], fe[4 * kk + 2], fe[4 * kk + 3], de + kk * 128, kk != 0);
        wgmma_rs_n64<1, 1>(aI, fa[4 * kk], fa[4 * kk + 1], fa[4 * kk + 2], fa[4 * kk + 3], de + 512 + kk * 128, kk != 0);
      }
      wg_commit();
      wg_wait<0>();
      fence_regs(aR); fence_regs(aI);
    }
    TL(9 + 8 * rnd);
    const bool edge = pr == 0 || pr == 112;
    if (edge) {
#pragma unroll
      for (int i = 0; i < 16; i++) { aR[i] *= 0.5f; aI[i] *= 0.5f; }
    }
#pragma unroll
    for (int i = 0; i < 8; i++) {
      const float* a = ((i & 1) ? aI : aR) + 16 * (i >> 2) + 2 - (i & 2);
      *reinterpret_cast<uint4*>(smem + SP_W + item * 16384 + (i >> 1) * 4096 + (i & 1) * 64 + (tid >> 2) * 128 + q * 16) =
          make_uint4(pack2(a[0], a[1]), pack2(a[4], a[5]), pack2(a[8], a[9]), pack2(a[12], a[13]));
    }
    fence_async_smem();
    bar_sync(1 + wg, 128);
    if (tid == 0) {
      const uint32_t src = sb + SP_W + item * 16384;
      __nv_bfloat16* dst = p.s->yt + (size_t)(pr < 112 ? 4 * pr : 1) * S_;
      bulk_s2g(dst, src, edge ? 4096 : 16384);
      if (pr == 0) bulk_s2g(dst + 2 * S_, src + 8192, 8192);
      asm volatile("cp.async.bulk.commit_group;" ::: "memory");
      if (rnd == nrnd - 1) {
        asm volatile("cp.async.bulk.wait_group 0;" ::: "memory");
        TL(11);
        red_add(&p.s->cnt_y[(pr < 112 ? pr >> 4 : 0) * 32], 1);
      }
    }
    __syncwarp();
    TL(10 + 8 * rnd);
  }
  if (lane == 0) *my_epoch = epoch;
}

__global__ void __cluster_dims__(2, 1, 1) __launch_bounds__(384, 1)
fused_kernel(const __grid_constant__ Params p) {
  extern __shared__ __align__(1024) uint8_t smem[];
  const uint32_t sb = smem_u32(smem);
  TL(0);
  const uint32_t rank = blockIdx.x & 1;
  const int hc = blockIdx.x >> 1;
  int grp, jj;
  if (hc < 4) { grp = 8; jj = hc; }
  else if (hc < 36) { grp = (hc - 4) & 7; jj = (hc - 4) >> 3; }
  else if (hc < 57) { jj = (hc - 36) / 7; grp = 1 + (hc - 36) - 7 * jj; jj += 4; }
  else if (hc < 60) { grp = 0; jj = hc - 53; }
  else { grp = 8; jj = hc - 56; }
  const int mt = 2 * grp + rank, bid = 2 * (7 * grp + jj) + rank;
  if (bid < NFFN) {
    const int t = threadIdx.x;
    if (t < 19 && 19 * jj + t < 128) asm volatile("prefetch.global.L2 [%0];" ::"l"(p.px + (128 * mt + 19 * jj + t) * D_));
    if (t >= 128 && t < 136) asm volatile("prefetch.global.L2 [%0];" ::"l"((rank ? p.pwu : p.pwg) + (4 * grp + (t & 3)) * F_ + 256 * jj + 16 * (t & 4)));
  }
  if (threadIdx.x == 256) {
#pragma unroll
    for (int i = 0; i < NSTAGE; i++) { mbar_init(BAR_FULL(sb, i), 1); mbar_init(BAR_EMPTY(sb, i), 4); }
    asm volatile("fence.mbarrier_init.release.cluster;" ::: "memory");
  } else if (threadIdx.x == 320) {
    mbar_init(BAR_X(sb, 0), 1);
    if (bid < NFFN) {
      mbar_expect_tx(BAR_X(sb, 0), 16384);
      tma2d(sb + SM_X, &p.x, 0, 128 * mt, BAR_X(sb, 0));
    }
#pragma unroll
    for (int i = 1; i < NSTAGE; i++) mbar_init(BAR_X(sb, i), 1);
    mbar_init(BAR_XFREE(sb), 2);
    asm volatile("fence.mbarrier_init.release.cluster;" ::: "memory");
  } else if (threadIdx.x == 352) {
#pragma unroll
    for (int i = 0; i < NSTAGE; i++) { mbar_init(BAR_Y(sb, i), 1); mbar_init(BAR_E2(sb, i), 2); }
    asm volatile("fence.mbarrier_init.release.cluster;" ::: "memory");
  } else if (threadIdx.x == 288 && bid < NFFN) {
    prefetch_tmap(rank ? &p.wu : &p.wg); prefetch_tmap(&p.ct);
  }
  __syncwarp();
  asm volatile("barrier.cluster.arrive.relaxed.aligned;" ::: "memory");
  const int wg = __shfl_sync(0xffffffffu, threadIdx.x >> 7, 0);
  if (bid >= NFFN) {
    spectral_cta(sb, smem, p, bid - NFFN, wg);
  } else if (wg < 2) {
    asm volatile("setmaxnreg.inc.sync.aligned.u32 232;");
    asm volatile("barrier.cluster.wait.acquire.aligned;" ::: "memory");
    TL(1);
    ffn_consumer(sb, smem, p, bid, wg, threadIdx.x & 127, mt, jj);
  } else {
    asm volatile("setmaxnreg.dec.sync.aligned.u32 40;");
    asm volatile("barrier.cluster.wait.acquire.aligned;" ::: "memory");
    TL(1);
    if (threadIdx.x == 320) {
      constexpr int order[13] = {XORDER};
#pragma unroll
      for (int i = 0; i < 13; i++) {
        if (order[i] < 8) {
          ring_issue(sb, p, order[i], order[i], false, 0, jj, rank);
        } else {
          const int kb = order[i] - 10;
          mbar_expect_tx(BAR_X(sb, kb), 16384);
          tma2d(sb + SM_X + kb * 16384, &p.x, 64 * kb, 128 * mt, BAR_X(sb, kb));
        }
      }
      TL(2);
    }
    __syncwarp();
    ffn_producer(sb, smem, bid, p, (threadIdx.x >> 5) & 3, threadIdx.x & 31, mt, jj, rank);
  }
}

typedef CUresult (*EncodeFn)(CUtensorMap*, CUtensorMapDataType, cuuint32_t, void*, const cuuint64_t*, const cuuint64_t*,
                             const cuuint32_t*, const cuuint32_t*, CUtensorMapInterleave, CUtensorMapSwizzle,
                             CUtensorMapL2promotion, CUtensorMapFloatOOBfill);

void make_map(EncodeFn fn, CUtensorMap* m, const void* base, int rank, const cuuint64_t* dims, const cuuint64_t* strides,
              const cuuint32_t* box, CUtensorMapSwizzle sw) {
  const cuuint32_t es[4] = {1, 1, 1, 1};
  fn(m, CU_TENSOR_MAP_DATA_TYPE_BFLOAT16, rank, const_cast<void*>(base), dims, strides, box, es,
     CU_TENSOR_MAP_INTERLEAVE_NONE, sw, CU_TENSOR_MAP_L2_PROMOTION_L2_256B, CU_TENSOR_MAP_FLOAT_OOB_FILL_NONE);
}

}

extern "C" void kernel_launch(void* const* d_in, const int* in_sizes, int n_in, void* d_out, int out_size) {
  const __nv_bfloat16* x = (const __nv_bfloat16*)d_in[0];
  const __nv_bfloat16* w_r = (const __nv_bfloat16*)d_in[1];
  const __nv_bfloat16* w_i = (const __nv_bfloat16*)d_in[2];
  const __nv_bfloat16* wg = (const __nv_bfloat16*)d_in[4];
  const __nv_bfloat16* wu = (const __nv_bfloat16*)d_in[5];
  const __nv_bfloat16* wd = (const __nv_bfloat16*)d_in[6];
  const __nv_bfloat16* gate_w = (const __nv_bfloat16*)d_in[7];

  void* fnp = nullptr;
  cudaDriverEntryPointQueryResult qr;
  cudaGetDriverEntryPoint("cuTensorMapEncodeTiled", &fnp, cudaEnableDefault, &qr);
  EncodeFn fn = (EncodeFn)fnp;
  void *ctab, *spec, *scr;
  cudaGetSymbolAddress(&ctab, g_ctab);
  cudaGetSymbolAddress(&spec, g_spec);
  cudaGetSymbolAddress(&scr, g_scratch);
  const void* yt = (const char*)scr + offsetof(Scratch, yt);
  Params p;
  p.s = (Scratch*)scr; p.out = (__nv_bfloat16*)d_out;
  p.px = x; p.w_r = w_r; p.w_i = w_i; p.gate_w = gate_w; p.pwg = wg; p.pwu = wu; p.pwd = wd;
  p.ctab = (const tab::Table*)ctab; p.spec = (const tab::Spec*)spec;
  {
    const cuuint64_t d[2] = {D_, S_}, s[1] = {D_ * 2};
    const cuuint32_t b[2] = {64, 128};
    make_map(fn, &p.x, x, 2, d, s, b, CU_TENSOR_MAP_SWIZZLE_128B);
  }
  {
    const cuuint64_t d[3] = {64, D_, F_ / 64}, s[2] = {F_ * 2, 128};
    const cuuint32_t b[3] = {64, 32, 2};
    make_map(fn, &p.wg, wg, 3, d, s, b, CU_TENSOR_MAP_SWIZZLE_128B);
    make_map(fn, &p.wu, wu, 3, d, s, b, CU_TENSOR_MAP_SWIZZLE_128B);
  }
  {
    const cuuint64_t d[2] = {D_, F_}, s[1] = {D_ * 2};
    const cuuint32_t b[2] = {64, 64};
    make_map(fn, &p.wd, wd, 2, d, s, b, CU_TENSOR_MAP_SWIZZLE_128B);
  }
  {
    const cuuint64_t d[2] = {D_, D_}, s[1] = {D_ * 2};
    const cuuint32_t b[2] = {64, 64};
    make_map(fn, &p.ct, ctab, 2, d, s, b, CU_TENSOR_MAP_SWIZZLE_128B);
  }
  {
    const cuuint64_t d[3] = {64, D_, S_ / 64}, s[2] = {S_ * 2, 128};
    const cuuint32_t b[3] = {64, 64, 2};
    make_map(fn, &p.yt, yt, 3, d, s, b, CU_TENSOR_MAP_SWIZZLE_128B);
  }
  cudaFuncSetAttribute(fused_kernel, cudaFuncAttributeMaxDynamicSharedMemorySize, SM_TOTAL);
  fused_kernel<<<NCTA, 384, SM_TOTAL, cudaStreamPerThread>>>(p, x, w_r, w_i, gate_w, wd, (__nv_bfloat16*)d_out);
}
```

```cpp
#include <cuda_runtime.h>
#include <cuda_bf16.h>
#include <cuda.h>
#include <stdint.h>
#include <stddef.h>

namespace {

constexpr int S_ = 2048, D_ = 448, F_ = 1792, DF_ = 225;
constexpr int NFFN = 112, NSPEC = 20, NCTA = NFFN + NSPEC;
constexpr int NSTAGE = 7, STAGE_BYTES = 16384;
constexpr int SM_X = 0, SM_RING = 114688, SM_BAR = 229376, SM_TOTAL = SM_BAR + 512;
constexpr int SP_Z = 0, SP_W = 98304, SP_TW = 198656, SP_T = 215040, SLAB_BYTES = 16 * DF_ * 2;
constexpr uint32_t SPIN_LIMIT = 1u << 20;

namespace tab {
constexpr double PI = 3.14159265358979323846264338327950288;
constexpr double csin(double x) {
  double t = x, s = x;
  for (int i = 1; i < 20; i++) { t = -t * x * x / ((2 * i) * (2 * i + 1)); s += t; }
  return s;
}
constexpr double ccos(double x) {
  double t = 1, s = 1;
  for (int i = 1; i < 20; i++) { t = -t * x * x / ((2 * i - 1) * (2 * i)); s += t; }
  return s;
}
constexpr uint32_t to_bf16(double v) {
  uint32_t sign = v < 0 ? 0x8000u : 0u;
  double a = v < 0 ? -v : v;
  if (a < 1e-12) return 0;
  int e = 0;
  while (a >= 2.0) { a /= 2; e++; }
  while (a < 1.0) { a *= 2; e--; }
  double m = a * 128.0;
  int mi = (int)m;
  double fr = m - mi;
  if (fr > 0.5 || (fr == 0.5 && (mi & 1))) mi++;
  if (mi == 256) { mi = 128; e++; }
  return sign | (uint32_t)((e + 127) << 7) | (uint32_t)(mi - 128);
}
struct Base { uint32_t v[448]; };
constexpr Base make_base() {
  Base b{};
  for (int m = 0; m < 448; m++) {
    int mm = m > 224 ? m - 448 : m;
    double ang = 2 * PI * mm / 448.0;
    b.v[m] = to_bf16(ccos(ang)) | (to_bf16(-csin(ang)) << 16);
  }
  return b;
}
constexpr Base base = make_base();
struct Row { uint32_t v[224]; };
constexpr Row make_row(int d) {
  Row r{};
  r.v[0] = 0x3f80u | ((d & 1) ? 0xbf800000u : 0x3f800000u);
  int m = 0;
  for (int c = 1; c < 224; c++) { m += d; if (m >= 448) m -= 448; r.v[c] = base.v[m]; }
  return r;
}
struct Table { Row r[448]; };
constexpr Table make_table() {
  Table t{};
  for (int d = 0; d < 448; d++) t.r[d] = make_row(d);
  return t;
}
struct Cs { double c[2048], s[2048]; };
constexpr Cs make_cs() {
  Cs t{};
  for (int m = 0; m <= 256; m++) {
    const double a = 2 * PI * m / 2048.0, c = ccos(a), s = csin(a);
    t.c[m] = c; t.s[m] = s;
    t.c[512 - m] = s; t.s[512 - m] = c;
  }
  for (int m = 513; m < 2048; m++) { t.c[m] = -t.s[m - 512]; t.s[m] = t.c[m - 512]; }
  return t;
}
constexpr Cs cs = make_cs();
struct Spec {
  uint32_t fo[2048], fot[2048];
  uint16_t t32[4096];
  uint32_t fe[2048];
  uint32_t tw[2048];
};
constexpr uint32_t blk(int h, int c, int a) { return to_bf16(h == c ? cs.c[a & 2047] : (h ? -cs.s[a & 2047] : cs.s[a & 2047])); }
constexpr Spec make_spec() {
  Spec t{};
  for (int row = 0; row < 64; row++)
    for (int col = 0; col < 64; col++) {
      const int c = row & 31, k2 = col & 31, n2 = 8 * ((c >> 1) & 3) + 2 * (c >> 3) + (c & 1), m = 64 * ((n2 * k2) & 31);
      const double v = (row >> 5) == (col >> 5) ? cs.c[m] : (row < 32 ? -cs.s[m] : cs.s[m]);
      t.t32[row * 64 + (((col >> 3) ^ (row & 7)) << 3) + (col & 7)] = (uint16_t)to_bf16(v);
    }
  for (int th = 0; th < 128; th++)
    for (int i = 0; i < 16; i++) {
      const int r = 8 * (th >> 5) + ((th & 31) >> 2), h = i & 1, c = i >> 3, m = 8 * ((i >> 1) & 3) + 2 * (th & 3);
      const int o = ((i >> 2) * 128 + th) * 4 + (i & 3);
      t.fe[o] = blk(h, c, 64 * m * r) | (blk(h, c, 64 * (m + 1) * r) << 16);
      t.fo[o] = blk(h, c, 32 * (2 * m + 1) * r) | (blk(h, c, 32 * (2 * m + 3) * r) << 16);
      t.fot[o] = blk(h, c, 32 * (2 * r + 1) * m) | (blk(h, c, 32 * (2 * r + 1) * (m + 1)) << 16);
      const int k1 = r + 32 * h, n2 = 8 * (th & 3) + 2 * ((i >> 1) & 3);
      t.tw[o] = blk(0, c, n2 * k1) | (blk(0, c, (n2 + 1) * k1) << 16);
    }
  return t;
}
}
}

__device__ __align__(1024) const tab::Table g_ctab = tab::make_table();
__device__ __align__(1024) const tab::Spec g_spec = tab::make_spec();

struct Scratch {
  uint32_t cnt_w[32];
  uint32_t cnt_x1[7 * 32];
  uint32_t cnt_y[7 * 32];
  uint32_t epoch[NCTA * 12 + 240 + 256];
  uint32_t gate[S_];
  uint4 x1t[113 * 1024];
  __nv_bfloat16 yt[D_ * S_];
  uint4 wt[114 * 1024];
  uint4 part[16 * 7 * 6 * 2 * 4 * 128];
};
static_assert(offsetof(Scratch, x1t) % 1024 == 0, "alignment");
__device__ __align__(1024) Scratch g_scratch;
#define TL(i)

namespace {

struct Params {
  Scratch* s;
  __nv_bfloat16* out;
  const __nv_bfloat16 *px, *w_r, *w_i, *gate_w, *pwg, *pwu, *pwd;
  const tab::Table* ctab;
  const tab::Spec* spec;
  CUtensorMap x, wg, wu, wd, ct, yt;
};

__device__ __forceinline__ uint32_t smem_u32(const void* p) { return (uint32_t)__cvta_generic_to_shared(p); }
__device__ __forceinline__ void mbar_init(uint32_t bar, uint32_t cnt) {
  asm volatile("mbarrier.init.shared::cta.b64 [%0], %1;" ::"r"(bar), "r"(cnt) : "memory");
}
__device__ __forceinline__ void mbar_expect_tx(uint32_t bar, uint32_t bytes) {
  asm volatile("mbarrier.arrive.expect_tx.shared::cta.b64 _, [%0], %1;" ::"r"(bar), "r"(bytes) : "memory");
}
__device__ __forceinline__ void mbar_arrive(uint32_t bar) {
  asm volatile("mbarrier.arrive.shared::cta.b64 _, [%0];" ::"r"(bar) : "memory");
}
__device__ __forceinline__ void mbar_arrive_cluster(uint32_t bar, uint32_t cta) {
  asm volatile("{\n.reg .b32 ra;\nmapa.shared::cluster.u32 ra, %0, %1;\n"
               "mbarrier.arrive.shared::cluster.b64 _, [ra];\n}" ::"r"(bar), "r"(cta) : "memory");
}
__device__ __forceinline__ void mbar_wait(uint32_t bar, uint32_t parity) {
  uint32_t ok, n = 0;
  do {
    asm volatile("{\n.reg .pred p;\nmbarrier.try_wait.parity.shared::cta.b64 p, [%1], %2;\nselp.u32 %0, 1, 0, p;\n}"
                 : "=r"(ok) : "r"(bar), "r"(parity) : "memory");
  } while (!ok && ++n < SPIN_LIMIT);
}
__device__ __forceinline__ void mbar_wait_cluster(uint32_t bar, uint32_t parity) {
  uint32_t ok, n = 0;
  do {
    asm volatile("{\n.reg .pred p;\nmbarrier.try_wait.parity.acquire.cluster.shared::cta.b64 p, [%1], %2;\nselp.u32 %0, 1, 0, p;\n}"
                 : "=r"(ok) : "r"(bar), "r"(parity) : "memory");
  } while (!ok && ++n < SPIN_LIMIT);
}
__device__ __forceinline__ void tma2d(uint32_t dst, const CUtensorMap* m, int c0, int c1, uint32_t bar) {
  asm volatile("cp.async.bulk.tensor.2d.shared::cluster.global.mbarrier::complete_tx::bytes [%0], [%1, {%3, %4}], [%2];"
               ::"r"(dst), "l"(m), "r"(bar), "r"(c0), "r"(c1) : "memory");
}
__device__ __forceinline__ void tma3d(uint32_t dst, const CUtensorMap* m, int c0, int c1, int c2, uint32_t bar) {
  asm volatile("cp.async.bulk.tensor.3d.shared::cluster.global.mbarrier::complete_tx::bytes [%0], [%1, {%3, %4, %5}], [%2];"
               ::"r"(dst), "l"(m), "r"(bar), "r"(c0), "r"(c1), "r"(c2) : "memory");
}
__device__ __forceinline__ void tma2d_mc(uint32_t dst, const CUtensorMap* m, int c0, int c1, uint32_t bar) {
  asm volatile("cp.async.bulk.tensor.2d.shared::cluster.global.mbarrier::complete_tx::bytes.multicast::cluster [%0], [%1, {%3, %4}], [%2], %5;"
               ::"r"(dst), "l"(m), "r"(bar), "r"(c0), "r"(c1), "h"((uint16_t)3) : "memory");
}
__device__ __forceinline__ void tma3d_mc(uint32_t dst, const CUtensorMap* m, int c0, int c1, int c2, uint32_t bar) {
  asm volatile("cp.async.bulk.tensor.3d.shared::cluster.global.mbarrier::complete_tx::bytes.multicast::cluster [%0], [%1, {%3, %4, %5}], [%2], %6;"
               ::"r"(dst), "l"(m), "r"(bar), "r"(c0), "r"(c1), "r"(c2), "h"((uint16_t)3) : "memory");
}
__device__ __forceinline__ void bulk_g2s(uint32_t dst, const void* src, uint32_t bytes, uint32_t bar) {
  asm volatile("cp.async.bulk.shared::cluster.global.mbarrier::complete_tx::bytes [%0], [%1], %2, [%3];"
               ::"r"(dst), "l"(src), "r"(bytes), "r"(bar) : "memory");
}
__device__ __forceinline__ void bulk_s2g(void* dst, uint32_t src, uint32_t bytes) {
  asm volatile("cp.async.bulk.global.shared::cta.bulk_group [%0], [%1], %2;" ::"l"(dst), "r"(src), "r"(bytes) : "memory");
}
__device__ __forceinline__ void prefetch_tmap(const CUtensorMap* m) {
  asm volatile("prefetch.tensormap [%0];" ::"l"(m) : "memory");
}
__device__ __forceinline__ void l2_prefetch(const void* p, uint32_t bytes) {
  asm volatile("cp.async.bulk.prefetch.L2.global [%0], %1;" ::"l"(p), "r"(bytes) : "memory");
}
__device__ __forceinline__ void wg_fence() { asm volatile("wgmma.fence.sync.aligned;" ::: "memory"); }
__device__ __forceinline__ void wg_commit() { asm volatile("wgmma.commit_group.sync.aligned;" ::: "memory"); }
template <int N> __device__ __forceinline__ void wg_wait() { asm volatile("wgmma.wait_group.sync.aligned %0;" ::"n"(N) : "memory"); }
template <int N> __device__ __forceinline__ void fence_regs(float (&d)[N]) {
#pragma unroll
  for (int i = 0; i < N; i++) asm volatile("" : "+f"(d[i])::"memory");
}
template <int N> __device__ __forceinline__ void fence_regs(uint32_t (&d)[N]) {
#pragma unroll
  for (int i = 0; i < N; i++) asm volatile("" : "+r"(d[i])::"memory");
}
__device__ __forceinline__ void bar_sync(int id, int n) { asm volatile("bar.sync %0, %1;" ::"r"(id), "r"(n) : "memory"); }
__device__ __forceinline__ void bar_arrive(int id, int n) { asm volatile("bar.arrive %0, %1;" ::"r"(id), "r"(n) : "memory"); }
__device__ __forceinline__ void fence_gpu() { asm volatile("fence.acq_rel.gpu;" ::: "memory"); }
__device__ __forceinline__ void fence_async() { asm volatile("fence.proxy.async;" ::: "memory"); }
__device__ __forceinline__ void fence_async_smem() { asm volatile("fence.proxy.async.shared::cta;" ::: "memory"); }
__device__ __forceinline__ void red_add(uint32_t* p, uint32_t v) {
  asm volatile("red.relaxed.gpu.global.add.u32 [%0], %1;" ::"l"(p), "r"(v) : "memory");
}
__device__ __forceinline__ uint32_t ld_relaxed(const uint32_t* p) {
  uint32_t v;
  asm volatile("ld.relaxed.gpu.global.u32 %0, [%1];" : "=r"(v) : "l"(p) : "memory");
  return v;
}
__device__ __forceinline__ void wait_counter(const uint32_t* p, uint32_t target) {
  uint32_t v, n = 0;
  while (true) {
    asm volatile("ld.acquire.gpu.global.u32 %0, [%1];" : "=r"(v) : "l"(p) : "memory");
    if ((int32_t)(v - target) >= 0 || ++n > SPIN_LIMIT) break;
  }
}
__device__ __forceinline__ uint4 ld_relaxed(const uint4* p) {
  uint4 v;
  asm volatile("ld.relaxed.gpu.global.v4.u32 {%0, %1, %2, %3}, [%4];" : "=r"(v.x), "=r"(v.y), "=r"(v.z), "=r"(v.w) : "l"(p) : "memory");
  return v;
}
__device__ __forceinline__ void st_relaxed(uint4* p, uint4 v) {
  asm volatile("st.relaxed.gpu.global.v4.u32 [%0], {%1, %2, %3, %4};" ::"l"(p), "r"(v.x), "r"(v.y), "r"(v.z), "r"(v.w) : "memory");
}
__device__ __forceinline__ void st_relaxed(uint32_t* p, uint32_t v) {
  asm volatile("st.relaxed.gpu.global.u32 [%0], %1;" ::"l"(p), "r"(v) : "memory");
}
__device__ __forceinline__ uint32_t pack2(float lo, float hi) {
  uint32_t r;
  asm("cvt.rn.bf16x2.f32 %0, %1, %2;" : "=r"(r) : "f"(hi), "f"(lo));
  return r;
}
__device__ __forceinline__ uint32_t mul2(uint32_t a, uint32_t b) {
  uint32_t r;
  asm("mul.rn.bf16x2 %0, %1, %2;" : "=r"(r) : "r"(a), "r"(b));
  return r;
}
__device__ __forceinline__ uint32_t fma2(uint32_t a, uint32_t b, uint32_t c) {
  uint32_t r;
  asm("fma.rn.bf16x2 %0, %1, %2, %3;" : "=r"(r) : "r"(a), "r"(b), "r"(c));
  return r;
}
__device__ __forceinline__ uint32_t add2(uint32_t a, uint32_t b) {
  uint32_t r;
  asm("add.rn.bf16x2 %0, %1, %2;" : "=r"(r) : "r"(a), "r"(b));
  return r;
}
__device__ __forceinline__ uint32_t sub2(uint32_t a, uint32_t b) {
  uint32_t r;
  asm("sub.rn.bf16x2 %0, %1, %2;" : "=r"(r) : "r"(a), "r"(b));
  return r;
}
__device__ __forceinline__ uint32_t fms2(uint32_t a, uint32_t b, uint32_t c) {
  uint32_t r;
  asm("{\n.reg .b32 n;\nneg.bf16x2 n, %3;\nfma.rn.bf16x2 %0, %1, %2, n;\n}" : "=r"(r) : "r"(a), "r"(b), "r"(c));
  return r;
}
__device__ __forceinline__ float bf_lo(uint32_t v) { return __uint_as_float(v << 16); }
__device__ __forceinline__ float bf_hi(uint32_t v) { return __uint_as_float(v & 0xffff0000u); }
__device__ __forceinline__ float bf_round(float v) { return bf_lo(pack2(v, 0.f)); }
__device__ __forceinline__ float tanh_fast(float v) {
  float r;
  asm("tanh.approx.f32 %0, %1;" : "=f"(r) : "f"(v));
  return r;
}
__device__ __forceinline__ uint64_t mk_desc(uint32_t addr, uint32_t lbo, uint32_t sbo, uint32_t mode) {
  return (uint64_t)((addr & 0x3FFFF) >> 4) | ((uint64_t)(lbo >> 4) << 16) | ((uint64_t)(sbo >> 4) << 32) | ((uint64_t)mode << 62);
}
__device__ __forceinline__ void stmatrix_x4(uint32_t addr, uint32_t r0, uint32_t r1, uint32_t r2, uint32_t r3) {
  asm volatile("stmatrix.sync.aligned.m8n8.x4.shared.b16 [%0], {%1, %2, %3, %4};" ::"r"(addr), "r"(r0), "r"(r1), "r"(r2), "r"(r3) : "memory");
}

template <int TA, int TB>
__device__ __forceinline__ void wgmma_ss_n256(float (&d)[128], uint64_t da, uint64_t db, int sd) {
  asm volatile("{\n.reg .pred p;\nsetp.ne.b32 p, %130, 0;\n"
      "wgmma.mma_async.sync.aligned.m64n256k16.f32.bf16.bf16 {"
      "%0, %1, %2, %3, %4, %5, %6, %7, %8, %9, %10, %11, %12, %13, %14, %15, %16, %17, %18, %19, %20, %21, %22, %23, "
      "%24, %25, %26, %27, %28, %29, %30, %31, %32, %33, %34, %35, %36, %37, %38, %39, %40, %41, %42, %43, %44, %45, "
      "%46, %47, %48, %49, %50, %51, %52, %53, %54, %55, %56, %57, %58, %59, %60, %61, %62, %63, %64, %65, %66, %67, "
      "%68, %69, %70, %71, %72, %73, %74, %75, %76, %77, %78, %79, %80, %81, %82, %83, %84, %85, %86, %87, %88, %89, "
      "%90, %91, %92, %93, %94, %95, %96, %97, %98, %99, %100, %101, %102, %103, %104, %105, %106, %107, %108, %109, "
      "%110, %111, %112, %113, %114, %115, %116, %117, %118, %119, %120, %121, %122, %123, %124, %125, %126, %127"
      "}, %128, %129, p, 1, 1, %131, %132;\n}\n"
      : "+f"(d[0]), "+f"(d[1]), "+f"(d[2]), "+f"(d[3]), "+f"(d[4]), "+f"(d[5]), "+f"(d[6]), "+f"(d[7]), "+f"(d[8]),
        "+f"(d[9]), "+f"(d[10]), "+f"(d[11]), "+f"(d[12]), "+f"(d[13]), "+f"(d[14]), "+f"(d[15]), "+f"(d[16]),
        "+f"(d[17]), "+f"(d[18]), "+f"(d[19]), "+f"(d[20]), "+f"(d[21]), "+f"(d[22]), "+f"(d[23]), "+f"(d[24]),
        "+f"(d[25]), "+f"(d[26]), "+f"(d[27]), "+f"(d[28]), "+f"(d[29]), "+f"(d[30]), "+f"(d[31]), "+f"(d[32]),
        "+f"(d[33]), "+f"(d[34]), "+f"(d[35]), "+f"(d[36]), "+f"(d[37]), "+f"(d[38]), "+f"(d[39]), "+f"(d[40]),
        "+f"(d[41]), "+f"(d[42]), "+f"(d[43]), "+f"(d[44]), "+f"(d[45]), "+f"(d[46]), "+f"(d[47]), "+f"(d[48]),
        "+f"(d[49]), "+f"(d[50]), "+f"(d[51]), "+f"(d[52]), "+f"(d[53]), "+f"(d[54]), "+f"(d[55]), "+f"(d[56]),
        "+f"(d[57]), "+f"(d[58]), "+f"(d[59]), "+f"(d[60]), "+f"(d[61]), "+f"(d[62]), "+f"(d[63]), "+f"(d[64]),
        "+f"(d[65]), "+f"(d[66]), "+f"(d[67]), "+f"(d[68]), "+f"(d[69]), "+f"(d[70]), "+f"(d[71]), "+f"(d[72]),
        "+f"(d[73]), "+f"(d[74]), "+f"(d[75]), "+f"(d[76]), "+f"(d[77]), "+f"(d[78]), "+f"(d[79]), "+f"(d[80]),
        "+f"(d[81]), "+f"(d[82]), "+f"(d[83]), "+f"(d[84]), "+f"(d[85]), "+f"(d[86]), "+f"(d[87]), "+f"(d[88]),
        "+f"(d[89]), "+f"(d[90]), "+f"(d[91]), "+f"(d[92]), "+f"(d[93]), "+f"(d[94]), "+f"(d[95]), "+f"(d[96]),
        "+f"(d[97]), "+f"(d[98]), "+f"(d[99]), "+f"(d[100]), "+f"(d[101]), "+f"(d[102]), "+f"(d[103]), "+f"(d[104]),
        "+f"(d[105]), "+f"(d[106]), "+f"(d[107]), "+f"(d[108]), "+f"(d[109]), "+f"(d[110]), "+f"(d[111]),
        "+f"(d[112]), "+f"(d[113]), "+f"(d[114]), "+f"(d[115]), "+f"(d[116]), "+f"(d[117]), "+f"(d[118]),
        "+f"(d[119]), "+f"(d[120]), "+f"(d[121]), "+f"(d[122]), "+f"(d[123]), "+f"(d[124]), "+f"(d[125]),
        "+f"(d[126]), "+f"(d[127])
      : "l"(da), "l"(db), "r"(sd), "n"(TA), "n"(TB));
}
template <int TA, int TB>
__device__ __forceinline__ void wgmma_ss_n128(float (&d)[64], uint64_t da, uint64_t db, int sd) {
  asm volatile("{\n.reg .pred p;\nsetp.ne.b32 p, %66, 0;\n"
      "wgmma.mma_async.sync.aligned.m64n128k16.f32.bf16.bf16 {"
      "%0, %1, %2, %3, %4, %5, %6, %7, %8, %9, %10, %11, %12, %13, %14, %15, %16, %17, %18, %19, %20, %21, %22, %23, "
      "%24, %25, %26, %27, %28, %29, %30, %31, %32, %33, %34, %35, %36, %37, %38, %39, %40, %41, %42, %43, %44, %45, "
      "%46, %47, %48, %49, %50, %51, %52, %53, %54, %55, %56, %57, %58, %59, %60, %61, %62, %63"
      "}, %64, %65, p, 1, 1, %67, %68;\n}\n"
      : "+f"(d[0]), "+f"(d[1]), "+f"(d[2]), "+f"(d[3]), "+f"(d[4]), "+f"(d[5]), "+f"(d[6]), "+f"(d[7]), "+f"(d[8]),
        "+f"(d[9]), "+f"(d[10]), "+f"(d[11]), "+f"(d[12]), "+f"(d[13]), "+f"(d[14]), "+f"(d[15]), "+f"(d[16]),
        "+f"(d[17]), "+f"(d[18]), "+f"(d[19]), "+f"(d[20]), "+f"(d[21]), "+f"(d[22]), "+f"(d[23]), "+f"(d[24]),
        "+f"(d[25]), "+f"(d[26]), "+f"(d[27]), "+f"(d[28]), "+f"(d[29]), "+f"(d[30]), "+f"(d[31]), "+f"(d[32]),
        "+f"(d[33]), "+f"(d[34]), "+f"(d[35]), "+f"(d[36]), "+f"(d[37]), "+f"(d[38]), "+f"(d[39]), "+f"(d[40]),
        "+f"(d[41]), "+f"(d[42]), "+f"(d[43]), "+f"(d[44]), "+f"(d[45]), "+f"(d[46]), "+f"(d[47]), "+f"(d[48]),
        "+f"(d[49]), "+f"(d[50]), "+f"(d[51]), "+f"(d[52]), "+f"(d[53]), "+f"(d[54]), "+f"(d[55]), "+f"(d[56]),
        "+f"(d[57]), "+f"(d[58]), "+f"(d[59]), "+f"(d[60]), "+f"(d[61]), "+f"(d[62]), "+f"(d[63])
      : "l"(da), "l"(db), "r"(sd), "n"(TA), "n"(TB));
}
template <int TA, int TB>
__device__ __forceinline__ void wgmma_ss_n64(float (&d)[32], uint64_t da, uint64_t db, int sd) {
  asm volatile("{\n.reg .pred p;\nsetp.ne.b32 p, %34, 0;\n"
      "wgmma.mma_async.sync.aligned.m64n64k16.f32.bf16.bf16 {"
      "%0, %1, %2, %3, %4, %5, %6, %7, %8, %9, %10, %11, %12, %13, %14, %15, %16, %17, %18, %19, %20, %21, %22, %23, "
      "%24, %25, %26, %27, %28, %29, %30, %31"
      "}, %32, %33, p, 1, 1, %35, %36;\n}\n"
      : "+f"(d[0]), "+f"(d[1]), "+f"(d[2]), "+f"(d[3]), "+f"(d[4]), "+f"(d[5]), "+f"(d[6]), "+f"(d[7]), "+f"(d[8]),
        "+f"(d[9]), "+f"(d[10]), "+f"(d[11]), "+f"(d[12]), "+f"(d[13]), "+f"(d[14]), "+f"(d[15]), "+f"(d[16]),
        "+f"(d[17]), "+f"(d[18]), "+f"(d[19]), "+f"(d[20]), "+f"(d[21]), "+f"(d[22]), "+f"(d[23]), "+f"(d[24]),
        "+f"(d[25]), "+f"(d[26]), "+f"(d[27]), "+f"(d[28]), "+f"(d[29]), "+f"(d[30]), "+f"(d[31])
      : "l"(da), "l"(db), "r"(sd), "n"(TA), "n"(TB));
}
template <int SA, int TB>
__device__ __forceinline__ void wgmma_rs_n64(float (&d)[32], uint32_t a0, uint32_t a1, uint32_t a2, uint32_t a3, uint64_t db, int sd) {
  asm volatile("{\n.reg .pred p;\nsetp.ne.b32 p, %37, 0;\n"
      "wgmma.mma_async.sync.aligned.m64n64k16.f32.bf16.bf16 {"
      "%0, %1, %2, %3, %4, %5, %6, %7, %8, %9, %10, %11, %12, %13, %14, %15, %16, %17, %18, %19, %20, %21, %22, %23, "
      "%24, %25, %26, %27, %28, %29, %30, %31"
      "}, {%32, %33, %34, %35}, %36, p, %38, 1, %39;\n}\n"
      : "+f"(d[0]), "+f"(d[1]), "+f"(d[2]), "+f"(d[3]), "+f"(d[4]), "+f"(d[5]), "+f"(d[6]), "+f"(d[7]), "+f"(d[8]),
        "+f"(d[9]), "+f"(d[10]), "+f"(d[11]), "+f"(d[12]), "+f"(d[13]), "+f"(d[14]), "+f"(d[15]), "+f"(d[16]),
        "+f"(d[17]), "+f"(d[18]), "+f"(d[19]), "+f"(d[20]), "+f"(d[21]), "+f"(d[22]), "+f"(d[23]), "+f"(d[24]),
        "+f"(d[25]), "+f"(d[26]), "+f"(d[27]), "+f"(d[28]), "+f"(d[29]), "+f"(d[30]), "+f"(d[31])
      : "r"(a0), "r"(a1), "r"(a2), "r"(a3), "l"(db), "r"(sd), "n"(SA), "n"(TB));
}

__device__ __forceinline__ uint32_t BAR_FULL(uint32_t sb, int i) { return sb + SM_BAR + 8 * i; }
__device__ __forceinline__ uint32_t BAR_EMPTY(uint32_t sb, int i) { return sb + SM_BAR + 64 + 8 * i; }
__device__ __forceinline__ uint32_t BAR_X(uint32_t sb, int i) { return sb + SM_BAR + 128 + 8 * i; }
__device__ __forceinline__ uint32_t BAR_Y(uint32_t sb, int i) { return sb + SM_BAR + 192 + 8 * i; }
__device__ __forceinline__ uint32_t BAR_XFREE(uint32_t sb) { return sb + SM_BAR + 256; }

__device__ __forceinline__ uint32_t BAR_E2(uint32_t sb, int i) { return sb + SM_BAR + 264 + 8 * i; }
#define CMASK 0xd4u
#define XORDER 0, 1, 11, 2, 3, 12, 13, 4, 5, 14, 6, 15, 16
#define XSPREAD 4
#define PFAT 3
#define SKEW 3
#define EQW 38
#define EQA 37
#define GL4 6
#define GS0 2
#define GL2 6
#define GS1 4
constexpr int Q_G1B = 18, Q_G2 = 32, Q_XR = 39, Q_P3 = 46, Q_END = 50;

__device__ __forceinline__ uint32_t y_addr(int kb) { return kb < 3 ? SM_RING + (kb + (Q_G2 + 4) % NSTAGE) * STAGE_BYTES : SM_X + (kb - 3) * 16384; }
static_assert((Q_G2 + 4) % NSTAGE + 2 < NSTAGE, "");

struct Ring {
  uint32_t slot, phase;
  __device__ __forceinline__ void next() { if (++slot == NSTAGE) { slot = 0; phase ^= 1; } }
};

__device__ __forceinline__ void release_slot(uint32_t sb, uint32_t slot, int tid, int times) {
  if (tid < 2 * times) mbar_arrive_cluster(BAR_EMPTY(sb, slot), tid & 1);
}

__device__ __forceinline__ void ffn_consumer(uint32_t sb, const uint8_t* smem, const Params& p, int bid, int wg, int tid, int mt, int jj) {
  const int lane = tid & 31, warp = tid >> 5, q = lane & 3, r0 = 16 * warp + (lane >> 2);
  uint32_t* const my_epoch = &p.s->epoch[blockIdx.x * 12 + (threadIdx.x >> 5)];
  const uint32_t epoch = ld_relaxed(my_epoch) + 1;
  Ring rg{0, 0};
  uint32_t u[64];
  float acc[128];
  uint32_t prev = 0, cmask = CMASK;
  int st = 0;
  auto g1_stage = [&](uint32_t slot, int s) {
    const uint64_t da = mk_desc(sb + SM_X + (s >> 1) * 16384 + wg * 8192 + (s & 1) * 64, 16, 1024, 1);
    const uint64_t db = mk_desc(sb + SM_RING + slot * STAGE_BYTES, 4096, 1024, 1);
    wg_fence();
    wgmma_ss_n256<0, 1>(acc, da, db, s != 0);
    wgmma_ss_n256<0, 1>(acc, da + 2, db + 128, 1);
    wg_commit();
  };
  if (wg == 1) {
    float ap[64];
    constexpr int QX = 32 - __builtin_clz(CMASK);
    constexpr int NPRE = QX + XSPREAD;
    uint4* const x1dst = p.s->x1t + ((64 * jj + r0 + 8) >> 2) * 1024 + (r0 & 3) * 128 + 8 * mt + (q ^ (mt & 3));
    const int x1lo = 64 * jj + r0 == 1 ? 110 * 1024 - 128 : -2048;
#pragma unroll
    for (int qi = 0; qi < NPRE; qi++) {
      const int slot = qi % NSTAGE, nc = __builtin_popcount(CMASK & ((1u << qi) - 1));
      if (qi == 0) TL(60);
      mbar_wait(BAR_FULL(sb, slot), (qi / NSTAGE) & 1);
      if (qi == 0) TL(61);
      if ((CMASK >> qi) & 1) {
#pragma unroll
        for (int kb = 2 * nc; kb < 2 * nc + 2 && kb < 7; kb++) {
          const uint64_t da = mk_desc(sb + SM_RING + slot * STAGE_BYTES + (kb & 1) * 8192, 8192, 1024, 1);
          const uint64_t db = mk_desc(sb + SM_X + kb * 16384, 16, 1024, 1);
          mbar_wait(BAR_X(sb, kb), 0);
          TL(16 + kb);
          wg_fence();
#pragma unroll
          for (int kk = 0; kk < 4; kk++) wgmma_ss_n128<1, 0>(ap, da + kk * 128, db + kk * 2, (kb | kk) != 0);
          wg_commit();
        }
      } else {
        if (((qi - nc) & 1) == 0 && qi - nc >= 4 * nc) mbar_wait(BAR_X(sb, (qi - nc) >> 1), 0);
        TL(32 + qi - nc);
        g1_stage(slot, qi - nc);
      }
      if (qi > 0) {
        wg_wait<1>();
        release_slot(sb, (qi - 1) % NSTAGE, tid, ((CMASK >> (qi - 1)) & 1) ? 2 : 1);
      }
      if (qi >= QX) {
        if (qi == QX) { fence_regs(ap); TL(2); }
#pragma unroll
        for (int t = (qi - QX) * (4 / XSPREAD); t < (qi - QX + 1) * (4 / XSPREAD); t++)
#pragma unroll
        for (int h = 0; h < 2; h++)
          x1dst[(h ? 0 : x1lo) + 512 * (t & 1) + 4 * (t >> 1)] = make_uint4((pack2(ap[16 * t + 2 * h], ap[16 * t + 2 * h + 1]) & ~1u) | (epoch & 1), pack2(ap[16 * t + 4 + 2 * h], ap[16 * t + 5 + 2 * h]),
                                             pack2(ap[16 * t + 8 + 2 * h], ap[16 * t + 9 + 2 * h]), pack2(ap[16 * t + 12 + 2 * h], ap[16 * t + 13 + 2 * h]));
      }
    }
    bar_arrive(7, 160);
    st = NPRE - 4; cmask = 0; prev = (NPRE - 1) % NSTAGE;
    rg.slot = NPRE % NSTAGE; rg.phase = (NPRE / NSTAGE) & 1;
  }
#pragma unroll 1
  for (int pass = 0; pass < 2; pass++) {
#pragma unroll 1
    for (; st < 14; st++) {
      while (cmask & 1) { cmask >>= 1; rg.next(); }
      cmask >>= 1;
      if (pass == 0 && (st & 1) == 0) mbar_wait(BAR_X(sb, st >> 1), 0);
      if (st == 14 - SKEW && wg == 1) bar_sync(9 + pass, 256);
      mbar_wait(BAR_FULL(sb, rg.slot), rg.phase);
      TL(32 + 14 * pass + st);
      g1_stage(rg.slot, st);
      wg_wait<1>();
      if (st > 0) release_slot(sb, prev, tid, 1);
      prev = rg.slot;
      rg.next();
    }
    st = 0;
    if (wg == 0) bar_arrive(9 + pass, 256);
    wg_wait<0>();
    fence_regs(acc);
    release_slot(sb, prev, tid, 1);
    TL(3 + 2 * pass);
#pragma unroll
    for (int i = 0; i < 32; i++) {
      const float g0 = 0.5f * acc[2 * i], g1 = 0.5f * acc[2 * i + 1];
      const float s0 = fmaf(g0, tanh_fast(g0), g0), s1 = fmaf(g1, tanh_fast(g1), g1);
      u[32 + i] = pack2(s0 * acc[64 + 2 * i], s1 * acc[64 + 2 * i + 1]);
    }
    if (pass == 0) {
#pragma unroll
      for (int i = 0; i < 32; i++) u[i] = u[32 + i];
    }
    TL(4 + 2 * pass);
  }
  fence_regs(u);
  float accA[32], accB[32];
  auto stage = [&](float (&acc)[32], int qi) {
    const int st = qi & 1;
    if (qi == EQW && wg == 0) bar_sync(1, 256);
    if (qi < Q_XR) mbar_wait(BAR_FULL(sb, qi % NSTAGE), (qi / NSTAGE) & 1);
    else mbar_wait(BAR_X(sb, qi - Q_XR), 1);
    const uint64_t db = mk_desc(sb + (qi < Q_XR ? SM_RING + (qi % NSTAGE) * STAGE_BYTES : SM_X + (qi - Q_XR) * 16384), 8192, 1024, 1);
    wg_fence();
#pragma unroll
    for (int kk = 0; kk < 8; kk++) {
      const uint32_t* a = u + 32 * st + 4 * kk;
      wgmma_rs_n64<1, 1>(acc, a[0], a[1], a[2], a[3], db + kk * 128, (st | kk) != 0);
    }
    wg_commit();
    if (qi == EQA && wg == 1) bar_arrive(1, 256);
  };
  auto retire = [&](int qi) {
    wg_wait<1>();
    if (qi >= Q_G2 && qi < Q_G2 + 4) release_slot(sb, qi % NSTAGE, tid, 1);
    else if (qi >= Q_G2 + 4 && qi < Q_G2 + 11 && tid == 0) mbar_arrive(BAR_E2(sb, qi - Q_G2 - 4));
  };
  const uint32_t par = epoch & 1;
  auto put = [&](float (&acc)[32], int c) {
    fence_regs(acc);
    int o = jj + 1 + c;
    if (o >= 7) o -= 7;
    uint4* dst = p.s->part + ((((mt * 7 + o) * 6 + c) * 2 + wg) * 4) * 128 + tid;
#pragma unroll
    for (int v = 0; v < 4; v++) {
      const float* a = acc + 8 * v;
      st_relaxed(dst + v * 128, make_uint4((pack2(a[0], a[1]) & ~1u) | par, pack2(a[2], a[3]), pack2(a[4], a[5]), pack2(a[6], a[7])));
    }
  };
  const uint4* const src = p.s->part + (((mt * 7 + jj) * 6 * 2 + wg) * 4) * 128 + tid;
  auto gload = [&](uint4 (&pv)[8], int c) {
#pragma unroll
    for (int i = 0; i < 8; i++) pv[i] = ld_relaxed(src + ((2 * c + (i >> 2)) * 8 + (i & 3)) * 128);
  };
  auto gload1 = [&](uint4 (&pv)[8], int c) {
#pragma unroll
    for (int i = 0; i < 4; i++) pv[4 * (c & 1) + i] = ld_relaxed(src + (c * 8 + i) * 128);
  };
  auto gsum = [&](uint4 (&pv)[8], int c) {
#pragma unroll 1
    for (uint32_t n = 0; n < SPIN_LIMIT; n++) {
      uint32_t bad = 0;
#pragma unroll
      for (int i = 0; i < 8; i++) bad |= pv[i].x ^ par;
      if (!__any_sync(0xffffffffu, bad & 1)) break;
      gload(pv, c);
    }
    TL(24 + c);
#pragma unroll
    for (int i = 0; i < 4; i++) {
      const uint32_t w[4] = {add2(pv[i].x, pv[4 + i].x), add2(pv[i].y, pv[4 + i].y), add2(pv[i].z, pv[4 + i].z), add2(pv[i].w, pv[4 + i].w)};
#pragma unroll
      for (int k = 0; k < 4; k++) { accA[8 * i + 2 * k] += bf_lo(w[k]); accA[8 * i + 2 * k + 1] += bf_hi(w[k]); }
    }
  };
  uint4 pv0[8], pv1[8], pv2[8];
  const int row = 128 * mt + 64 * wg + r0;
  uint32_t gt0, gt1;
#pragma unroll
  for (int c2 = 0; c2 < 4; c2++) {
    const int qi = Q_G2 + 4 * c2;
    stage(accA, qi);
    retire(qi - 1);
    stage(accA, qi + 1);
    if (c2 == 3) TL(27);
    if (c2 > 0) put(accB, 2 * c2 - 1);
    if (c2 == 2) gload1(pv0, 1);
    if (c2 == 3) gload1(pv1, 3);
    TL(7 + c2);
    if (c2 == 3) break;
    retire(qi);
    stage(accB, qi + 2);
    retire(qi + 1);
    stage(accB, qi + 3);
    put(accA, 2 * c2);
    if (c2 == 1) gload1(pv0, 0);
    if (c2 == 2) gload1(pv1, 2);
    if (c2 == 0) { gt0 = ld_relaxed(&p.s->gate[row]); gt1 = ld_relaxed(&p.s->gate[row + 8]); }
    retire(qi + 2);
  }
#pragma unroll
  for (int kb = 0; kb < 7; kb++) {
    const int qt = Q_XR + (kb >> 1);
    if ((kb & 1) == 0) mbar_wait(BAR_FULL(sb, qt % NSTAGE), (qt / NSTAGE) & 1);
    mbar_wait(BAR_Y(sb, kb), 0);
    const uint64_t da = mk_desc(sb + y_addr(kb) + wg * 8192, 8192, 1024, 1);
    const uint64_t db = mk_desc(sb + SM_RING + (qt % NSTAGE) * STAGE_BYTES + (kb & 1) * 8192, 16, 1024, 1);
    wg_fence();
#pragma unroll
    for (int kk = 0; kk < 4; kk++) wgmma_ss_n64<1, 0>(accB, da + kk * 128, db + kk * 2, (kb | kk) != 0);
    wg_commit();
    if (kb == 1) { wg_wait<2>(); fence_regs(accA); TL(15); }
    if (kb == GS0) gsum(pv0, 0);
    if (kb == GL4) gload1(pv2, 4);
    if (kb == GL2) gload1(pv2, 5);
    if (kb == GS1) gsum(pv1, 1);
  }
  TL(11);
  for (uint32_t n = 0; (((gt0 ^ epoch) | (gt1 ^ epoch)) & 0xffffu) && n < SPIN_LIMIT; n++) {
    gt0 = ld_relaxed(&p.s->gate[row]); gt1 = ld_relaxed(&p.s->gate[row + 8]);
  }
  gsum(pv2, 2);
  const float ga0 = bf_hi(gt0), ga1 = bf_hi(gt1);
  TL(12);
  wg_wait<0>();
  fence_regs(accB);
  TL(13);
  const float gb0 = bf_round(1.f - ga0), gb1 = bf_round(1.f - ga1);
  const float gs0 = ga0 * (2.f / (float)(S_ * D_)), gs1 = ga1 * (2.f / (float)(S_ * D_));
  uint4* const o = reinterpret_cast<uint4*>(p.out + (size_t)row * D_ + 64 * jj + 8 * q);
#pragma unroll
  for (int h = 0; h < 2; h++) {
    const float gs = h ? gs1 : gs0, gb = h ? gb1 : gb0;
#pragma unroll
    for (int k = 0; k < 2; k++) {
      uint32_t w[4];
#pragma unroll
      for (int j = 0; j < 4; j++) {
        const int i = 16 * k + 4 * j + 2 * h;
        w[j] = pack2(fmaf(gs, accB[i], gb * accA[i]), fmaf(gs, accB[i + 1], gb * accA[i + 1]));
      }
      const bool o1 = q & 1, o2 = q & 2;
      uint32_t a = __shfl_xor_sync(0xffffffffu, o1 ? w[0] : w[1], 1), b = __shfl_xor_sync(0xffffffffu, o1 ? w[2] : w[3], 1);
      if (o1) { w[0] = a; w[2] = b; } else { w[1] = a; w[3] = b; }
      a = __shfl_xor_sync(0xffffffffu, o2 ? w[0] : w[2], 2); b = __shfl_xor_sync(0xffffffffu, o2 ? w[1] : w[3], 2);
      if (o2) { w[0] = a; w[1] = b; } else { w[2] = a; w[3] = b; }
      o[h * D_ + 4 * k] = make_uint4(w[0], w[1], w[2], w[3]);
    }
  }
  if (lane == 0) *my_epoch = epoch;
  TL(14);
}

__device__ __forceinline__ void ring_issue(uint32_t sb, const Params& p, int qi, uint32_t slot, bool wait, uint32_t phase, int jj, uint32_t rank) {
  const CUtensorMap* m;
  int c0, c1, c2 = 0;
  bool half = false, is3d = false;
  if (qi < Q_G2) {
    const int nc = __popc(CMASK & ((1u << qi) - 1));
    if ((CMASK >> qi) & 1) {
      m = &p.ct; c0 = 64 * jj; c1 = 128 * nc + 64 * rank; half = nc == 3;
    } else {
      const int pass = qi >= Q_G1B;
      m = rank ? &p.wu : &p.wg; c0 = 0; c1 = 32 * (qi - nc - 14 * pass); c2 = 4 * jj + 2 * pass; is3d = true;
    }
  } else if (qi < Q_P3) {
    int o = jj + 1 + ((qi - Q_G2) >> 1);
    if (o >= 7) o -= 7;
    m = &p.wd; c0 = 64 * o; c1 = 256 * jj + 128 * (qi & 1) + 64 * rank;
  } else {
    m = &p.ct; c0 = 128 * (qi - Q_P3) + 64 * rank; c1 = 64 * jj; half = qi == Q_END - 1;
  }
  uint32_t bar = BAR_FULL(sb, slot), dst = sb + SM_RING + slot * STAGE_BYTES + rank * 8192;
  if (qi >= Q_XR && qi < Q_P3) {
    bar = BAR_X(sb, qi - Q_XR); dst = sb + SM_X + (qi - Q_XR) * 16384 + rank * 8192;
    if (qi == Q_XR) mbar_wait_cluster(BAR_XFREE(sb), 0);
  } else {
    if (wait) mbar_wait_cluster(BAR_EMPTY(sb, slot), phase ^ (qi >= Q_P3));
    mbar_expect_tx(bar, half ? 8192 : 16384);
  }
  if (is3d) tma3d_mc(dst, m, c0, c1, c2, bar);
  else if (!(half && rank)) tma2d_mc(dst, m, c0, c1, bar);
}

__device__ __forceinline__ void ffn_producer(uint32_t sb, const uint8_t* smem, int bid, const Params& p, int warp, int lane, int mt, int jj, uint32_t rank) {
  if (warp < 2) {
    if (lane == 0) {
      uint32_t slot = warp, phase = 0;
#pragma unroll 1
      for (int qi = NSTAGE + warp; qi < Q_END; qi += 2) {
        if (qi < Q_XR || qi >= Q_P3) ring_issue(sb, p, qi, slot, true, phase, jj, rank);
        if (warp == 1 && qi >= Q_G1B + 8 && qi < Q_XR) ring_issue(sb, p, Q_XR + ((qi - Q_G1B - 8) >> 1), 0, false, 0, jj, rank);
        TL(10 + qi);
        slot += 2;
        if (slot >= NSTAGE) { slot -= NSTAGE; phase ^= 1; }
      }
    }
  } else {
    const int wg = warp - 2;
    uint32_t* const my_epoch = &p.s->epoch[blockIdx.x * 12 + 8 + warp];
    const uint32_t epoch = ld_relaxed(my_epoch) + 1;
    if (wg == 0) {
      if (lane == 0) { prefetch_tmap(&p.wd); prefetch_tmap(&p.yt); }
      {
        const uint4* gw4 = reinterpret_cast<const uint4*>(p.gate_w);
        const uint4 ga = __ldg(gw4 + lane), gb = lane < 24 ? __ldg(gw4 + 32 + lane) : make_uint4(0, 0, 0, 0);
        if (lane < 7) { mbar_wait(BAR_X(sb, lane), 0); mbar_expect_tx(BAR_X(sb, lane), 16384); mbar_expect_tx(BAR_Y(sb, lane), 16384); }
        __syncwarp();
        float mine = 0.f;
#pragma unroll 1
        for (int u = 0; u < 19; u++) {
          const int r = min(19 * jj + u, 127);
          const uint8_t* xr = smem + SM_X + (lane >> 3) * 16384 + r * 128 + (((lane ^ r) & 7) << 4);
          const uint4 xa = *reinterpret_cast<const uint4*>(xr);
          const uint4 xb = lane < 24 ? *reinterpret_cast<const uint4*>(xr + 65536) : make_uint4(0, 0, 0, 0);
          float s = 0.f;
          auto dot2 = [&](uint32_t a, uint32_t b) {
            const uint32_t pr = mul2(a, b);
            s += bf_lo(pr) + bf_hi(pr);
          };
          dot2(xa.x, ga.x); dot2(xa.y, ga.y); dot2(xa.z, ga.z); dot2(xa.w, ga.w);
          dot2(xb.x, gb.x); dot2(xb.y, gb.y); dot2(xb.z, gb.z); dot2(xb.w, gb.w);
#pragma unroll
          for (int o = 16; o > 0; o >>= 1) s += __shfl_xor_sync(0xffffffffu, s, o);
          if (lane == u) mine = s;
        }
        if (lane < 19 && 19 * jj + lane < 128)
          st_relaxed(&p.s->gate[128 * mt + 19 * jj + lane], pack2(0.f, 1.f / (1.f + __expf(-bf_round(mine)))) | (epoch & 0xffffu));
      }
      TL(9);
      if (lane < 2) mbar_arrive_cluster(BAR_XFREE(sb), lane);
    } else {
      mbar_wait(BAR_X(sb, PFAT), 0);
      if (lane < 6) {
        int row = 176 + 3 * bid + (lane >> 1);
        if (row >= D_) row -= D_;
        l2_prefetch(((lane & 1) ? p.pwu : p.pwg) + row * F_, F_ * 2);
      }
      TL(2);
      bar_sync(7, 160);
      if (lane == 0) { red_add(&p.s->cnt_x1[jj * 32], 1);
        l2_prefetch(p.pwd + bid * 16 * D_, 32 * D_); }
      TL(5);
    }
    mbar_wait(BAR_E2(sb, 0), 0);
    TL(3);
    const int kb = 2 * lane + wg;
    bool todo = kb < 7, ready = false;
    uint32_t n = 0;
    while (__any_sync(0xffffffffu, todo)) {
      if (todo) {
        uint32_t ok;
        if (!ready) {
          asm volatile("ld.acquire.gpu.global.u32 %0, [%1];" : "=r"(ok) : "l"(&p.s->cnt_y[kb * 32]) : "memory");
          ready = (int32_t)(ok - epoch * (kb ? 16 : 17)) >= 0;
        }
        asm volatile("{\n.reg .pred p;\nmbarrier.test_wait.parity.shared::cta.b64 p, [%1], 0;\nselp.u32 %0, 1, 0, p;\n}"
                     : "=r"(ok) : "r"(BAR_E2(sb, kb)) : "memory");
        if ((ok && ready) || ++n > SPIN_LIMIT) {
          tma3d(sb + y_addr(kb), &p.yt, 0, 64 * kb, 2 * mt, BAR_Y(sb, kb));
          todo = false;
        }
      }
      __nanosleep(40);
    }
    TL(4);
    if (lane == 0) *my_epoch = epoch;
  }
}

__device__ __forceinline__ void spectral_cta(uint32_t sb, uint8_t* smem, const Params& p, int sc, int wg) {
  const int t384 = threadIdx.x, lane = t384 & 31, warp12 = t384 >> 5, tid = t384 & 127;
  const int warp = tid >> 5, q = lane & 3;
  const int sl0 = 6 * sc + min(sc, 8), nsl = sc < 8 ? 7 : 6;
  if (t384 == 320) {
#pragma unroll 1
    for (int i = 0; i < nsl; i++) {
      mbar_expect_tx(BAR_X(sb, i), 2 * SLAB_BYTES);
      const int row = 128 * ((sl0 + i) >> 3) + 8 * ((sl0 + i) & 7);
      const uint32_t dst = sb + SP_Z + 2 * i * SLAB_BYTES;
      bulk_g2s(dst, p.w_r + row * DF_, SLAB_BYTES / 2, BAR_X(sb, i));
      bulk_g2s(dst + SLAB_BYTES / 2, p.w_r + (row + 64) * DF_, SLAB_BYTES / 2, BAR_X(sb, i));
      bulk_g2s(dst + SLAB_BYTES, p.w_i + row * DF_, SLAB_BYTES / 2, BAR_X(sb, i));
      bulk_g2s(dst + 3 * SLAB_BYTES / 2, p.w_i + (row + 64) * DF_, SLAB_BYTES / 2, BAR_X(sb, i));
    }
  } else if (t384 == 352 && sc < 19) {
    mbar_expect_tx(BAR_Y(sb, 6), 24576);
    bulk_g2s(sb + SP_TW, p.spec, 24576, BAR_Y(sb, 6));
  }
  uint32_t* const my_epoch = &p.s->epoch[blockIdx.x * 12 + warp12];
  const uint32_t epoch = ld_relaxed(my_epoch) + 1;
  uint32_t fe[16], tw[16];
#pragma unroll
  for (int i = 0; i < 4; i++) {
    const uint4 a = __ldg(reinterpret_cast<const uint4*>(p.spec->fe) + i * 128 + tid);
    const uint4 b = __ldg(reinterpret_cast<const uint4*>(p.spec->tw) + i * 128 + tid);
    fe[4 * i] = a.x; fe[4 * i + 1] = a.y; fe[4 * i + 2] = a.z; fe[4 * i + 3] = a.w;
    tw[4 * i] = b.x; tw[4 * i + 1] = b.y; tw[4 * i + 2] = b.z; tw[4 * i + 3] = b.w;
  }
  __syncwarp();
  asm volatile("barrier.cluster.wait.acquire.aligned;" ::: "memory");
#pragma unroll 2
  for (int un = wg; un < 8 * nsl; un += 3) {
    const int i = un >> 3, sl = sl0 + i, pr = 16 * (un & 7) + 4 * (lane >> 3) + warp, r = lane & 7;
    mbar_wait(BAR_X(sb, i), 0);
    if (pr < 113) {
      const uint16_t* w = reinterpret_cast<const uint16_t*>(smem + SP_Z + 2 * i * SLAB_BYTES) + r * DF_ + 2 * pr;
      const uint32_t m = pr < 112 ? 0xffffffffu : 0u;
      p.s->wt[pr * 1024 + sl * 8 + (r ^ ((sl >> 2) & 6))] =
          make_uint4(w[0] | ((uint32_t)w[8 * DF_] << 16), w[16 * DF_] | ((uint32_t)w[24 * DF_] << 16),
                     (w[1] | ((uint32_t)w[8 * DF_ + 1] << 16)) & m, (w[16 * DF_ + 1] | ((uint32_t)w[24 * DF_ + 1] << 16)) & m);
    }
  }
  __syncthreads();
  if (t384 == 352) { fence_gpu(); red_add(&p.s->cnt_w[0], 1); TL(2); }
  TL(1);
  if (sc == 19) return;
  const int nrnd = (sc == 18 && wg == 2) ? 1 : 2;
  auto pair_of = [&](int r) { const int i = 3 * sc + wg + 57 * r; return i ? i - 1 : 112; };
  auto fetch = [&]() {
    const int item = wg + 3 * lane, pr = pair_of(lane);
    const uint32_t bar = warp ? BAR_Y(sb, item) : BAR_FULL(sb, item);
    mbar_expect_tx(bar, 16384);
    wait_counter(warp ? &p.s->cnt_w[0] : &p.s->cnt_x1[(pr < 112 ? pr >> 4 : 0) * 32], epoch * (warp ? NSPEC : 16));
    if (warp) fence_async();
    bulk_g2s(sb + (warp ? SP_W : SP_Z) + item * 16384, (warp ? p.s->wt : p.s->x1t) + pr * 1024, 16384, bar);
  };
  if (lane < nrnd && warp == 0) fetch();
  __syncwarp();
  fence_regs(fe); fence_regs(tw);
  mbar_wait(BAR_Y(sb, 6), 0);
  TL(3);
  const uint64_t dT_n = mk_desc(sb + SP_T, 8192, 1024, 1);
#pragma unroll 1
  for (int rnd = 0; rnd < nrnd; rnd++) {
    const int item = wg + 3 * rnd, pr = pair_of(rnd);
    const uint32_t z = sb + SP_Z + item * 16384;
    uint32_t fa[16], fb[16];
    auto load_frag = [&](int off) {
#pragma unroll
      for (int i = 0; i < 4; i++) {
        const uint4 a = *reinterpret_cast<const uint4*>(smem + SP_TW + off + i * 2048 + tid * 16);
        fa[4 * i] = a.x; fa[4 * i + 1] = a.y; fa[4 * i + 2] = a.z; fa[4 * i + 3] = a.w;
      }
      fence_regs(fa);
    };
    load_frag(0);
    {
      const uint32_t live = pr == 0 ? 0xddu : (pr == 112 ? 0x11u : 0xffu);
#pragma unroll 1
      for (uint32_t n = 0; n < 4096; n++) {
        mbar_wait(BAR_FULL(sb, item), n & 1);
        uint32_t bad = 0;
#pragma unroll
        for (int i = 0; i < 8; i++) bad |= ((*reinterpret_cast<const volatile uint32_t*>(smem + SP_Z + item * 16384 + i * 2048 + tid * 16) ^ epoch) & 1) << i;
        uint32_t again;
        asm volatile("{\n.reg .pred p, q;\nsetp.ne.u32 p, %1, 0;\nbarrier.red.or.pred q, %2, 128, p;\nselp.u32 %0, 1, 0, q;\n}"
                     : "=r"(again) : "r"(bad & live), "r"(1 + wg) : "memory");
        if (!again) break;
        TL(20);
        if (tid == 0) { mbar_expect_tx(BAR_FULL(sb, item), 16384); bulk_g2s(z, p.s->x1t + pr * 1024, 16384, BAR_FULL(sb, item)); }
      }
    }
    TL(4 + 8 * rnd);
    if (rnd == 0 && wg > 0) bar_sync(3 + wg, 256);
    float aR[32], aI[32];
    {
      const uint64_t de = mk_desc(z, 4096, 512, 2);
      wg_fence();
#pragma unroll
      for (int kk = 0; kk < 4; kk++) {
        wgmma_rs_n64<1, 1>(aR, fe[4 * kk], fe[4 * kk + 1], fe[4 * kk + 2], fe[4 * kk + 3], de + kk * 64, kk != 0);
        wgmma_rs_n64<1, 1>(aI, fa[4 * kk], fa[4 * kk + 1], fa[4 * kk + 2], fa[4 * kk + 3], de + 512 + kk * 64, kk != 0);
      }
      wg_commit();
      if (rnd == 0 && wg < 2) bar_arrive(4 + wg, 256);
      if (rnd == 0 && lane < nrnd && warp == 1) fetch();
      __syncwarp();
      wg_wait<0>();
      fence_regs(aR); fence_regs(aI);
    }
    TL(5 + 8 * rnd);
#pragma unroll
    for (int v = 0; v < 8; v++) {
      uint32_t* f = (v < 4 ? fa : fb) + 2 * (v & 3);
      const uint32_t* t = tw + 2 * (v & 3);
      const float *e = aR + 4 * v, *o = aI + 4 * v;
      const uint32_t er = pack2(e[0], e[1]), ei = pack2(e[2], e[3]), qr = pack2(o[0], o[1]), qi = pack2(o[2], o[3]);
      const uint32_t u0r = add2(er, qr), u0i = add2(ei, qi), u1r = sub2(er, qr), u1i = sub2(ei, qi);
      f[0] = fma2(u0r, t[0], mul2(u0i, t[8]));
      f[8] = fms2(u0i, t[0], mul2(u0r, t[8]));
      f[1] = fma2(u1r, t[1], mul2(u1i, t[9]));
      f[9] = fms2(u1i, t[1], mul2(u1r, t[9]));
    }
    fence_regs(fa); fence_regs(fb);
    wg_fence();
#pragma unroll
    for (int kk = 0; kk < 4; kk++) {
      wgmma_rs_n64<1, 1>(aR, fa[4 * kk], fa[4 * kk + 1], fa[4 * kk + 2], fa[4 * kk + 3], dT_n + kk * 128, kk != 0);
      wgmma_rs_n64<1, 1>(aI, fb[4 * kk], fb[4 * kk + 1], fb[4 * kk + 2], fb[4 * kk + 3], dT_n + kk * 128, kk != 0);
    }
    wg_commit();
    if (rnd == 1 && tid == 0) {
      asm volatile("cp.async.bulk.wait_group 0;" ::: "memory");
      red_add(&p.s->cnt_y[(max(pr - 57, 0) >> 4) * 32], 1);
    }
    __syncwarp();
    mbar_wait(BAR_Y(sb, item), 0);
    wg_wait<0>();
    fence_regs(aR); fence_regs(aI);
    TL(6 + 8 * rnd);
    {
      const uint8_t* wp = smem + SP_W + item * 16384 + q * 1024 + warp * 128 + (((lane >> 2) ^ (2 * q)) << 4);
#pragma unroll
      for (int jb = 0; jb < 4; jb++) {
#pragma unroll
        for (int h = 0; h < 2; h++) {
          const uint4 w = *reinterpret_cast<const uint4*>(wp + jb * 4096 + h * 512);
          const int i = 4 * jb + 2 * h;
          const uint32_t ar = pack2(aR[i], aR[i + 1]), ai = pack2(aR[16 + i], aR[17 + i]);
          const uint32_t br = pack2(aI[i], aI[i + 1]), bi = pack2(aI[16 + i], aI[17 + i]);
          fa[2 * jb + h] = fms2(ar, w.x, mul2(ai, w.y));
          fa[8 + 2 * jb + h] = fma2(ar, w.y, mul2(ai, w.x));
          fb[2 * jb + h] = fms2(br, w.z, mul2(bi, w.w));
          fb[8 + 2 * jb + h] = fma2(br, w.w, mul2(bi, w.z));
        }
      }
    }
    fence_regs(fa); fence_regs(fb);
    wg_fence();
#pragma unroll
    for (int kk = 0; kk < 4; kk++) {
      wgmma_rs_n64<1, 0>(aR, fa[4 * kk], fa[4 * kk + 1], fa[4 * kk + 2], fa[4 * kk + 3], dT_n + kk * 2, kk != 0);
      wgmma_rs_n64<1, 0>(aI, fb[4 * kk], fb[4 * kk + 1], fb[4 * kk + 2], fb[4 * kk + 3], dT_n + kk * 2, kk != 0);
    }
    wg_commit();
    wg_wait<0>();
    fence_regs(aR); fence_regs(aI);
    TL(7 + 8 * rnd);
#pragma unroll
    for (int v = 0; v < 8; v++) {
      const float* a = (v < 4 ? aR : aI) + 4 * (v & 3);
      const uint32_t* t = tw + 2 * (v & 3);
      const uint32_t u0r = pack2(a[0], a[1]), u1r = pack2(a[2], a[3]), u0i = pack2(a[16], a[17]), u1i = pack2(a[18], a[19]);
      const uint32_t t0r = fms2(u0r, t[0], mul2(u0i, t[8])), t0i = fma2(u0i, t[0], mul2(u0r, t[8]));
      const uint32_t t1r = fms2(u1r, t[1], mul2(u1i, t[9])), t1i = fma2(u1i, t[1], mul2(u1r, t[9]));
      fa[v] = add2(t0i, t1i); fa[8 + v] = add2(t0r, t1r);
      fb[v] = sub2(t0i, t1i); fb[8 + v] = sub2(t0r, t1r);
    }
    bar_sync(1 + wg, 128);
#pragma unroll
    for (int u = 0; u < 4; u++) {
      const uint32_t a = z + (32 * (u >> 1) + 8 * warp + (lane & 7)) * 128 + (((4 * (u & 1) + (lane >> 3)) ^ (lane & 7)) << 4);
      stmatrix_x4(a, fa[4 * u], fa[4 * u + 1], fa[4 * u + 2], fa[4 * u + 3]);
      stmatrix_x4(a + 8192, fb[4 * u], fb[4 * u + 1], fb[4 * u + 2], fb[4 * u + 3]);
    }
    load_frag(8192);
    fence_async_smem();
    bar_sync(1 + wg, 128);
    TL(8 + 8 * rnd);
    {
      const uint64_t de = mk_desc(z, 8192, 1024, 1);
      wg_fence();
#pragma unroll
      for (int kk = 0; kk < 4; kk++) {
        wgmma_rs_n64<1, 1>(aR, fe[4 * kk], fe[4 * kk + 1], fe[4 * kk + 2], fe[4 * kk + 3], de + kk * 128, kk != 0);
        wgmma_rs_n64<1, 1>(aI, fa[4 * kk], fa[4 * kk + 1], fa[4 * kk + 2], fa[4 * kk + 3], de + 512 + kk * 128, kk != 0);
      }
      wg_commit();
      wg_wait<0>();
      fence_regs(aR); fence_regs(aI);
    }
    TL(9 + 8 * rnd);
    const bool edge = pr == 0 || pr == 112;
    if (edge) {
#pragma unroll
      for (int i = 0; i < 16; i++) { aR[i] *= 0.5f; aI[i] *= 0.5f; }
    }
#pragma unroll
    for (int i = 0; i < 8; i++) {
      const float* a = ((i & 1) ? aI : aR) + 16 * (i >> 2) + 2 - (i & 2);
      *reinterpret_cast<uint4*>(smem + SP_W + item * 16384 + (i >> 1) * 4096 + (i & 1) * 64 + (tid >> 2) * 128 + q * 16) =
          make_uint4(pack2(a[0], a[1]), pack2(a[4], a[5]), pack2(a[8], a[9]), pack2(a[12], a[13]));
    }
    fence_async_smem();
    bar_sync(1 + wg, 128);
    if (tid == 0) {
      const uint32_t src = sb + SP_W + item * 16384;
      __nv_bfloat16* dst = p.s->yt + (size_t)(pr < 112 ? 4 * pr : 1) * S_;
      bulk_s2g(dst, src, edge ? 4096 : 16384);
      if (pr == 0) bulk_s2g(dst + 2 * S_, src + 8192, 8192);
      asm volatile("cp.async.bulk.commit_group;" ::: "memory");
      if (rnd == nrnd - 1) {
        asm volatile("cp.async.bulk.wait_group 0;" ::: "memory");
        TL(11);
        red_add(&p.s->cnt_y[(pr < 112 ? pr >> 4 : 0) * 32], 1);
      }
    }
    __syncwarp();
    TL(10 + 8 * rnd);
  }
  if (lane == 0) *my_epoch = epoch;
}

__global__ void __cluster_dims__(2, 1, 1) __launch_bounds__(384, 1)
fused_kernel(const __grid_constant__ Params p) {
  extern __shared__ __align__(1024) uint8_t smem[];
  const uint32_t sb = smem_u32(smem);
  TL(0);
  const uint32_t rank = blockIdx.x & 1;
  const int hc = blockIdx.x >> 1;
  int grp, jj;
  if (hc < 4) { grp = 8; jj = hc; }
  else if (hc < 36) { grp = (hc - 4) & 7; jj = (hc - 4) >> 3; }
  else if (hc < 57) { jj = (hc - 36) / 7; grp = 1 + (hc - 36) - 7 * jj; jj += 4; }
  else if (hc < 60) { grp = 0; jj = hc - 53; }
  else { grp = 8; jj = hc - 56; }
  const int mt = 2 * grp + rank, bid = 2 * (7 * grp + jj) + rank;
  if (bid < NFFN) {
    const int t = threadIdx.x;
    if (t < 19 && 19 * jj + t < 128) asm volatile("prefetch.global.L2 [%0];" ::"l"(p.px + (128 * mt + 19 * jj + t) * D_));
    if (t >= 128 && t < 136) asm volatile("prefetch.global.L2 [%0];" ::"l"((rank ? p.pwu : p.pwg) + (4 * grp + (t & 3)) * F_ + 256 * jj + 16 * (t & 4)));
  }
  if (threadIdx.x == 256) {
#pragma unroll
    for (int i = 0; i < NSTAGE; i++) { mbar_init(BAR_FULL(sb, i), 1); mbar_init(BAR_EMPTY(sb, i), 4); }
    asm volatile("fence.mbarrier_init.release.cluster;" ::: "memory");
  } else if (threadIdx.x == 320) {
    mbar_init(BAR_X(sb, 0), 1);
    if (bid < NFFN) {
      mbar_expect_tx(BAR_X(sb, 0), 16384);
      tma2d(sb + SM_X, &p.x, 0, 128 * mt, BAR_X(sb, 0));
    }
#pragma unroll
    for (int i = 1; i < NSTAGE; i++) mbar_init(BAR_X(sb, i), 1);
    mbar_init(BAR_XFREE(sb), 2);
    asm volatile("fence.mbarrier_init.release.cluster;" ::: "memory");
  } else if (threadIdx.x == 352) {
#pragma unroll
    for (int i = 0; i < NSTAGE; i++) { mbar_init(BAR_Y(sb, i), 1); mbar_init(BAR_E2(sb, i), 2); }
    asm volatile("fence.mbarrier_init.release.cluster;" ::: "memory");
  } else if (threadIdx.x == 288 && bid < NFFN) {
    prefetch_tmap(rank ? &p.wu : &p.wg); prefetch_tmap(&p.ct);
  }
  __syncwarp();
  asm volatile("barrier.cluster.arrive.relaxed.aligned;" ::: "memory");
  const int wg = __shfl_sync(0xffffffffu, threadIdx.x >> 7, 0);
  if (bid >= NFFN) {
    spectral_cta(sb, smem, p, bid - NFFN, wg);
  } else if (wg < 2) {
    asm volatile("setmaxnreg.inc.sync.aligned.u32 232;");
    asm volatile("barrier.cluster.wait.acquire.aligned;" ::: "memory");
    TL(1);
    ffn_consumer(sb, smem, p, bid, wg, threadIdx.x & 127, mt, jj);
  } else {
    asm volatile("setmaxnreg.dec.sync.aligned.u32 40;");
    asm volatile("barrier.cluster.wait.acquire.aligned;" ::: "memory");
    TL(1);
    if (threadIdx.x == 320) {
      constexpr int order[13] = {XORDER};
#pragma unroll
      for (int i = 0; i < 13; i++) {
        if (order[i] < 8) {
          ring_issue(sb, p, order[i], order[i], false, 0, jj, rank);
        } else {
          const int kb = order[i] - 10;
          mbar_expect_tx(BAR_X(sb, kb), 16384);
          tma2d(sb + SM_X + kb * 16384, &p.x, 64 * kb, 128 * mt, BAR_X(sb, kb));
        }
      }
      TL(2);
    }
    __syncwarp();
    ffn_producer(sb, smem, bid, p, (threadIdx.x >> 5) & 3, threadIdx.x & 31, mt, jj, rank);
  }
}

typedef CUresult (*EncodeFn)(CUtensorMap*, CUtensorMapDataType, cuuint32_t, void*, const cuuint64_t*, const cuuint64_t*,
                             const cuuint32_t*, const cuuint32_t*, CUtensorMapInterleave, CUtensorMapSwizzle,
                             CUtensorMapL2promotion, CUtensorMapFloatOOBfill);

void make_map(EncodeFn fn, CUtensorMap* m, const void* base, int rank, const cuuint64_t* dims, const cuuint64_t* strides,
              const cuuint32_t* box, CUtensorMapSwizzle sw) {
  const cuuint32_t es[4] = {1, 1, 1, 1};
  fn(m, CU_TENSOR_MAP_DATA_TYPE_BFLOAT16, rank, const_cast<void*>(base), dims, strides, box, es,
     CU_TENSOR_MAP_INTERLEAVE_NONE, sw, CU_TENSOR_MAP_L2_PROMOTION_L2_256B, CU_TENSOR_MAP_FLOAT_OOB_FILL_NONE);
}

}

extern "C" void kernel_launch(void* const* d_in, const int* in_sizes, int n_in, void* d_out, int out_size) {
  const __nv_bfloat16* x = (const __nv_bfloat16*)d_in[0];
  const __nv_bfloat16* w_r = (const __nv_bfloat16*)d_in[1];
  const __nv_bfloat16* w_i = (const __nv_bfloat16*)d_in[2];
  const __nv_bfloat16* wg = (const __nv_bfloat16*)d_in[4];
  const __nv_bfloat16* wu = (const __nv_bfloat16*)d_in[5];
  const __nv_bfloat16* wd = (const __nv_bfloat16*)d_in[6];
  const __nv_bfloat16* gate_w = (const __nv_bfloat16*)d_in[7];

  void* fnp = nullptr;
  cudaDriverEntryPointQueryResult qr;
  cudaGetDriverEntryPoint("cuTensorMapEncodeTiled", &fnp, cudaEnableDefault, &qr);
  EncodeFn fn = (EncodeFn)fnp;
  void *ctab, *spec, *scr;
  cudaGetSymbolAddress(&ctab, g_ctab);
  cudaGetSymbolAddress(&spec, g_spec);
  cudaGetSymbolAddress(&scr, g_scratch);
  const void* yt = (const char*)scr + offsetof(Scratch, yt);
  Params p;
  p.s = (Scratch*)scr; p.out = (__nv_bfloat16*)d_out;
  p.px = x; p.w_r = w_r; p.w_i = w_i; p.gate_w = gate_w; p.pwg = wg; p.pwu = wu; p.pwd = wd;
  p.ctab = (const tab::Table*)ctab; p.spec = (const tab::Spec*)spec;
  {
    const cuuint64_t d[2] = {D_, S_}, s[1] = {D_ * 2};
    const cuuint32_t b[2] = {64, 128};
    make_map(fn, &p.x, x, 2, d, s, b, CU_TENSOR_MAP_SWIZZLE_128B);
  }
  {
    const cuuint64_t d[3] = {64, D_, F_ / 64}, s[2] = {F_ * 2, 128};
    const cuuint32_t b[3] = {64, 32, 2};
    make_map(fn, &p.wg, wg, 3, d, s, b, CU_TENSOR_MAP_SWIZZLE_128B);
    make_map(fn, &p.wu, wu, 3, d, s, b, CU_TENSOR_MAP_SWIZZLE_128B);
  }
  {
    const cuuint64_t d[2] = {D_, F_}, s[1] = {D_ * 2};
    const cuuint32_t b[2] = {64, 64};
    make_map(fn, &p.wd, wd, 2, d, s, b, CU_TENSOR_MAP_SWIZZLE_128B);
  }
  {
    const cuuint64_t d[2] = {D_, D_}, s[1] = {D_ * 2};
    const cuuint32_t b[2] = {64, 64};
    make_map(fn, &p.ct, ctab, 2, d, s, b, CU_TENSOR_MAP_SWIZZLE_128B);
  }
  {
    const cuuint64_t d[3] = {64, D_, S_ / 64}, s[2] = {S_ * 2, 128};
    const cuuint32_t b[3] = {64, 64, 2};
    make_map(fn, &p.yt, yt, 3, d, s, b, CU_TENSOR_MAP_SWIZZLE_128B);
  }
  cudaFuncSetAttribute(fused_kernel, cudaFuncAttributeMaxDynamicSharedMemorySize, SM_TOTAL);
  fused_kernel<<<NCTA, 384, SM_TOTAL, cudaStreamPerThread>>>(p, x, w_r, w_i, gate_w, wd, (__nv_bfloat16*)d_out);
}
```

```cpp
#include <cuda_runtime.h>
#include <cuda_bf16.h>
#include <cuda.h>
#include <stdint.h>
#include <stddef.h>

namespace {

constexpr int S_ = 2048, D_ = 448, F_ = 1792, DF_ = 225;
constexpr int NFFN = 112, NSPEC = 20, NCTA = NFFN + NSPEC;
constexpr int NSTAGE = 7, STAGE_BYTES = 16384;
constexpr int SM_X = 0, SM_RING = 114688, SM_BAR = 229376, SM_TOTAL = SM_BAR + 512;
constexpr int SP_Z = 0, SP_W = 98304, SP_TW = 198656, SP_T = 215040, SLAB_BYTES = 16 * DF_ * 2;
constexpr uint32_t SPIN_LIMIT = 1u << 20;

namespace tab {
constexpr double PI = 3.14159265358979323846264338327950288;
constexpr double csin(double x) {
  double t = x, s = x;
  for (int i = 1; i < 20; i++) { t = -t * x * x / ((2 * i) * (2 * i + 1)); s += t; }
  return s;
}
constexpr double ccos(double x) {
  double t = 1, s = 1;
  for (int i = 1; i < 20; i++) { t = -t * x * x / ((2 * i - 1) * (2 * i)); s += t; }
  return s;
}
constexpr uint32_t to_bf16(double v) {
  uint32_t sign = v < 0 ? 0x8000u : 0u;
  double a = v < 0 ? -v : v;
  if (a < 1e-12) return 0;
  int e = 0;
  while (a >= 2.0) { a /= 2; e++; }
  while (a < 1.0) { a *= 2; e--; }
  double m = a * 128.0;
  int mi = (int)m;
  double fr = m - mi;
  if (fr > 0.5 || (fr == 0.5 && (mi & 1))) mi++;
  if (mi == 256) { mi = 128; e++; }
  return sign | (uint32_t)((e + 127) << 7) | (uint32_t)(mi - 128);
}
struct Base { uint32_t v[448]; };
constexpr Base make_base() {
  Base b{};
  for (int m = 0; m < 448; m++) {
    int mm = m > 224 ? m - 448 : m;
    double ang = 2 * PI * mm / 448.0;
    b.v[m] = to_bf16(ccos(ang)) | (to_bf16(-csin(ang)) << 16);
  }
  return b;
}
constexpr Base base = make_base();
struct Row { uint32_t v[224]; };
constexpr Row make_row(int d) {
  Row r{};
  r.v[0] = 0x3f80u | ((d & 1) ? 0xbf800000u : 0x3f800000u);
  int m = 0;
  for (int c = 1; c < 224; c++) { m += d; if (m >= 448) m -= 448; r.v[c] = base.v[m]; }
  return r;
}
struct Table { Row r[448]; };
constexpr Table make_table() {
  Table t{};
  for (int d = 0; d < 448; d++) t.r[d] = make_row(d);
  return t;
}
struct Cs { double c[2048], s[2048]; };
constexpr Cs make_cs() {
  Cs t{};
  for (int m = 0; m <= 256; m++) {
    const double a = 2 * PI * m / 2048.0, c = ccos(a), s = csin(a);
    t.c[m] = c; t.s[m] = s;
    t.c[512 - m] = s; t.s[512 - m] = c;
  }
  for (int m = 513; m < 2048; m++) { t.c[m] = -t.s[m - 512]; t.s[m] = t.c[m - 512]; }
  return t;
}
constexpr Cs cs = make_cs();
struct Spec {
  uint32_t fo[2048], fot[2048];
  uint16_t t32[4096];
  uint32_t fe[2048];
  uint32_t tw[2048];
};
constexpr uint32_t blk(int h, int c, int a) { return to_bf16(h == c ? cs.c[a & 2047] : (h ? -cs.s[a & 2047] : cs.s[a & 2047])); }
constexpr Spec make_spec() {
  Spec t{};
  for (int row = 0; row < 64; row++)
    for (int col = 0; col < 64; col++) {
      const int c = row & 31, k2 = col & 31, n2 = 8 * ((c >> 1) & 3) + 2 * (c >> 3) + (c & 1), m = 64 * ((n2 * k2) & 31);
      const double v = (row >> 5) == (col >> 5) ? cs.c[m] : (row < 32 ? -cs.s[m] : cs.s[m]);
      t.t32[row * 64 + (((col >> 3) ^ (row & 7)) << 3) + (col & 7)] = (uint16_t)to_bf16(v);
    }
  for (int th = 0; th < 128; th++)
    for (int i = 0; i < 16; i++) {
      const int r = 8 * (th >> 5) + ((th & 31) >> 2), h = i & 1, c = i >> 3, m = 8 * ((i >> 1) & 3) + 2 * (th & 3);
      const int o = ((i >> 2) * 128 + th) * 4 + (i & 3);
      t.fe[o] = blk(h, c, 64 * m * r) | (blk(h, c, 64 * (m + 1) * r) << 16);
      t.fo[o] = blk(h, c, 32 * (2 * m + 1) * r) | (blk(h, c, 32 * (2 * m + 3) * r) << 16);
      t.fot[o] = blk(h, c, 32 * (2 * r + 1) * m) | (blk(h, c, 32 * (2 * r + 1) * (m + 1)) << 16);
      const int k1 = r + 32 * h, n2 = 8 * (th & 3) + 2 * ((i >> 1) & 3);
      t.tw[o] = blk(0, c, n2 * k1) | (blk(0, c, (n2 + 1) * k1) << 16);
    }
  return t;
}
}
}

__device__ __align__(1024) const tab::Table g_ctab = tab::make_table();
__device__ __align__(1024) const tab::Spec g_spec = tab::make_spec();

struct Scratch {
  uint32_t cnt_w[32];
  uint32_t cnt_x1[7 * 32];
  uint32_t cnt_y[7 * 32];
  uint32_t epoch[NCTA * 12 + 240 + 256];
  uint32_t gate[S_];
  uint4 x1t[113 * 1024];
  __nv_bfloat16 yt[D_ * S_];
  uint4 wt[114 * 1024];
  uint4 part[16 * 7 * 6 * 2 * 4 * 128];
};
static_assert(offsetof(Scratch, x1t) % 1024 == 0, "alignment");
__device__ __align__(1024) Scratch g_scratch;
#define TL(i)

namespace {

struct Params {
  Scratch* s;
  __nv_bfloat16* out;
  const __nv_bfloat16 *px, *w_r, *w_i, *gate_w, *pwg, *pwu, *pwd;
  const tab::Table* ctab;
  const tab::Spec* spec;
  CUtensorMap x, wg, wu, wd, ct, yt;
};

__device__ __forceinline__ uint32_t smem_u32(const void* p) { return (uint32_t)__cvta_generic_to_shared(p); }
__device__ __forceinline__ void mbar_init(uint32_t bar, uint32_t cnt) {
  asm volatile("mbarrier.init.shared::cta.b64 [%0], %1;" ::"r"(bar), "r"(cnt) : "memory");
}
__device__ __forceinline__ void mbar_expect_tx(uint32_t bar, uint32_t bytes) {
  asm volatile("mbarrier.arrive.expect_tx.shared::cta.b64 _, [%0], %1;" ::"r"(bar), "r"(bytes) : "memory");
}
__device__ __forceinline__ void mbar_arrive(uint32_t bar) {
  asm volatile("mbarrier.arrive.shared::cta.b64 _, [%0];" ::"r"(bar) : "memory");
}
__device__ __forceinline__ void mbar_arrive_cluster(uint32_t bar, uint32_t cta) {
  asm volatile("{\n.reg .b32 ra;\nmapa.shared::cluster.u32 ra, %0, %1;\n"
               "mbarrier.arrive.shared::cluster.b64 _, [ra];\n}" ::"r"(bar), "r"(cta) : "memory");
}
__device__ __forceinline__ void mbar_wait(uint32_t bar, uint32_t parity) {
  uint32_t ok, n = 0;
  do {
    asm volatile("{\n.reg .pred p;\nmbarrier.try_wait.parity.shared::cta.b64 p, [%1], %2;\nselp.u32 %0, 1, 0, p;\n}"
                 : "=r"(ok) : "r"(bar), "r"(parity) : "memory");
  } while (!ok && ++n < SPIN_LIMIT);
}
__device__ __forceinline__ void mbar_wait_cluster(uint32_t bar, uint32_t parity) {
  uint32_t ok, n = 0;
  do {
    asm volatile("{\n.reg .pred p;\nmbarrier.try_wait.parity.acquire.cluster.shared::cta.b64 p, [%1], %2;\nselp.u32 %0, 1, 0, p;\n}"
                 : "=r"(ok) : "r"(bar), "r"(parity) : "memory");
  } while (!ok && ++n < SPIN_LIMIT);
}
__device__ __forceinline__ void tma2d(uint32_t dst, const CUtensorMap* m, int c0, int c1, uint32_t bar) {
  asm volatile("cp.async.bulk.tensor.2d.shared::cluster.global.mbarrier::complete_tx::bytes [%0], [%1, {%3, %4}], [%2];"
               ::"r"(dst), "l"(m), "r"(bar), "r"(c0), "r"(c1) : "memory");
}
__device__ __forceinline__ void tma3d(uint32_t dst, const CUtensorMap* m, int c0, int c1, int c2, uint32_t bar) {
  asm volatile("cp.async.bulk.tensor.3d.shared::cluster.global.mbarrier::complete_tx::bytes [%0], [%1, {%3, %4, %5}], [%2];"
               ::"r"(dst), "l"(m), "r"(bar), "r"(c0), "r"(c1), "r"(c2) : "memory");
}
__device__ __forceinline__ void tma2d_mc(uint32_t dst, const CUtensorMap* m, int c0, int c1, uint32_t bar) {
  asm volatile("cp.async.bulk.tensor.2d.shared::cluster.global.mbarrier::complete_tx::bytes.multicast::cluster [%0], [%1, {%3, %4}], [%2], %5;"
               ::"r"(dst), "l"(m), "r"(bar), "r"(c0), "r"(c1), "h"((uint16_t)3) : "memory");
}
__device__ __forceinline__ void tma3d_mc(uint32_t dst, const CUtensorMap* m, int c0, int c1, int c2, uint32_t bar) {
  asm volatile("cp.async.bulk.tensor.3d.shared::cluster.global.mbarrier::complete_tx::bytes.multicast::cluster [%0], [%1, {%3, %4, %5}], [%2], %6;"
               ::"r"(dst), "l"(m), "r"(bar), "r"(c0), "r"(c1), "r"(c2), "h"((uint16_t)3) : "memory");
}
__device__ __forceinline__ void bulk_g2s(uint32_t dst, const void* src, uint32_t bytes, uint32_t bar) {
  asm volatile("cp.async.bulk.shared::cluster.global.mbarrier::complete_tx::bytes [%0], [%1], %2, [%3];"
               ::"r"(dst), "l"(src), "r"(bytes), "r"(bar) : "memory");
}
__device__ __forceinline__ void bulk_s2g(void* dst, uint32_t src, uint32_t bytes) {
  asm volatile("cp.async.bulk.global.shared::cta.bulk_group [%0], [%1], %2;" ::"l"(dst), "r"(src), "r"(bytes) : "memory");
}
__device__ __forceinline__ void prefetch_tmap(const CUtensorMap* m) {
  asm volatile("prefetch.tensormap [%0];" ::"l"(m) : "memory");
}
__device__ __forceinline__ void l2_prefetch(const void* p, uint32_t bytes) {
  asm volatile("cp.async.bulk.prefetch.L2.global [%0], %1;" ::"l"(p), "r"(bytes) : "memory");
}
__device__ __forceinline__ void wg_fence() { asm volatile("wgmma.fence.sync.aligned;" ::: "memory"); }
__device__ __forceinline__ void wg_commit() { asm volatile("wgmma.commit_group.sync.aligned;" ::: "memory"); }
template <int N> __device__ __forceinline__ void wg_wait() { asm volatile("wgmma.wait_group.sync.aligned %0;" ::"n"(N) : "memory"); }
template <int N> __device__ __forceinline__ void fence_regs(float (&d)[N]) {
#pragma unroll
  for (int i = 0; i < N; i++) asm volatile("" : "+f"(d[i])::"memory");
}
template <int N> __device__ __forceinline__ void fence_regs(uint32_t (&d)[N]) {
#pragma unroll
  for (int i = 0; i < N; i++) asm volatile("" : "+r"(d[i])::"memory");
}
__device__ __forceinline__ void bar_sync(int id, int n) { asm volatile("bar.sync %0, %1;" ::"r"(id), "r"(n) : "memory"); }
__device__ __forceinline__ void bar_arrive(int id, int n) { asm volatile("bar.arrive %0, %1;" ::"r"(id), "r"(n) : "memory"); }
__device__ __forceinline__ void fence_gpu() { asm volatile("fence.acq_rel.gpu;" ::: "memory"); }
__device__ __forceinline__ void fence_async() { asm volatile("fence.proxy.async;" ::: "memory"); }
__device__ __forceinline__ void fence_async_smem() { asm volatile("fence.proxy.async.shared::cta;" ::: "memory"); }
__device__ __forceinline__ void red_add(uint32_t* p, uint32_t v) {
  asm volatile("red.relaxed.gpu.global.add.u32 [%0], %1;" ::"l"(p), "r"(v) : "memory");
}
__device__ __forceinline__ uint32_t ld_relaxed(const uint32_t* p) {
  uint32_t v;
  asm volatile("ld.relaxed.gpu.global.u32 %0, [%1];" : "=r"(v) : "l"(p) : "memory");
  return v;
}
__device__ __forceinline__ void wait_counter(const uint32_t* p, uint32_t target) {
  uint32_t v, n = 0;
  while (true) {
    asm volatile("ld.acquire.gpu.global.u32 %0, [%1];" : "=r"(v) : "l"(p) : "memory");
    if ((int32_t)(v - target) >= 0 || ++n > SPIN_LIMIT) break;
  }
}
__device__ __forceinline__ uint4 ld_relaxed(const uint4* p) {
  uint4 v;
  asm volatile("ld.relaxed.gpu.global.v4.u32 {%0, %1, %2, %3}, [%4];" : "=r"(v.x), "=r"(v.y), "=r"(v.z), "=r"(v.w) : "l"(p) : "memory");
  return v;
}
__device__ __forceinline__ void st_relaxed(uint4* p, uint4 v) {
  asm volatile("st.relaxed.gpu.global.v4.u32 [%0], {%1, %2, %3, %4};" ::"l"(p), "r"(v.x), "r"(v.y), "r"(v.z), "r"(v.w) : "memory");
}
__device__ __forceinline__ void st_relaxed(uint32_t* p, uint32_t v) {
  asm volatile("st.relaxed.gpu.global.u32 [%0], %1;" ::"l"(p), "r"(v) : "memory");
}
__device__ __forceinline__ uint32_t pack2(float lo, float hi) {
  uint32_t r;
  asm("cvt.rn.bf16x2.f32 %0, %1, %2;" : "=r"(r) : "f"(hi), "f"(lo));
  return r;
}
__device__ __forceinline__ uint32_t mul2(uint32_t a, uint32_t b) {
  uint32_t r;
  asm("mul.rn.bf16x2 %0, %1, %2;" : "=r"(r) : "r"(a), "r"(b));
  return r;
}
__device__ __forceinline__ uint32_t fma2(uint32_t a, uint32_t b, uint32_t c) {
  uint32_t r;
  asm("fma.rn.bf16x2 %0, %1, %2, %3;" : "=r"(r) : "r"(a), "r"(b), "r"(c));
  return r;
}
__device__ __forceinline__ uint32_t add2(uint32_t a, uint32_t b) {
  uint32_t r;
  asm("add.rn.bf16x2 %0, %1, %2;" : "=r"(r) : "r"(a), "r"(b));
  return r;
}
__device__ __forceinline__ uint32_t sub2(uint32_t a, uint32_t b) {
  uint32_t r;
  asm("sub.rn.bf16x2 %0, %1, %2;" : "=r"(r) : "r"(a), "r"(b));
  return r;
}
__device__ __forceinline__ uint32_t fms2(uint32_t a, uint32_t b, uint32_t c) {
  uint32_t r;
  asm("{\n.reg .b32 n;\nneg.bf16x2 n, %3;\nfma.rn.bf16x2 %0, %1, %2, n;\n}" : "=r"(r) : "r"(a), "r"(b), "r"(c));
  return r;
}
__device__ __forceinline__ float bf_lo(uint32_t v) { return __uint_as_float(v << 16); }
__device__ __forceinline__ float bf_hi(uint32_t v) { return __uint_as_float(v & 0xffff0000u); }
__device__ __forceinline__ float bf_round(float v) { return bf_lo(pack2(v, 0.f)); }
__device__ __forceinline__ float tanh_fast(float v) {
  float r;
  asm("tanh.approx.f32 %0, %1;" : "=f"(r) : "f"(v));
  return r;
}
__device__ __forceinline__ uint64_t mk_desc(uint32_t addr, uint32_t lbo, uint32_t sbo, uint32_t mode) {
  return (uint64_t)((addr & 0x3FFFF) >> 4) | ((uint64_t)(lbo >> 4) << 16) | ((uint64_t)(sbo >> 4) << 32) | ((uint64_t)mode << 62);
}
__device__ __forceinline__ void stmatrix_x4(uint32_t addr, uint32_t r0, uint32_t r1, uint32_t r2, uint32_t r3) {
  asm volatile("stmatrix.sync.aligned.m8n8.x4.shared.b16 [%0], {%1, %2, %3, %4};" ::"r"(addr), "r"(r0), "r"(r1), "r"(r2), "r"(r3) : "memory");
}

template <int TA, int TB>
__device__ __forceinline__ void wgmma_ss_n256(float (&d)[128], uint64_t da, uint64_t db, int sd) {
  asm volatile("{\n.reg .pred p;\nsetp.ne.b32 p, %130, 0;\n"
      "wgmma.mma_async.sync.aligned.m64n256k16.f32.bf16.bf16 {"
      "%0, %1, %2, %3, %4, %5, %6, %7, %8, %9, %10, %11, %12, %13, %14, %15, %16, %17, %18, %19, %20, %21, %22, %23, "
      "%24, %25, %26, %27, %28, %29, %30, %31, %32, %33, %34, %35, %36, %37, %38, %39, %40, %41, %42, %43, %44, %45, "
      "%46, %47, %48, %49, %50, %51, %52, %53, %54, %55, %56, %57, %58, %59, %60, %61, %62, %63, %64, %65, %66, %67, "
      "%68, %69, %70, %71, %72, %73, %74, %75, %76, %77, %78, %79, %80, %81, %82, %83, %84, %85, %86, %87, %88, %89, "
      "%90, %91, %92, %93, %94, %95, %96, %97, %98, %99, %100, %101, %102, %103, %104, %105, %106, %107, %108, %109, "
      "%110, %111, %112, %113, %114, %115, %116, %117, %118, %119, %120, %121, %122, %123, %124, %125, %126, %127"
      "}, %128, %129, p, 1, 1, %131, %132;\n}\n"
      : "+f"(d[0]), "+f"(d[1]), "+f"(d[2]), "+f"(d[3]), "+f"(d[4]), "+f"(d[5]), "+f"(d[6]), "+f"(d[7]), "+f"(d[8]),
        "+f"(d[9]), "+f"(d[10]), "+f"(d[11]), "+f"(d[12]), "+f"(d[13]), "+f"(d[14]), "+f"(d[15]), "+f"(d[16]),
        "+f"(d[17]), "+f"(d[18]), "+f"(d[19]), "+f"(d[20]), "+f"(d[21]), "+f"(d[22]), "+f"(d[23]), "+f"(d[24]),
        "+f"(d[25]), "+f"(d[26]), "+f"(d[27]), "+f"(d[28]), "+f"(d[29]), "+f"(d[30]), "+f"(d[31]), "+f"(d[32]),
        "+f"(d[33]), "+f"(d[34]), "+f"(d[35]), "+f"(d[36]), "+f"(d[37]), "+f"(d[38]), "+f"(d[39]), "+f"(d[40]),
        "+f"(d[41]), "+f"(d[42]), "+f"(d[43]), "+f"(d[44]), "+f"(d[45]), "+f"(d[46]), "+f"(d[47]), "+f"(d[48]),
        "+f"(d[49]), "+f"(d[50]), "+f"(d[51]), "+f"(d[52]), "+f"(d[53]), "+f"(d[54]), "+f"(d[55]), "+f"(d[56]),
        "+f"(d[57]), "+f"(d[58]), "+f"(d[59]), "+f"(d[60]), "+f"(d[61]), "+f"(d[62]), "+f"(d[63]), "+f"(d[64]),
        "+f"(d[65]), "+f"(d[66]), "+f"(d[67]), "+f"(d[68]), "+f"(d[69]), "+f"(d[70]), "+f"(d[71]), "+f"(d[72]),
        "+f"(d[73]), "+f"(d[74]), "+f"(d[75]), "+f"(d[76]), "+f"(d[77]), "+f"(d[78]), "+f"(d[79]), "+f"(d[80]),
        "+f"(d[81]), "+f"(d[82]), "+f"(d[83]), "+f"(d[84]), "+f"(d[85]), "+f"(d[86]), "+f"(d[87]), "+f"(d[88]),
        "+f"(d[89]), "+f"(d[90]), "+f"(d[91]), "+f"(d[92]), "+f"(d[93]), "+f"(d[94]), "+f"(d[95]), "+f"(d[96]),
        "+f"(d[97]), "+f"(d[98]), "+f"(d[99]), "+f"(d[100]), "+f"(d[101]), "+f"(d[102]), "+f"(d[103]), "+f"(d[104]),
        "+f"(d[105]), "+f"(d[106]), "+f"(d[107]), "+f"(d[108]), "+f"(d[109]), "+f"(d[110]), "+f"(d[111]),
        "+f"(d[112]), "+f"(d[113]), "+f"(d[114]), "+f"(d[115]), "+f"(d[116]), "+f"(d[117]), "+f"(d[118]),
        "+f"(d[119]), "+f"(d[120]), "+f"(d[121]), "+f"(d[122]), "+f"(d[123]), "+f"(d[124]), "+f"(d[125]),
        "+f"(d[126]), "+f"(d[127])
      : "l"(da), "l"(db), "r"(sd), "n"(TA), "n"(TB));
}
template <int TA, int TB>
__device__ __forceinline__ void wgmma_ss_n128(float (&d)[64], uint64_t da, uint64_t db, int sd) {
  asm volatile("{\n.reg .pred p;\nsetp.ne.b32 p, %66, 0;\n"
      "wgmma.mma_async.sync.aligned.m64n128k16.f32.bf16.bf16 {"
      "%0, %1, %2, %3, %4, %5, %6, %7, %8, %9, %10, %11, %12, %13, %14, %15, %16, %17, %18, %19, %20, %21, %22, %23, "
      "%24, %25, %26, %27, %28, %29, %30, %31, %32, %33, %34, %35, %36, %37, %38, %39, %40, %41, %42, %43, %44, %45, "
      "%46, %47, %48, %49, %50, %51, %52, %53, %54, %55, %56, %57, %58, %59, %60, %61, %62, %63"
      "}, %64, %65, p, 1, 1, %67, %68;\n}\n"
      : "+f"(d[0]), "+f"(d[1]), "+f"(d[2]), "+f"(d[3]), "+f"(d[4]), "+f"(d[5]), "+f"(d[6]), "+f"(d[7]), "+f"(d[8]),
        "+f"(d[9]), "+f"(d[10]), "+f"(d[11]), "+f"(d[12]), "+f"(d[13]), "+f"(d[14]), "+f"(d[15]), "+f"(d[16]),
        "+f"(d[17]), "+f"(d[18]), "+f"(d[19]), "+f"(d[20]), "+f"(d[21]), "+f"(d[22]), "+f"(d[23]), "+f"(d[24]),
        "+f"(d[25]), "+f"(d[26]), "+f"(d[27]), "+f"(d[28]), "+f"(d[29]), "+f"(d[30]), "+f"(d[31]), "+f"(d[32]),
        "+f"(d[33]), "+f"(d[34]), "+f"(d[35]), "+f"(d[36]), "+f"(d[37]), "+f"(d[38]), "+f"(d[39]), "+f"(d[40]),
        "+f"(d[41]), "+f"(d[42]), "+f"(d[43]), "+f"(d[44]), "+f"(d[45]), "+f"(d[46]), "+f"(d[47]), "+f"(d[48]),
        "+f"(d[49]), "+f"(d[50]), "+f"(d[51]), "+f"(d[52]), "+f"(d[53]), "+f"(d[54]), "+f"(d[55]), "+f"(d[56]),
        "+f"(d[57]), "+f"(d[58]), "+f"(d[59]), "+f"(d[60]), "+f"(d[61]), "+f"(d[62]), "+f"(d[63])
      : "l"(da), "l"(db), "r"(sd), "n"(TA), "n"(TB));
}
template <int TA, int TB>
__device__ __forceinline__ void wgmma_ss_n64(float (&d)[32], uint64_t da, uint64_t db, int sd) {
  asm volatile("{\n.reg .pred p;\nsetp.ne.b32 p, %34, 0;\n"
      "wgmma.mma_async.sync.aligned.m64n64k16.f32.bf16.bf16 {"
      "%0, %1, %2, %3, %4, %5, %6, %7, %8, %9, %10, %11, %12, %13, %14, %15, %16, %17, %18, %19, %20, %21, %22, %23, "
      "%24, %25, %26, %27, %28, %29, %30, %31"
      "}, %32, %33, p, 1, 1, %35, %36;\n}\n"
      : "+f"(d[0]), "+f"(d[1]), "+f"(d[2]), "+f"(d[3]), "+f"(d[4]), "+f"(d[5]), "+f"(d[6]), "+f"(d[7]), "+f"(d[8]),
        "+f"(d[9]), "+f"(d[10]), "+f"(d[11]), "+f"(d[12]), "+f"(d[13]), "+f"(d[14]), "+f"(d[15]), "+f"(d[16]),
        "+f"(d[17]), "+f"(d[18]), "+f"(d[19]), "+f"(d[20]), "+f"(d[21]), "+f"(d[22]), "+f"(d[23]), "+f"(d[24]),
        "+f"(d[25]), "+f"(d[26]), "+f"(d[27]), "+f"(d[28]), "+f"(d[29]), "+f"(d[30]), "+f"(d[31])
      : "l"(da), "l"(db), "r"(sd), "n"(TA), "n"(TB));
}
template <int SA, int TB>
__device__ __forceinline__ void wgmma_rs_n64(float (&d)[32], uint32_t a0, uint32_t a1, uint32_t a2, uint32_t a3, uint64_t db, int sd) {
  asm volatile("{\n.reg .pred p;\nsetp.ne.b32 p, %37, 0;\n"
      "wgmma.mma_async.sync.aligned.m64n64k16.f32.bf16.bf16 {"
      "%0, %1, %2, %3, %4, %5, %6, %7, %8, %9, %10, %11, %12, %13, %14, %15, %16, %17, %18, %19, %20, %21, %22, %23, "
      "%24, %25, %26, %27, %28, %29, %30, %31"
      "}, {%32, %33, %34, %35}, %36, p, %38, 1, %39;\n}\n"
      : "+f"(d[0]), "+f"(d[1]), "+f"(d[2]), "+f"(d[3]), "+f"(d[4]), "+f"(d[5]), "+f"(d[6]), "+f"(d[7]), "+f"(d[8]),
        "+f"(d[9]), "+f"(d[10]), "+f"(d[11]), "+f"(d[12]), "+f"(d[13]), "+f"(d[14]), "+f"(d[15]), "+f"(d[16]),
        "+f"(d[17]), "+f"(d[18]), "+f"(d[19]), "+f"(d[20]), "+f"(d[21]), "+f"(d[22]), "+f"(d[23]), "+f"(d[24]),
        "+f"(d[25]), "+f"(d[26]), "+f"(d[27]), "+f"(d[28]), "+f"(d[29]), "+f"(d[30]), "+f"(d[31])
      : "r"(a0), "r"(a1), "r"(a2), "r"(a3), "l"(db), "r"(sd), "n"(SA), "n"(TB));
}

__device__ __forceinline__ uint32_t BAR_FULL(uint32_t sb, int i) { return sb + SM_BAR + 8 * i; }
__device__ __forceinline__ uint32_t BAR_EMPTY(uint32_t sb, int i) { return sb + SM_BAR + 64 + 8 * i; }
__device__ __forceinline__ uint32_t BAR_X(uint32_t sb, int i) { return sb + SM_BAR + 128 + 8 * i; }
__device__ __forceinline__ uint32_t BAR_Y(uint32_t sb, int i) { return sb + SM_BAR + 192 + 8 * i; }
__device__ __forceinline__ uint32_t BAR_XFREE(uint32_t sb) { return sb + SM_BAR + 256; }

__device__ __forceinline__ uint32_t BAR_E2(uint32_t sb, int i) { return sb + SM_BAR + 264 + 8 * i; }
#define CMASK 0xd4u
#define XORDER 0, 1, 11, 2, 3, 12, 13, 4, 5, 14, 6, 15, 16
#define XSPREAD 4
#define PFAT 3
#define SKEW 3
#define EQW 38
#define EQA 37
#define GL4 6
#define GS0 2
#define GL2 6
#define GS1 4
constexpr int Q_G1B = 18, Q_G2 = 32, Q_XR = 39, Q_P3 = 46, Q_END = 50;

__device__ __forceinline__ uint32_t y_addr(int kb) { return kb < 3 ? SM_RING + (kb + (Q_G2 + 4) % NSTAGE) * STAGE_BYTES : SM_X + (kb - 3) * 16384; }
static_assert((Q_G2 + 4) % NSTAGE + 2 < NSTAGE, "");

struct Ring {
  uint32_t slot, phase;
  __device__ __forceinline__ void next() { if (++slot == NSTAGE) { slot = 0; phase ^= 1; } }
};

__device__ __forceinline__ void release_slot(uint32_t sb, uint32_t slot, int tid, int times) {
  if (tid < 2 * times) mbar_arrive_cluster(BAR_EMPTY(sb, slot), tid & 1);
}

__device__ __forceinline__ void ffn_consumer(uint32_t sb, const uint8_t* smem, const Params& p, int bid, int wg, int tid, int mt, int jj) {
  const int lane = tid & 31, warp = tid >> 5, q = lane & 3, r0 = 16 * warp + (lane >> 2);
  uint32_t* const my_epoch = &p.s->epoch[blockIdx.x * 12 + (threadIdx.x >> 5)];
  const uint32_t epoch = ld_relaxed(my_epoch) + 1;
  Ring rg{0, 0};
  uint32_t u[64];
  float acc[128];
  uint32_t prev = 0, cmask = CMASK;
  int st = 0;
  auto g1_stage = [&](uint32_t slot, int s) {
    const uint64_t da = mk_desc(sb + SM_X + (s >> 1) * 16384 + wg * 8192 + (s & 1) * 64, 16, 1024, 1);
    const uint64_t db = mk_desc(sb + SM_RING + slot * STAGE_BYTES, 4096, 1024, 1);
    wg_fence();
    wgmma_ss_n256<0, 1>(acc, da, db, s != 0);
    wgmma_ss_n256<0, 1>(acc, da + 2, db + 128, 1);
    wg_commit();
  };
  if (wg == 1) {
    float ap[64];
    constexpr int QX = 32 - __builtin_clz(CMASK);
    constexpr int NPRE = QX + XSPREAD;
    uint4* const x1dst = p.s->x1t + ((64 * jj + r0 + 8) >> 2) * 1024 + (r0 & 3) * 128 + 8 * mt + (q ^ (mt & 3));
    const int x1lo = 64 * jj + r0 == 1 ? 110 * 1024 - 128 : -2048;
#pragma unroll
    for (int qi = 0; qi < NPRE; qi++) {
      const int slot = qi % NSTAGE, nc = __builtin_popcount(CMASK & ((1u << qi) - 1));
      if (qi == 0) TL(60);
      mbar_wait(BAR_FULL(sb, slot), (qi / NSTAGE) & 1);
      if (qi == 0) TL(61);
      if ((CMASK >> qi) & 1) {
#pragma unroll
        for (int kb = 2 * nc; kb < 2 * nc + 2 && kb < 7; kb++) {
          const uint64_t da = mk_desc(sb + SM_RING + slot * STAGE_BYTES + (kb & 1) * 8192, 8192, 1024, 1);
          const uint64_t db = mk_desc(sb + SM_X + kb * 16384, 16, 1024, 1);
          mbar_wait(BAR_X(sb, kb), 0);
          TL(16 + kb);
          wg_fence();
#pragma unroll
          for (int kk = 0; kk < 4; kk++) wgmma_ss_n128<1, 0>(ap, da + kk * 128, db + kk * 2, (kb | kk) != 0);
          wg_commit();
        }
      } else {
        if (((qi - nc) & 1) == 0 && qi - nc >= 4 * nc) mbar_wait(BAR_X(sb, (qi - nc) >> 1), 0);
        TL(32 + qi - nc);
        g1_stage(slot, qi - nc);
      }
      if (qi > 0) {
        wg_wait<1>();
        release_slot(sb, (qi - 1) % NSTAGE, tid, ((CMASK >> (qi - 1)) & 1) ? 2 : 1);
      }
      if (qi >= QX) {
        if (qi == QX) { fence_regs(ap); TL(2); }
#pragma unroll
        for (int t = (qi - QX) * (4 / XSPREAD); t < (qi - QX + 1) * (4 / XSPREAD); t++)
#pragma unroll
        for (int h = 0; h < 2; h++)
          x1dst[(h ? 0 : x1lo) + 512 * (t & 1) + 4 * (t >> 1)] = make_uint4((pack2(ap[16 * t + 2 * h], ap[16 * t + 2 * h + 1]) & ~1u) | (epoch & 1), pack2(ap[16 * t + 4 + 2 * h], ap[16 * t + 5 + 2 * h]),
                                             pack2(ap[16 * t + 8 + 2 * h], ap[16 * t + 9 + 2 * h]), pack2(ap[16 * t + 12 + 2 * h], ap[16 * t + 13 + 2 * h]));
      }
    }
    bar_arrive(7, 160);
    st = NPRE - 4; cmask = 0; prev = (NPRE - 1) % NSTAGE;
    rg.slot = NPRE % NSTAGE; rg.phase = (NPRE / NSTAGE) & 1;
  }
#pragma unroll 1
  for (int pass = 0; pass < 2; pass++) {
#pragma unroll 1
    for (; st < 14; st++) {
      while (cmask & 1) { cmask >>= 1; rg.next(); }
      cmask >>= 1;
      if (pass == 0 && (st & 1) == 0) mbar_wait(BAR_X(sb, st >> 1), 0);
      if (st == 14 - SKEW && wg == 1) bar_sync(9 + pass, 256);
      mbar_wait(BAR_FULL(sb, rg.slot), rg.phase);
      TL(32 + 14 * pass + st);
      g1_stage(rg.slot, st);
      wg_wait<1>();
      if (st > 0) release_slot(sb, prev, tid, 1);
      prev = rg.slot;
      rg.next();
    }
    st = 0;
    if (wg == 0) bar_arrive(9 + pass, 256);
    wg_wait<0>();
    fence_regs(acc);
    release_slot(sb, prev, tid, 1);
    TL(3 + 2 * pass);
#pragma unroll
    for (int i = 0; i < 32; i++) {
      const float g0 = 0.5f * acc[2 * i], g1 = 0.5f * acc[2 * i + 1];
      const float s0 = fmaf(g0, tanh_fast(g0), g0), s1 = fmaf(g1, tanh_fast(g1), g1);
      u[32 + i] = pack2(s0 * acc[64 + 2 * i], s1 * acc[64 + 2 * i + 1]);
    }
    if (pass == 0) {
#pragma unroll
      for (int i = 0; i < 32; i++) u[i] = u[32 + i];
    }
    TL(4 + 2 * pass);
  }
  fence_regs(u);
  float accA[32], accB[32];
  auto stage = [&](float (&acc)[32], int qi) {
    const int st = qi & 1;
    if (qi == EQW && wg == 0) bar_sync(1, 256);
    if (qi < Q_XR) mbar_wait(BAR_FULL(sb, qi % NSTAGE), (qi / NSTAGE) & 1);
    else mbar_wait(BAR_X(sb, qi - Q_XR), 1);
    const uint64_t db = mk_desc(sb + (qi < Q_XR ? SM_RING + (qi % NSTAGE) * STAGE_BYTES : SM_X + (qi - Q_XR) * 16384), 8192, 1024, 1);
    wg_fence();
#pragma unroll
    for (int kk = 0; kk < 8; kk++) {
      const uint32_t* a = u + 32 * st + 4 * kk;
      wgmma_rs_n64<1, 1>(acc, a[0], a[1], a[2], a[3], db + kk * 128, (st | kk) != 0);
    }
    wg_commit();
    if (qi == EQA && wg == 1) bar_arrive(1, 256);
  };
  auto retire = [&](int qi) {
    wg_wait<1>();
    if (qi >= Q_G2 && qi < Q_G2 + 4) release_slot(sb, qi % NSTAGE, tid, 1);
    else if (qi >= Q_G2 + 4 && qi < Q_G2 + 11 && tid == 0) mbar_arrive(BAR_E2(sb, qi - Q_G2 - 4));
  };
  const uint32_t par = epoch & 1;
  auto put = [&](float (&acc)[32], int c) {
    fence_regs(acc);
    int o = jj + 1 + c;
    if (o >= 7) o -= 7;
    uint4* dst = p.s->part + ((((mt * 7 + o) * 6 + c) * 2 + wg) * 4) * 128 + tid;
#pragma unroll
    for (int v = 0; v < 4; v++) {
      const float* a = acc + 8 * v;
      st_relaxed(dst + v * 128, make_uint4((pack2(a[0], a[1]) & ~1u) | par, pack2(a[2], a[3]), pack2(a[4], a[5]), pack2(a[6], a[7])));
    }
  };
  const uint4* const src = p.s->part + (((mt * 7 + jj) * 6 * 2 + wg) * 4) * 128 + tid;
  auto gload = [&](uint4 (&pv)[8], int c) {
#pragma unroll
    for (int i = 0; i < 8; i++) pv[i] = ld_relaxed(src + ((2 * c + (i >> 2)) * 8 + (i & 3)) * 128);
  };
  auto gload1 = [&](uint4 (&pv)[8], int c) {
#pragma unroll
    for (int i = 0; i < 4; i++) pv[4 * (c & 1) + i] = ld_relaxed(src + (c * 8 + i) * 128);
  };
  auto gsum = [&](uint4 (&pv)[8], int c, float s0, float s1) {
#pragma unroll 1
    for (uint32_t n = 0; n < SPIN_LIMIT; n++) {
      uint32_t bad = 0;
#pragma unroll
      for (int i = 0; i < 8; i++) bad |= pv[i].x ^ par;
      if (!__any_sync(0xffffffffu, bad & 1)) break;
      gload(pv, c);
    }
    TL(24 + c);
#pragma unroll
    for (int i = 0; i < 4; i++) {
      const uint32_t w[4] = {add2(pv[i].x, pv[4 + i].x), add2(pv[i].y, pv[4 + i].y), add2(pv[i].z, pv[4 + i].z), add2(pv[i].w, pv[4 + i].w)};
#pragma unroll
      for (int k = 0; k < 4; k++) {
        const float s = (k & 1) ? s1 : s0;
        accA[8 * i + 2 * k] = fmaf(s, bf_lo(w[k]), accA[8 * i + 2 * k]); accA[8 * i + 2 * k + 1] = fmaf(s, bf_hi(w[k]), accA[8 * i + 2 * k + 1]);
      }
    }
  };
  uint4 pv0[8], pv1[8], pv2[8];
  const int row = 128 * mt + 64 * wg + r0;
  uint32_t gt0, gt1;
#pragma unroll
  for (int c2 = 0; c2 < 4; c2++) {
    const int qi = Q_G2 + 4 * c2;
    stage(accA, qi);
    retire(qi - 1);
    stage(accA, qi + 1);
    if (c2 == 3) TL(27);
    if (c2 > 0) put(accB, 2 * c2 - 1);
    if (c2 == 2) gload1(pv0, 1);
    if (c2 == 3) gload1(pv1, 3);
    TL(7 + c2);
    if (c2 == 3) break;
    retire(qi);
    stage(accB, qi + 2);
    retire(qi + 1);
    stage(accB, qi + 3);
    put(accA, 2 * c2);
    if (c2 == 1) gload1(pv0, 0);
    if (c2 == 2) gload1(pv1, 2);
    if (c2 == 0) { gt0 = ld_relaxed(&p.s->gate[row]); gt1 = ld_relaxed(&p.s->gate[row + 8]); }
    retire(qi + 2);
  }
#pragma unroll
  for (int kb = 0; kb < 7; kb++) {
    const int qt = Q_XR + (kb >> 1);
    if ((kb & 1) == 0) mbar_wait(BAR_FULL(sb, qt % NSTAGE), (qt / NSTAGE) & 1);
    mbar_wait(BAR_Y(sb, kb), 0);
    const uint64_t da = mk_desc(sb + y_addr(kb) + wg * 8192, 8192, 1024, 1);
    const uint64_t db = mk_desc(sb + SM_RING + (qt % NSTAGE) * STAGE_BYTES + (kb & 1) * 8192, 16, 1024, 1);
    wg_fence();
#pragma unroll
    for (int kk = 0; kk < 4; kk++) wgmma_ss_n64<1, 0>(accB, da + kk * 128, db + kk * 2, (kb | kk) != 0);
    wg_commit();
    if (kb == 1) { wg_wait<2>(); fence_regs(accA); TL(15); }
    if (kb == GS0) gsum(pv0, 0, 1.f, 1.f);
    if (kb == GL4) gload1(pv2, 4);
    if (kb == GL2) gload1(pv2, 5);
    if (kb == GS1) gsum(pv1, 1, 1.f, 1.f);
  }
  TL(11);
  for (uint32_t n = 0; (((gt0 ^ epoch) | (gt1 ^ epoch)) & 0xffffu) && n < SPIN_LIMIT; n++) {
    gt0 = ld_relaxed(&p.s->gate[row]); gt1 = ld_relaxed(&p.s->gate[row + 8]);
  }
  const float ga0 = bf_hi(gt0), ga1 = bf_hi(gt1);
  const float gb0 = bf_round(1.f - ga0), gb1 = bf_round(1.f - ga1);
  const float gs0 = ga0 * (2.f / (float)(S_ * D_)), gs1 = ga1 * (2.f / (float)(S_ * D_));
  wg_wait<0>();
  fence_regs(accB);
#pragma unroll
  for (int i = 0; i < 32; i++) accA[i] = (i & 2) ? fmaf(gs1, accB[i], gb1 * accA[i]) : fmaf(gs0, accB[i], gb0 * accA[i]);
  fence_regs(accA);
  TL(12);
  gsum(pv2, 2, gb0, gb1);
  TL(13);
  uint4* const o = reinterpret_cast<uint4*>(p.out + (size_t)row * D_ + 64 * jj + 8 * q);
#pragma unroll
  for (int h = 0; h < 2; h++) {
#pragma unroll
    for (int k = 0; k < 2; k++) {
      uint32_t w[4];
#pragma unroll
      for (int j = 0; j < 4; j++) {
        const int i = 16 * k + 4 * j + 2 * h;
        w[j] = pack2(accA[i], accA[i + 1]);
      }
      const bool o1 = q & 1, o2 = q & 2;
      uint32_t a = __shfl_xor_sync(0xffffffffu, o1 ? w[0] : w[1], 1), b = __shfl_xor_sync(0xffffffffu, o1 ? w[2] : w[3], 1);
      if (o1) { w[0] = a; w[2] = b; } else { w[1] = a; w[3] = b; }
      a = __shfl_xor_sync(0xffffffffu, o2 ? w[0] : w[2], 2); b = __shfl_xor_sync(0xffffffffu, o2 ? w[1] : w[3], 2);
      if (o2) { w[0] = a; w[1] = b; } else { w[2] = a; w[3] = b; }
      o[h * D_ + 4 * k] = make_uint4(w[0], w[1], w[2], w[3]);
    }
  }
  if (lane == 0) *my_epoch = epoch;
  TL(14);
}

__device__ __forceinline__ void ring_issue(uint32_t sb, const Params& p, int qi, uint32_t slot, bool wait, uint32_t phase, int jj, uint32_t rank) {
  const CUtensorMap* m;
  int c0, c1, c2 = 0;
  bool half = false, is3d = false;
  if (qi < Q_G2) {
    const int nc = __popc(CMASK & ((1u << qi) - 1));
    if ((CMASK >> qi) & 1) {
      m = &p.ct; c0 = 64 * jj; c1 = 128 * nc + 64 * rank; half = nc == 3;
    } else {
      const int pass = qi >= Q_G1B;
      m = rank ? &p.wu : &p.wg; c0 = 0; c1 = 32 * (qi - nc - 14 * pass); c2 = 4 * jj + 2 * pass; is3d = true;
    }
  } else if (qi < Q_P3) {
    int o = jj + 1 + ((qi - Q_G2) >> 1);
    if (o >= 7) o -= 7;
    m = &p.wd; c0 = 64 * o; c1 = 256 * jj + 128 * (qi & 1) + 64 * rank;
  } else {
    m = &p.ct; c0 = 128 * (qi - Q_P3) + 64 * rank; c1 = 64 * jj; half = qi == Q_END - 1;
  }
  uint32_t bar = BAR_FULL(sb, slot), dst = sb + SM_RING + slot * STAGE_BYTES + rank * 8192;
  if (qi >= Q_XR && qi < Q_P3) {
    bar = BAR_X(sb, qi - Q_XR); dst = sb + SM_X + (qi - Q_XR) * 16384 + rank * 8192;
    if (qi == Q_XR) mbar_wait_cluster(BAR_XFREE(sb), 0);
  } else {
    if (wait) mbar_wait_cluster(BAR_EMPTY(sb, slot), phase ^ (qi >= Q_P3));
    mbar_expect_tx(bar, half ? 8192 : 16384);
  }
  if (is3d) tma3d_mc(dst, m, c0, c1, c2, bar);
  else if (!(half && rank)) tma2d_mc(dst, m, c0, c1, bar);
}

__device__ __forceinline__ void ffn_producer(uint32_t sb, const uint8_t* smem, int bid, const Params& p, int warp, int lane, int mt, int jj, uint32_t rank) {
  if (warp < 2) {
    if (lane == 0) {
      uint32_t slot = warp, phase = 0;
#pragma unroll 1
      for (int qi = NSTAGE + warp; qi < Q_END; qi += 2) {
        if (qi < Q_XR || qi >= Q_P3) ring_issue(sb, p, qi, slot, true, phase, jj, rank);
        if (warp == 1 && qi >= Q_G1B + 8 && qi < Q_XR) ring_issue(sb, p, Q_XR + ((qi - Q_G1B - 8) >> 1), 0, false, 0, jj, rank);
        TL(10 + qi);
        slot += 2;
        if (slot >= NSTAGE) { slot -= NSTAGE; phase ^= 1; }
      }
    }
  } else {
    const int wg = warp - 2;
    uint32_t* const my_epoch = &p.s->epoch[blockIdx.x * 12 + 8 + warp];
    const uint32_t epoch = ld_relaxed(my_epoch) + 1;
    if (wg == 0) {
      if (lane == 0) { prefetch_tmap(&p.wd); prefetch_tmap(&p.yt); }
      {
        const uint4* gw4 = reinterpret_cast<const uint4*>(p.gate_w);
        const uint4 ga = __ldg(gw4 + lane), gb = lane < 24 ? __ldg(gw4 + 32 + lane) : make_uint4(0, 0, 0, 0);
        if (lane < 7) { mbar_wait(BAR_X(sb, lane), 0); mbar_expect_tx(BAR_X(sb, lane), 16384); mbar_expect_tx(BAR_Y(sb, lane), 16384); }
        __syncwarp();
        float mine = 0.f;
#pragma unroll 1
        for (int u = 0; u < 19; u++) {
          const int r = min(19 * jj + u, 127);
          const uint8_t* xr = smem + SM_X + (lane >> 3) * 16384 + r * 128 + (((lane ^ r) & 7) << 4);
          const uint4 xa = *reinterpret_cast<const uint4*>(xr);
          const uint4 xb = lane < 24 ? *reinterpret_cast<const uint4*>(xr + 65536) : make_uint4(0, 0, 0, 0);
          float s = 0.f;
          auto dot2 = [&](uint32_t a, uint32_t b) {
            const uint32_t pr = mul2(a, b);
            s += bf_lo(pr) + bf_hi(pr);
          };
          dot2(xa.x, ga.x); dot2(xa.y, ga.y); dot2(xa.z, ga.z); dot2(xa.w, ga.w);
          dot2(xb.x, gb.x); dot2(xb.y, gb.y); dot2(xb.z, gb.z); dot2(xb.w, gb.w);
#pragma unroll
          for (int o = 16; o > 0; o >>= 1) s += __shfl_xor_sync(0xffffffffu, s, o);
          if (lane == u) mine = s;
        }
        if (lane < 19 && 19 * jj + lane < 128)
          st_relaxed(&p.s->gate[128 * mt + 19 * jj + lane], pack2(0.f, 1.f / (1.f + __expf(-bf_round(mine)))) | (epoch & 0xffffu));
      }
      TL(9);
      if (lane < 2) mbar_arrive_cluster(BAR_XFREE(sb), lane);
    } else {
      mbar_wait(BAR_X(sb, PFAT), 0);
      if (lane < 6) {
        int row = 176 + 3 * bid + (lane >> 1);
        if (row >= D_) row -= D_;
        l2_prefetch(((lane & 1) ? p.pwu : p.pwg) + row * F_, F_ * 2);
      }
      TL(2);
      bar_sync(7, 160);
      if (lane == 0) { red_add(&p.s->cnt_x1[jj * 32], 1);
        l2_prefetch(p.pwd + bid * 16 * D_, 32 * D_); }
      TL(5);
    }
    mbar_wait(BAR_E2(sb, 0), 0);
    TL(3);
    const int kb = 2 * lane + wg;
    bool todo = kb < 7, ready = false;
    uint32_t n = 0;
    while (__any_sync(0xffffffffu, todo)) {
      if (todo) {
        uint32_t ok;
        if (!ready) {
          asm volatile("ld.acquire.gpu.global.u32 %0, [%1];" : "=r"(ok) : "l"(&p.s->cnt_y[kb * 32]) : "memory");
          ready = (int32_t)(ok - epoch * (kb ? 16 : 17)) >= 0;
        }
        asm volatile("{\n.reg .pred p;\nmbarrier.test_wait.parity.shared::cta.b64 p, [%1], 0;\nselp.u32 %0, 1, 0, p;\n}"
                     : "=r"(ok) : "r"(BAR_E2(sb, kb)) : "memory");
        if ((ok && ready) || ++n > SPIN_LIMIT) {
          tma3d(sb + y_addr(kb), &p.yt, 0, 64 * kb, 2 * mt, BAR_Y(sb, kb));
          todo = false;
        }
      }
      __nanosleep(40);
    }
    TL(4);
    if (lane == 0) *my_epoch = epoch;
  }
}

__device__ __forceinline__ void spectral_cta(uint32_t sb, uint8_t* smem, const Params& p, int sc, int wg) {
  const int t384 = threadIdx.x, lane = t384 & 31, warp12 = t384 >> 5, tid = t384 & 127;
  const int warp = tid >> 5, q = lane & 3;
  const int sl0 = 6 * sc + min(sc, 8), nsl = sc < 8 ? 7 : 6;
  if (t384 == 320) {
#pragma unroll 1
    for (int i = 0; i < nsl; i++) {
      mbar_expect_tx(BAR_X(sb, i), 2 * SLAB_BYTES);
      const int row = 128 * ((sl0 + i) >> 3) + 8 * ((sl0 + i) & 7);
      const uint32_t dst = sb + SP_Z + 2 * i * SLAB_BYTES;
      bulk_g2s(dst, p.w_r + row * DF_, SLAB_BYTES / 2, BAR_X(sb, i));
      bulk_g2s(dst + SLAB_BYTES / 2, p.w_r + (row + 64) * DF_, SLAB_BYTES / 2, BAR_X(sb, i));
      bulk_g2s(dst + SLAB_BYTES, p.w_i + row * DF_, SLAB_BYTES / 2, BAR_X(sb, i));
      bulk_g2s(dst + 3 * SLAB_BYTES / 2, p.w_i + (row + 64) * DF_, SLAB_BYTES / 2, BAR_X(sb, i));
    }
  } else if (t384 == 352 && sc < 19) {
    mbar_expect_tx(BAR_Y(sb, 6), 24576);
    bulk_g2s(sb + SP_TW, p.spec, 24576, BAR_Y(sb, 6));
  }
  uint32_t* const my_epoch = &p.s->epoch[blockIdx.x * 12 + warp12];
  const uint32_t epoch = ld_relaxed(my_epoch) + 1;
  uint32_t fe[16], tw[16];
#pragma unroll
  for (int i = 0; i < 4; i++) {
    const uint4 a = __ldg(reinterpret_cast<const uint4*>(p.spec->fe) + i * 128 + tid);
    const uint4 b = __ldg(reinterpret_cast<const uint4*>(p.spec->tw) + i * 128 + tid);
    fe[4 * i] = a.x; fe[4 * i + 1] = a.y; fe[4 * i + 2] = a.z; fe[4 * i + 3] = a.w;
    tw[4 * i] = b.x; tw[4 * i + 1] = b.y; tw[4 * i + 2] = b.z; tw[4 * i + 3] = b.w;
  }
  __syncwarp();
  asm volatile("barrier.cluster.wait.acquire.aligned;" ::: "memory");
#pragma unroll 2
  for (int un = wg; un < 8 * nsl; un += 3) {
    const int i = un >> 3, sl = sl0 + i, pr = 16 * (un & 7) + 4 * (lane >> 3) + warp, r = lane & 7;
    mbar_wait(BAR_X(sb, i), 0);
    if (pr < 113) {
      const uint16_t* w = reinterpret_cast<const uint16_t*>(smem + SP_Z + 2 * i * SLAB_BYTES) + r * DF_ + 2 * pr;
      const uint32_t m = pr < 112 ? 0xffffffffu : 0u;
      p.s->wt[pr * 1024 + sl * 8 + (r ^ ((sl >> 2) & 6))] =
          make_uint4(w[0] | ((uint32_t)w[8 * DF_] << 16), w[16 * DF_] | ((uint32_t)w[24 * DF_] << 16),
                     (w[1] | ((uint32_t)w[8 * DF_ + 1] << 16)) & m, (w[16 * DF_ + 1] | ((uint32_t)w[24 * DF_ + 1] << 16)) & m);
    }
  }
  __syncthreads();
  if (t384 == 352) { fence_gpu(); red_add(&p.s->cnt_w[0], 1); TL(2); }
  TL(1);
  if (sc == 19) return;
  const int nrnd = (sc == 18 && wg == 2) ? 1 : 2;
  auto pair_of = [&](int r) { const int i = 3 * sc + wg + 57 * r; return i ? i - 1 : 112; };
  auto fetch = [&]() {
    const int item = wg + 3 * lane, pr = pair_of(lane);
    const uint32_t bar = warp ? BAR_Y(sb, item) : BAR_FULL(sb, item);
    mbar_expect_tx(bar, 16384);
    wait_counter(warp ? &p.s->cnt_w[0] : &p.s->cnt_x1[(pr < 112 ? pr >> 4 : 0) * 32], epoch * (warp ? NSPEC : 16));
    if (warp) fence_async();
    bulk_g2s(sb + (warp ? SP_W : SP_Z) + item * 16384, (warp ? p.s->wt : p.s->x1t) + pr * 1024, 16384, bar);
  };
  if (lane < nrnd && warp == 0) fetch();
  __syncwarp();
  fence_regs(fe); fence_regs(tw);
  mbar_wait(BAR_Y(sb, 6), 0);
  TL(3);
  const uint64_t dT_n = mk_desc(sb + SP_T, 8192, 1024, 1);
#pragma unroll 1
  for (int rnd = 0; rnd < nrnd; rnd++) {
    const int item = wg + 3 * rnd, pr = pair_of(rnd);
    const uint32_t z = sb + SP_Z + item * 16384;
    uint32_t fa[16], fb[16];
    auto load_frag = [&](int off) {
#pragma unroll
      for (int i = 0; i < 4; i++) {
        const uint4 a = *reinterpret_cast<const uint4*>(smem + SP_TW + off + i * 2048 + tid * 16);
        fa[4 * i] = a.x; fa[4 * i + 1] = a.y; fa[4 * i + 2] = a.z; fa[4 * i + 3] = a.w;
      }
      fence_regs(fa);
    };
    load_frag(0);
    {
      const uint32_t live = pr == 0 ? 0xddu : (pr == 112 ? 0x11u : 0xffu);
#pragma unroll 1
      for (uint32_t n = 0; n < 4096; n++) {
        mbar_wait(BAR_FULL(sb, item), n & 1);
        uint32_t bad = 0;
#pragma unroll
        for (int i = 0; i < 8; i++) bad |= ((*reinterpret_cast<const volatile uint32_t*>(smem + SP_Z + item * 16384 + i * 2048 + tid * 16) ^ epoch) & 1) << i;
        uint32_t again;
        asm volatile("{\n.reg .pred p, q;\nsetp.ne.u32 p, %1, 0;\nbarrier.red.or.pred q, %2, 128, p;\nselp.u32 %0, 1, 0, q;\n}"
                     : "=r"(again) : "r"(bad & live), "r"(1 + wg) : "memory");
        if (!again) break;
        TL(20);
        if (tid == 0) { mbar_expect_tx(BAR_FULL(sb, item), 16384); bulk_g2s(z, p.s->x1t + pr * 1024, 16384, BAR_FULL(sb, item)); }
      }
    }
    TL(4 + 8 * rnd);
    if (rnd == 0 && wg > 0) bar_sync(3 + wg, 256);
    float aR[32], aI[32];
    {
      const uint64_t de = mk_desc(z, 4096, 512, 2);
      wg_fence();
#pragma unroll
      for (int kk = 0; kk < 4; kk++) {
        wgmma_rs_n64<1, 1>(aR, fe[4 * kk], fe[4 * kk + 1], fe[4 * kk + 2], fe[4 * kk + 3], de + kk * 64, kk != 0);
        wgmma_rs_n64<1, 1>(aI, fa[4 * kk], fa[4 * kk + 1], fa[4 * kk + 2], fa[4 * kk + 3], de + 512 + kk * 64, kk != 0);
      }
      wg_commit();
      if (rnd == 0 && wg < 2) bar_arrive(4 + wg, 256);
      if (rnd == 0 && lane < nrnd && warp == 1) fetch();
      __syncwarp();
      wg_wait<0>();
      fence_regs(aR); fence_regs(aI);
    }
    TL(5 + 8 * rnd);
#pragma unroll
    for (int v = 0; v < 8; v++) {
      uint32_t* f = (v < 4 ? fa : fb) + 2 * (v & 3);
      const uint32_t* t = tw + 2 * (v & 3);
      const float *e = aR + 4 * v, *o = aI + 4 * v;
      const uint32_t er = pack2(e[0], e[1]), ei = pack2(e[2], e[3]), qr = pack2(o[0], o[1]), qi = pack2(o[2], o[3]);
      const uint32_t u0r = add2(er, qr), u0i = add2(ei, qi), u1r = sub2(er, qr), u1i = sub2(ei, qi);
      f[0] = fma2(u0r, t[0], mul2(u0i, t[8]));
      f[8] = fms2(u0i, t[0], mul2(u0r, t[8]));
      f[1] = fma2(u1r, t[1], mul2(u1i, t[9]));
      f[9] = fms2(u1i, t[1], mul2(u1r, t[9]));
    }
    fence_regs(fa); fence_regs(fb);
    wg_fence();
#pragma unroll
    for (int kk = 0; kk < 4; kk++) {
      wgmma_rs_n64<1, 1>(aR, fa[4 * kk], fa[4 * kk + 1], fa[4 * kk + 2], fa[4 * kk + 3], dT_n + kk * 128, kk != 0);
      wgmma_rs_n64<1, 1>(aI, fb[4 * kk], fb[4 * kk + 1], fb[4 * kk + 2], fb[4 * kk + 3], dT_n + kk * 128, kk != 0);
    }
    wg_commit();
    if (rnd == 1 && tid == 0) {
      asm volatile("cp.async.bulk.wait_group 0;" ::: "memory");
      red_add(&p.s->cnt_y[(max(pr - 57, 0) >> 4) * 32], 1);
    }
    __syncwarp();
    mbar_wait(BAR_Y(sb, item), 0);
    wg_wait<0>();
    fence_regs(aR); fence_regs(aI);
    TL(6 + 8 * rnd);
    {
      const uint8_t* wp = smem + SP_W + item * 16384 + q * 1024 + warp * 128 + (((lane >> 2) ^ (2 * q)) << 4);
#pragma unroll
      for (int jb = 0; jb < 4; jb++) {
#pragma unroll
        for (int h = 0; h < 2; h++) {
          const uint4 w = *reinterpret_cast<const uint4*>(wp + jb * 4096 + h * 512);
          const int i = 4 * jb + 2 * h;
          const uint32_t ar = pack2(aR[i], aR[i + 1]), ai = pack2(aR[16 + i], aR[17 + i]);
          const uint32_t br = pack2(aI[i], aI[i + 1]), bi = pack2(aI[16 + i], aI[17 + i]);
          fa[2 * jb + h] = fms2(ar, w.x, mul2(ai, w.y));
          fa[8 + 2 * jb + h] = fma2(ar, w.y, mul2(ai, w.x));
          fb[2 * jb + h] = fms2(br, w.z, mul2(bi, w.w));
          fb[8 + 2 * jb + h] = fma2(br, w.w, mul2(bi, w.z));
        }
      }
    }
    fence_regs(fa); fence_regs(fb);
    wg_fence();
#pragma unroll
    for (int kk = 0; kk < 4; kk++) {
      wgmma_rs_n64<1, 0>(aR, fa[4 * kk], fa[4 * kk + 1], fa[4 * kk + 2], fa[4 * kk + 3], dT_n + kk * 2, kk != 0);
      wgmma_rs_n64<1, 0>(aI, fb[4 * kk], fb[4 * kk + 1], fb[4 * kk + 2], fb[4 * kk + 3], dT_n + kk * 2, kk != 0);
    }
    wg_commit();
    wg_wait<0>();
    fence_regs(aR); fence_regs(aI);
    TL(7 + 8 * rnd);
#pragma unroll
    for (int v = 0; v < 8; v++) {
      const float* a = (v < 4 ? aR : aI) + 4 * (v & 3);
      const uint32_t* t = tw + 2 * (v & 3);
      const uint32_t u0r = pack2(a[0], a[1]), u1r = pack2(a[2], a[3]), u0i = pack2(a[16], a[17]), u1i = pack2(a[18], a[19]);
      const uint32_t t0r = fms2(u0r, t[0], mul2(u0i, t[8])), t0i = fma2(u0i, t[0], mul2(u0r, t[8]));
      const uint32_t t1r = fms2(u1r, t[1], mul2(u1i, t[9])), t1i = fma2(u1i, t[1], mul2(u1r, t[9]));
      fa[v] = add2(t0i, t1i); fa[8 + v] = add2(t0r, t1r);
      fb[v] = sub2(t0i, t1i); fb[8 + v] = sub2(t0r, t1r);
    }
    bar_sync(1 + wg, 128);
#pragma unroll
    for (int u = 0; u < 4; u++) {
      const uint32_t a = z + (32 * (u >> 1) + 8 * warp + (lane & 7)) * 128 + (((4 * (u & 1) + (lane >> 3)) ^ (lane & 7)) << 4);
      stmatrix_x4(a, fa[4 * u], fa[4 * u + 1], fa[4 * u + 2], fa[4 * u + 3]);
      stmatrix_x4(a + 8192, fb[4 * u], fb[4 * u + 1], fb[4 * u + 2], fb[4 * u + 3]);
    }
    load_frag(8192);
    fence_async_smem();
    bar_sync(1 + wg, 128);
    TL(8 + 8 * rnd);
    {
      const uint64_t de = mk_desc(z, 8192, 1024, 1);
      wg_fence();
#pragma unroll
      for (int kk = 0; kk < 4; kk++) {
        wgmma_rs_n64<1, 1>(aR, fe[4 * kk], fe[4 * kk + 1], fe[4 * kk + 2], fe[4 * kk + 3], de + kk * 128, kk != 0);
        wgmma_rs_n64<1, 1>(aI, fa[4 * kk], fa[4 * kk + 1], fa[4 * kk + 2], fa[4 * kk + 3], de + 512 + kk * 128, kk != 0);
      }
      wg_commit();
      wg_wait<0>();
      fence_regs(aR); fence_regs(aI);
    }
    TL(9 + 8 * rnd);
    const bool edge = pr == 0 || pr == 112;
    if (edge) {
#pragma unroll
      for (int i = 0; i < 16; i++) { aR[i] *= 0.5f; aI[i] *= 0.5f; }
    }
#pragma unroll
    for (int i = 0; i < 8; i++) {
      const float* a = ((i & 1) ? aI : aR) + 16 * (i >> 2) + 2 - (i & 2);
      *reinterpret_cast<uint4*>(smem + SP_W + item * 16384 + (i >> 1) * 4096 + (i & 1) * 64 + (tid >> 2) * 128 + q * 16) =
          make_uint4(pack2(a[0], a[1]), pack2(a[4], a[5]), pack2(a[8], a[9]), pack2(a[12], a[13]));
    }
    fence_async_smem();
    bar_sync(1 + wg, 128);
    if (tid == 0) {
      const uint32_t src = sb + SP_W + item * 16384;
      __nv_bfloat16* dst = p.s->yt + (size_t)(pr < 112 ? 4 * pr : 1) * S_;
      bulk_s2g(dst, src, edge ? 4096 : 16384);
      if (pr == 0) bulk_s2g(dst + 2 * S_, src + 8192, 8192);
      asm volatile("cp.async.bulk.commit_group;" ::: "memory");
      if (rnd == nrnd - 1) {
        asm volatile("cp.async.bulk.wait_group 0;" ::: "memory");
        TL(11);
        red_add(&p.s->cnt_y[(pr < 112 ? pr >> 4 : 0) * 32], 1);
      }
    }
    __syncwarp();
    TL(10 + 8 * rnd);
  }
  if (lane == 0) *my_epoch = epoch;
}

__global__ void __cluster_dims__(2, 1, 1) __launch_bounds__(384, 1)
fused_kernel(const __grid_constant__ Params p) {
  extern __shared__ __align__(1024) uint8_t smem[];
  const uint32_t sb = smem_u32(smem);
  TL(0);
  const uint32_t rank = blockIdx.x & 1;
  const int hc = blockIdx.x >> 1;
  int grp, jj;
  if (hc < 4) { grp = 8; jj = hc; }
  else if (hc < 36) { grp = (hc - 4) & 7; jj = (hc - 4) >> 3; }
  else if (hc < 57) { jj = (hc - 36) / 7; grp = 1 + (hc - 36) - 7 * jj; jj += 4; }
  else if (hc < 60) { grp = 0; jj = hc - 53; }
  else { grp = 8; jj = hc - 56; }
  const int mt = 2 * grp + rank, bid = 2 * (7 * grp + jj) + rank;
  if (bid < NFFN) {
    const int t = threadIdx.x;
    if (t < 19 && 19 * jj + t < 128) asm volatile("prefetch.global.L2 [%0];" ::"l"(p.px + (128 * mt + 19 * jj + t) * D_));
    if (t >= 128 && t < 136) asm volatile("prefetch.global.L2 [%0];" ::"l"((rank ? p.pwu : p.pwg) + (4 * grp + (t & 3)) * F_ + 256 * jj + 16 * (t & 4)));
  }
  if (threadIdx.x == 256) {
#pragma unroll
    for (int i = 0; i < NSTAGE; i++) { mbar_init(BAR_FULL(sb, i), 1); mbar_init(BAR_EMPTY(sb, i), 4); }
    asm volatile("fence.mbarrier_init.release.cluster;" ::: "memory");
  } else if (threadIdx.x == 320) {
    mbar_init(BAR_X(sb, 0), 1);
    if (bid < NFFN) {
      mbar_expect_tx(BAR_X(sb, 0), 16384);
      tma2d(sb + SM_X, &p.x, 0, 128 * mt, BAR_X(sb, 0));
    }
#pragma unroll
    for (int i = 1; i < NSTAGE; i++) mbar_init(BAR_X(sb, i), 1);
    mbar_init(BAR_XFREE(sb), 2);
    asm volatile("fence.mbarrier_init.release.cluster;" ::: "memory");
  } else if (threadIdx.x == 352) {
#pragma unroll
    for (int i = 0; i < NSTAGE; i++) { mbar_init(BAR_Y(sb, i), 1); mbar_init(BAR_E2(sb, i), 2); }
    asm volatile("fence.mbarrier_init.release.cluster;" ::: "memory");
  } else if (threadIdx.x == 288 && bid < NFFN) {
    prefetch_tmap(rank ? &p.wu : &p.wg); prefetch_tmap(&p.ct);
  }
  __syncwarp();
  asm volatile("barrier.cluster.arrive.relaxed.aligned;" ::: "memory");
  const int wg = __shfl_sync(0xffffffffu, threadIdx.x >> 7, 0);
  if (bid >= NFFN) {
    spectral_cta(sb, smem, p, bid - NFFN, wg);
  } else if (wg < 2) {
    asm volatile("setmaxnreg.inc.sync.aligned.u32 232;");
    asm volatile("barrier.cluster.wait.acquire.aligned;" ::: "memory");
    TL(1);
    ffn_consumer(sb, smem, p, bid, wg, threadIdx.x & 127, mt, jj);
  } else {
    asm volatile("setmaxnreg.dec.sync.aligned.u32 40;");
    asm volatile("barrier.cluster.wait.acquire.aligned;" ::: "memory");
    TL(1);
    if (threadIdx.x == 320) {
      constexpr int order[13] = {XORDER};
#pragma unroll
      for (int i = 0; i < 13; i++) {
        if (order[i] < 8) {
          ring_issue(sb, p, order[i], order[i], false, 0, jj, rank);
        } else {
          const int kb = order[i] - 10;
          mbar_expect_tx(BAR_X(sb, kb), 16384);
          tma2d(sb + SM_X + kb * 16384, &p.x, 64 * kb, 128 * mt, BAR_X(sb, kb));
        }
      }
      TL(2);
    }
    __syncwarp();
    ffn_producer(sb, smem, bid, p, (threadIdx.x >> 5) & 3, threadIdx.x & 31, mt, jj, rank);
  }
}

typedef CUresult (*EncodeFn)(CUtensorMap*, CUtensorMapDataType, cuuint32_t, void*, const cuuint64_t*, const cuuint64_t*,
                             const cuuint32_t*, const cuuint32_t*, CUtensorMapInterleave, CUtensorMapSwizzle,
                             CUtensorMapL2promotion, CUtensorMapFloatOOBfill);

void make_map(EncodeFn fn, CUtensorMap* m, const void* base, int rank, const cuuint64_t* dims, const cuuint64_t* strides,
              const cuuint32_t* box, CUtensorMapSwizzle sw) {
  const cuuint32_t es[4] = {1, 1, 1, 1};
  fn(m, CU_TENSOR_MAP_DATA_TYPE_BFLOAT16, rank, const_cast<void*>(base), dims, strides, box, es,
     CU_TENSOR_MAP_INTERLEAVE_NONE, sw, CU_TENSOR_MAP_L2_PROMOTION_L2_256B, CU_TENSOR_MAP_FLOAT_OOB_FILL_NONE);
}

}

extern "C" void kernel_launch(void* const* d_in, const int* in_sizes, int n_in, void* d_out, int out_size) {
  const __nv_bfloat16* x = (const __nv_bfloat16*)d_in[0];
  const __nv_bfloat16* w_r = (const __nv_bfloat16*)d_in[1];
  const __nv_bfloat16* w_i = (const __nv_bfloat16*)d_in[2];
  const __nv_bfloat16* wg = (const __nv_bfloat16*)d_in[4];
  const __nv_bfloat16* wu = (const __nv_bfloat16*)d_in[5];
  const __nv_bfloat16* wd = (const __nv_bfloat16*)d_in[6];
  const __nv_bfloat16* gate_w = (const __nv_bfloat16*)d_in[7];

  void* fnp = nullptr;
  cudaDriverEntryPointQueryResult qr;
  cudaGetDriverEntryPoint("cuTensorMapEncodeTiled", &fnp, cudaEnableDefault, &qr);
  EncodeFn fn = (EncodeFn)fnp;
  void *ctab, *spec, *scr;
  cudaGetSymbolAddress(&ctab, g_ctab);
  cudaGetSymbolAddress(&spec, g_spec);
  cudaGetSymbolAddress(&scr, g_scratch);
  const void* yt = (const char*)scr + offsetof(Scratch, yt);
  Params p;
  p.s = (Scratch*)scr; p.out = (__nv_bfloat16*)d_out;
  p.px = x; p.w_r = w_r; p.w_i = w_i; p.gate_w = gate_w; p.pwg = wg; p.pwu = wu; p.pwd = wd;
  p.ctab = (const tab::Table*)ctab; p.spec = (const tab::Spec*)spec;
  {
    const cuuint64_t d[2] = {D_, S_}, s[1] = {D_ * 2};
    const cuuint32_t b[2] = {64, 128};
    make_map(fn, &p.x, x, 2, d, s, b, CU_TENSOR_MAP_SWIZZLE_128B);
  }
  {
    const cuuint64_t d[3] = {64, D_, F_ / 64}, s[2] = {F_ * 2, 128};
    const cuuint32_t b[3] = {64, 32, 2};
    make_map(fn, &p.wg, wg, 3, d, s, b, CU_TENSOR_MAP_SWIZZLE_128B);
    make_map(fn, &p.wu, wu, 3, d, s, b, CU_TENSOR_MAP_SWIZZLE_128B);
  }
  {
    const cuuint64_t d[2] = {D_, F_}, s[1] = {D_ * 2};
    const cuuint32_t b[2] = {64, 64};
    make_map(fn, &p.wd, wd, 2, d, s, b, CU_TENSOR_MAP_SWIZZLE_128B);
  }
  {
    const cuuint64_t d[2] = {D_, D_}, s[1] = {D_ * 2};
    const cuuint32_t b[2] = {64, 64};
    make_map(fn, &p.ct, ctab, 2, d, s, b, CU_TENSOR_MAP_SWIZZLE_128B);
  }
  {
    const cuuint64_t d[3] = {64, D_, S_ / 64}, s[2] = {S_ * 2, 128};
    const cuuint32_t b[3] = {64, 64, 2};
    make_map(fn, &p.yt, yt, 3, d, s, b, CU_TENSOR_MAP_SWIZZLE_128B);
  }
  cudaFuncSetAttribute(fused_kernel, cudaFuncAttributeMaxDynamicSharedMemorySize, SM_TOTAL);
  fused_kernel<<<NCTA, 384, SM_TOTAL, cudaStreamPerThread>>>(p, x, w_r, w_i, gate_w, wd, (__nv_bfloat16*)d_out);
}
```

```cpp
#include <cuda_runtime.h>
#include <cuda_bf16.h>
#include <cuda.h>
#include <stdint.h>
#include <stddef.h>

namespace {

constexpr int S_ = 2048, D_ = 448, F_ = 1792, DF_ = 225;
constexpr int NFFN = 112, NSPEC = 20, NCTA = NFFN + NSPEC;
constexpr int NSTAGE = 7, STAGE_BYTES = 16384;
constexpr int SM_X = 0, SM_RING = 114688, SM_BAR = 229376, SM_TOTAL = SM_BAR + 512;
constexpr int SP_Z = 0, SP_W = 98304, SP_TW = 198656, SP_T = 215040, SLAB_BYTES = 16 * DF_ * 2;
constexpr uint32_t SPIN_LIMIT = 1u << 20;

namespace tab {
constexpr double PI = 3.14159265358979323846264338327950288;
constexpr double csin(double x) {
  double t = x, s = x;
  for (int i = 1; i < 20; i++) { t = -t * x * x / ((2 * i) * (2 * i + 1)); s += t; }
  return s;
}
constexpr double ccos(double x) {
  double t = 1, s = 1;
  for (int i = 1; i < 20; i++) { t = -t * x * x / ((2 * i - 1) * (2 * i)); s += t; }
  return s;
}
constexpr uint32_t to_bf16(double v) {
  uint32_t sign = v < 0 ? 0x8000u : 0u;
  double a = v < 0 ? -v : v;
  if (a < 1e-12) return 0;
  int e = 0;
  while (a >= 2.0) { a /= 2; e++; }
  while (a < 1.0) { a *= 2; e--; }
  double m = a * 128.0;
  int mi = (int)m;
  double fr = m - mi;
  if (fr > 0.5 || (fr == 0.5 && (mi & 1))) mi++;
  if (mi == 256) { mi = 128; e++; }
  return sign | (uint32_t)((e + 127) << 7) | (uint32_t)(mi - 128);
}
struct Base { uint32_t v[448]; };
constexpr Base make_base() {
  Base b{};
  for (int m = 0; m < 448; m++) {
    int mm = m > 224 ? m - 448 : m;
    double ang = 2 * PI * mm / 448.0;
    b.v[m] = to_bf16(ccos(ang)) | (to_bf16(-csin(ang)) << 16);
  }
  return b;
}
constexpr Base base = make_base();
struct Row { uint32_t v[224]; };
constexpr Row make_row(int d) {
  Row r{};
  r.v[0] = 0x3f80u | ((d & 1) ? 0xbf800000u : 0x3f800000u);
  int m = 0;
  for (int c = 1; c < 224; c++) { m += d; if (m >= 448) m -= 448; r.v[c] = base.v[m]; }
  return r;
}
struct Table { Row r[448]; };
constexpr Table make_table() {
  Table t{};
  for (int d = 0; d < 448; d++) t.r[d] = make_row(d);
  return t;
}
struct Cs { double c[2048], s[2048]; };
constexpr Cs make_cs() {
  Cs t{};
  for (int m = 0; m <= 256; m++) {
    const double a = 2 * PI * m / 2048.0, c = ccos(a), s = csin(a);
    t.c[m] = c; t.s[m] = s;
    t.c[512 - m] = s; t.s[512 - m] = c;
  }
  for (int m = 513; m < 2048; m++) { t.c[m] = -t.s[m - 512]; t.s[m] = t.c[m - 512]; }
  return t;
}
constexpr Cs cs = make_cs();
struct Spec {
  uint32_t fo[2048], fot[2048];
  uint16_t t32[4096];
  uint32_t fe[2048];
  uint32_t tw[2048];
};
constexpr uint32_t blk(int h, int c, int a) { return to_bf16(h == c ? cs.c[a & 2047] : (h ? -cs.s[a & 2047] : cs.s[a & 2047])); }
constexpr Spec make_spec() {
  Spec t{};
  for (int row = 0; row < 64; row++)
    for (int col = 0; col < 64; col++) {
      const int c = row & 31, k2 = col & 31, n2 = 8 * ((c >> 1) & 3) + 2 * (c >> 3) + (c & 1), m = 64 * ((n2 * k2) & 31);
      const double v = (row >> 5) == (col >> 5) ? cs.c[m] : (row < 32 ? -cs.s[m] : cs.s[m]);
      t.t32[row * 64 + (((col >> 3) ^ (row & 7)) << 3) + (col & 7)] = (uint16_t)to_bf16(v);
    }
  for (int th = 0; th < 128; th++)
    for (int i = 0; i < 16; i++) {
      const int r = 8 * (th >> 5) + ((th & 31) >> 2), h = i & 1, c = i >> 3, m = 8 * ((i >> 1) & 3) + 2 * (th & 3);
      const int o = ((i >> 2) * 128 + th) * 4 + (i & 3);
      t.fe[o] = blk(h, c, 64 * m * r) | (blk(h, c, 64 * (m + 1) * r) << 16);
      t.fo[o] = blk(h, c, 32 * (2 * m + 1) * r) | (blk(h, c, 32 * (2 * m + 3) * r) << 16);
      t.fot[o] = blk(h, c, 32 * (2 * r + 1) * m) | (blk(h, c, 32 * (2 * r + 1) * (m + 1)) << 16);
      const int k1 = r + 32 * h, n2 = 8 * (th & 3) + 2 * ((i >> 1) & 3);
      t.tw[o] = blk(0, c, n2 * k1) | (blk(0, c, (n2 + 1) * k1) << 16);
    }
  return t;
}
}
}

__device__ __align__(1024) const tab::Table g_ctab = tab::make_table();
__device__ __align__(1024) const tab::Spec g_spec = tab::make_spec();

struct Scratch {
  uint32_t cnt_w[32];
  uint32_t cnt_x1[7 * 32];
  uint32_t cnt_y[7 * 32];
  uint32_t epoch[NCTA * 12 + 240 + 256];
  uint32_t gate[S_];
  uint4 x1t[113 * 1024];
  __nv_bfloat16 yt[D_ * S_];
  uint4 wt[114 * 1024];
  uint4 part[16 * 7 * 6 * 2 * 4 * 128];
};
static_assert(offsetof(Scratch, x1t) % 1024 == 0, "alignment");
__device__ __align__(1024) Scratch g_scratch;
#define TL(i)

namespace {

struct Params {
  Scratch* s;
  __nv_bfloat16* out;
  const __nv_bfloat16 *px, *w_r, *w_i, *gate_w, *pwg, *pwu, *pwd;
  const tab::Table* ctab;
  const tab::Spec* spec;
  CUtensorMap x, wg, wu, wd, ct, yt;
};

__device__ __forceinline__ uint32_t smem_u32(const void* p) { return (uint32_t)__cvta_generic_to_shared(p); }
__device__ __forceinline__ void mbar_init(uint32_t bar, uint32_t cnt) {
  asm volatile("mbarrier.init.shared::cta.b64 [%0], %1;" ::"r"(bar), "r"(cnt) : "memory");
}
__device__ __forceinline__ void mbar_expect_tx(uint32_t bar, uint32_t bytes) {
  asm volatile("mbarrier.arrive.expect_tx.shared::cta.b64 _, [%0], %1;" ::"r"(bar), "r"(bytes) : "memory");
}
__device__ __forceinline__ void mbar_arrive(uint32_t bar) {
  asm volatile("mbarrier.arrive.shared::cta.b64 _, [%0];" ::"r"(bar) : "memory");
}
__device__ __forceinline__ void mbar_arrive_cluster(uint32_t bar, uint32_t cta) {
  asm volatile("{\n.reg .b32 ra;\nmapa.shared::cluster.u32 ra, %0, %1;\n"
               "mbarrier.arrive.shared::cluster.b64 _, [ra];\n}" ::"r"(bar), "r"(cta) : "memory");
}
__device__ __forceinline__ void mbar_wait(uint32_t bar, uint32_t parity) {
  uint32_t ok, n = 0;
  do {
    asm volatile("{\n.reg .pred p;\nmbarrier.try_wait.parity.shared::cta.b64 p, [%1], %2;\nselp.u32 %0, 1, 0, p;\n}"
                 : "=r"(ok) : "r"(bar), "r"(parity) : "memory");
  } while (!ok && ++n < SPIN_LIMIT);
}
__device__ __forceinline__ void mbar_wait_cluster(uint32_t bar, uint32_t parity) {
  uint32_t ok, n = 0;
  do {
    asm volatile("{\n.reg .pred p;\nmbarrier.try_wait.parity.acquire.cluster.shared::cta.b64 p, [%1], %2;\nselp.u32 %0, 1, 0, p;\n}"
                 : "=r"(ok) : "r"(bar), "r"(parity) : "memory");
  } while (!ok && ++n < SPIN_LIMIT);
}
__device__ __forceinline__ void tma2d(uint32_t dst, const CUtensorMap* m, int c0, int c1, uint32_t bar) {
  asm volatile("cp.async.bulk.tensor.2d.shared::cluster.global.mbarrier::complete_tx::bytes [%0], [%1, {%3, %4}], [%2];"
               ::"r"(dst), "l"(m), "r"(bar), "r"(c0), "r"(c1) : "memory");
}
__device__ __forceinline__ void tma3d(uint32_t dst, const CUtensorMap* m, int c0, int c1, int c2, uint32_t bar) {
  asm volatile("cp.async.bulk.tensor.3d.shared::cluster.global.mbarrier::complete_tx::bytes [%0], [%1, {%3, %4, %5}], [%2];"
               ::"r"(dst), "l"(m), "r"(bar), "r"(c0), "r"(c1), "r"(c2) : "memory");
}
__device__ __forceinline__ void tma2d_mc(uint32_t dst, const CUtensorMap* m, int c0, int c1, uint32_t bar) {
  asm volatile("cp.async.bulk.tensor.2d.shared::cluster.global.mbarrier::complete_tx::bytes.multicast::cluster [%0], [%1, {%3, %4}], [%2], %5;"
               ::"r"(dst), "l"(m), "r"(bar), "r"(c0), "r"(c1), "h"((uint16_t)3) : "memory");
}
__device__ __forceinline__ void tma3d_mc(uint32_t dst, const CUtensorMap* m, int c0, int c1, int c2, uint32_t bar) {
  asm volatile("cp.async.bulk.tensor.3d.shared::cluster.global.mbarrier::complete_tx::bytes.multicast::cluster [%0], [%1, {%3, %4, %5}], [%2], %6;"
               ::"r"(dst), "l"(m), "r"(bar), "r"(c0), "r"(c1), "r"(c2), "h"((uint16_t)3) : "memory");
}
__device__ __forceinline__ void bulk_g2s(uint32_t dst, const void* src, uint32_t bytes, uint32_t bar) {
  asm volatile("cp.async.bulk.shared::cluster.global.mbarrier::complete_tx::bytes [%0], [%1], %2, [%3];"
               ::"r"(dst), "l"(src), "r"(bytes), "r"(bar) : "memory");
}
__device__ __forceinline__ void bulk_s2g(void* dst, uint32_t src, uint32_t bytes) {
  asm volatile("cp.async.bulk.global.shared::cta.bulk_group [%0], [%1], %2;" ::"l"(dst), "r"(src), "r"(bytes) : "memory");
}
__device__ __forceinline__ void prefetch_tmap(const CUtensorMap* m) {
  asm volatile("prefetch.tensormap [%0];" ::"l"(m) : "memory");
}
__device__ __forceinline__ void l2_prefetch(const void* p, uint32_t bytes) {
  asm volatile("cp.async.bulk.prefetch.L2.global [%0], %1;" ::"l"(p), "r"(bytes) : "memory");
}
__device__ __forceinline__ void wg_fence() { asm volatile("wgmma.fence.sync.aligned;" ::: "memory"); }
__device__ __forceinline__ void wg_commit() { asm volatile("wgmma.commit_group.sync.aligned;" ::: "memory"); }
template <int N> __device__ __forceinline__ void wg_wait() { asm volatile("wgmma.wait_group.sync.aligned %0;" ::"n"(N) : "memory"); }
template <int N> __device__ __forceinline__ void fence_regs(float (&d)[N]) {
#pragma unroll
  for (int i = 0; i < N; i++) asm volatile("" : "+f"(d[i])::"memory");
}
template <int N> __device__ __forceinline__ void fence_regs(uint32_t (&d)[N]) {
#pragma unroll
  for (int i = 0; i < N; i++) asm volatile("" : "+r"(d[i])::"memory");
}
__device__ __forceinline__ void bar_sync(int id, int n) { asm volatile("bar.sync %0, %1;" ::"r"(id), "r"(n) : "memory"); }
__device__ __forceinline__ void bar_arrive(int id, int n) { asm volatile("bar.arrive %0, %1;" ::"r"(id), "r"(n) : "memory"); }
__device__ __forceinline__ void fence_gpu() { asm volatile("fence.acq_rel.gpu;" ::: "memory"); }
__device__ __forceinline__ void fence_async() { asm volatile("fence.proxy.async.global;" ::: "memory"); }
__device__ __forceinline__ void fence_async_smem() { asm volatile("fence.proxy.async.shared::cta;" ::: "memory"); }
__device__ __forceinline__ void red_add(uint32_t* p, uint32_t v) {
  asm volatile("red.relaxed.gpu.global.add.u32 [%0], %1;" ::"l"(p), "r"(v) : "memory");
}
__device__ __forceinline__ uint32_t ld_relaxed(const uint32_t* p) {
  uint32_t v;
  asm volatile("ld.relaxed.gpu.global.u32 %0, [%1];" : "=r"(v) : "l"(p) : "memory");
  return v;
}
__device__ __forceinline__ void wait_counter(const uint32_t* p, uint32_t target) {
  uint32_t v, n = 0;
  while (true) {
    asm volatile("ld.acquire.gpu.global.u32 %0, [%1];" : "=r"(v) : "l"(p) : "memory");
    if ((int32_t)(v - target) >= 0 || ++n > SPIN_LIMIT) break;
  }
}
__device__ __forceinline__ uint4 ld_relaxed(const uint4* p) {
  uint4 v;
  asm volatile("ld.relaxed.gpu.global.v4.u32 {%0, %1, %2, %3}, [%4];" : "=r"(v.x), "=r"(v.y), "=r"(v.z), "=r"(v.w) : "l"(p) : "memory");
  return v;
}
__device__ __forceinline__ void st_relaxed(uint4* p, uint4 v) {
  asm volatile("st.relaxed.gpu.global.v4.u32 [%0], {%1, %2, %3, %4};" ::"l"(p), "r"(v.x), "r"(v.y), "r"(v.z), "r"(v.w) : "memory");
}
__device__ __forceinline__ void st_relaxed(uint32_t* p, uint32_t v) {
  asm volatile("st.relaxed.gpu.global.u32 [%0], %1;" ::"l"(p), "r"(v) : "memory");
}
__device__ __forceinline__ uint32_t pack2(float lo, float hi) {
  uint32_t r;
  asm("cvt.rn.bf16x2.f32 %0, %1, %2;" : "=r"(r) : "f"(hi), "f"(lo));
  return r;
}
__device__ __forceinline__ uint32_t mul2(uint32_t a, uint32_t b) {
  uint32_t r;
  asm("mul.rn.bf16x2 %0, %1, %2;" : "=r"(r) : "r"(a), "r"(b));
  return r;
}
__device__ __forceinline__ uint32_t fma2(uint32_t a, uint32_t b, uint32_t c) {
  uint32_t r;
  asm("fma.rn.bf16x2 %0, %1, %2, %3;" : "=r"(r) : "r"(a), "r"(b), "r"(c));
  return r;
}
__device__ __forceinline__ uint32_t add2(uint32_t a, uint32_t b) {
  uint32_t r;
  asm("add.rn.bf16x2 %0, %1, %2;" : "=r"(r) : "r"(a), "r"(b));
  return r;
}
__device__ __forceinline__ uint32_t sub2(uint32_t a, uint32_t b) {
  uint32_t r;
  asm("sub.rn.bf16x2 %0, %1, %2;" : "=r"(r) : "r"(a), "r"(b));
  return r;
}
__device__ __forceinline__ uint32_t fms2(uint32_t a, uint32_t b, uint32_t c) {
  uint32_t r;
  asm("{\n.reg .b32 n;\nneg.bf16x2 n, %3;\nfma.rn.bf16x2 %0, %1, %2, n;\n}" : "=r"(r) : "r"(a), "r"(b), "r"(c));
  return r;
}
__device__ __forceinline__ float bf_lo(uint32_t v) { return __uint_as_float(v << 16); }
__device__ __forceinline__ float bf_hi(uint32_t v) { return __uint_as_float(v & 0xffff0000u); }
__device__ __forceinline__ float bf_round(float v) { return bf_lo(pack2(v, 0.f)); }
__device__ __forceinline__ float tanh_fast(float v) {
  float r;
  asm("tanh.approx.f32 %0, %1;" : "=f"(r) : "f"(v));
  return r;
}
__device__ __forceinline__ uint64_t mk_desc(uint32_t addr, uint32_t lbo, uint32_t sbo, uint32_t mode) {
  return (uint64_t)((addr & 0x3FFFF) >> 4) | ((uint64_t)(lbo >> 4) << 16) | ((uint64_t)(sbo >> 4) << 32) | ((uint64_t)mode << 62);
}
__device__ __forceinline__ void stmatrix_x4(uint32_t addr, uint32_t r0, uint32_t r1, uint32_t r2, uint32_t r3) {
  asm volatile("stmatrix.sync.aligned.m8n8.x4.shared.b16 [%0], {%1, %2, %3, %4};" ::"r"(addr), "r"(r0), "r"(r1), "r"(r2), "r"(r3) : "memory");
}

template <int TA, int TB>
__device__ __forceinline__ void wgmma_ss_n256(float (&d)[128], uint64_t da, uint64_t db, int sd) {
  asm volatile("{\n.reg .pred p;\nsetp.ne.b32 p, %130, 0;\n"
      "wgmma.mma_async.sync.aligned.m64n256k16.f32.bf16.bf16 {"
      "%0, %1, %2, %3, %4, %5, %6, %7, %8, %9, %10, %11, %12, %13, %14, %15, %16, %17, %18, %19, %20, %21, %22, %23, "
      "%24, %25, %26, %27, %28, %29, %30, %31, %32, %33, %34, %35, %36, %37, %38, %39, %40, %41, %42, %43, %44, %45, "
      "%46, %47, %48, %49, %50, %51, %52, %53, %54, %55, %56, %57, %58, %59, %60, %61, %62, %63, %64, %65, %66, %67, "
      "%68, %69, %70, %71, %72, %73, %74, %75, %76, %77, %78, %79, %80, %81, %82, %83, %84, %85, %86, %87, %88, %89, "
      "%90, %91, %92, %93, %94, %95, %96, %97, %98, %99, %100, %101, %102, %103, %104, %105, %106, %107, %108, %109, "
      "%110, %111, %112, %113, %114, %115, %116, %117, %118, %119, %120, %121, %122, %123, %124, %125, %126, %127"
      "}, %128, %129, p, 1, 1, %131, %132;\n}\n"
      : "+f"(d[0]), "+f"(d[1]), "+f"(d[2]), "+f"(d[3]), "+f"(d[4]), "+f"(d[5]), "+f"(d[6]), "+f"(d[7]), "+f"(d[8]),
        "+f"(d[9]), "+f"(d[10]), "+f"(d[11]), "+f"(d[12]), "+f"(d[13]), "+f"(d[14]), "+f"(d[15]), "+f"(d[16]),
        "+f"(d[17]), "+f"(d[18]), "+f"(d[19]), "+f"(d[20]), "+f"(d[21]), "+f"(d[22]), "+f"(d[23]), "+f"(d[24]),
        "+f"(d[25]), "+f"(d[26]), "+f"(d[27]), "+f"(d[28]), "+f"(d[29]), "+f"(d[30]), "+f"(d[31]), "+f"(d[32]),
        "+f"(d[33]), "+f"(d[34]), "+f"(d[35]), "+f"(d[36]), "+f"(d[37]), "+f"(d[38]), "+f"(d[39]), "+f"(d[40]),
        "+f"(d[41]), "+f"(d[42]), "+f"(d[43]), "+f"(d[44]), "+f"(d[45]), "+f"(d[46]), "+f"(d[47]), "+f"(d[48]),
        "+f"(d[49]), "+f"(d[50]), "+f"(d[51]), "+f"(d[52]), "+f"(d[53]), "+f"(d[54]), "+f"(d[55]), "+f"(d[56]),
        "+f"(d[57]), "+f"(d[58]), "+f"(d[59]), "+f"(d[60]), "+f"(d[61]), "+f"(d[62]), "+f"(d[63]), "+f"(d[64]),
        "+f"(d[65]), "+f"(d[66]), "+f"(d[67]), "+f"(d[68]), "+f"(d[69]), "+f"(d[70]), "+f"(d[71]), "+f"(d[72]),
        "+f"(d[73]), "+f"(d[74]), "+f"(d[75]), "+f"(d[76]), "+f"(d[77]), "+f"(d[78]), "+f"(d[79]), "+f"(d[80]),
        "+f"(d[81]), "+f"(d[82]), "+f"(d[83]), "+f"(d[84]), "+f"(d[85]), "+f"(d[86]), "+f"(d[87]), "+f"(d[88]),
        "+f"(d[89]), "+f"(d[90]), "+f"(d[91]), "+f"(d[92]), "+f"(d[93]), "+f"(d[94]), "+f"(d[95]), "+f"(d[96]),
        "+f"(d[97]), "+f"(d[98]), "+f"(d[99]), "+f"(d[100]), "+f"(d[101]), "+f"(d[102]), "+f"(d[103]), "+f"(d[104]),
        "+f"(d[105]), "+f"(d[106]), "+f"(d[107]), "+f"(d[108]), "+f"(d[109]), "+f"(d[110]), "+f"(d[111]),
        "+f"(d[112]), "+f"(d[113]), "+f"(d[114]), "+f"(d[115]), "+f"(d[116]), "+f"(d[117]), "+f"(d[118]),
        "+f"(d[119]), "+f"(d[120]), "+f"(d[121]), "+f"(d[122]), "+f"(d[123]), "+f"(d[124]), "+f"(d[125]),
        "+f"(d[126]), "+f"(d[127])
      : "l"(da), "l"(db), "r"(sd), "n"(TA), "n"(TB));
}
template <int TA, int TB>
__device__ __forceinline__ void wgmma_ss_n128(float (&d)[64], uint64_t da, uint64_t db, int sd) {
  asm volatile("{\n.reg .pred p;\nsetp.ne.b32 p, %66, 0;\n"
      "wgmma.mma_async.sync.aligned.m64n128k16.f32.bf16.bf16 {"
      "%0, %1, %2, %3, %4, %5, %6, %7, %8, %9, %10, %11, %12, %13, %14, %15, %16, %17, %18, %19, %20, %21, %22, %23, "
      "%24, %25, %26, %27, %28, %29, %30, %31, %32, %33, %34, %35, %36, %37, %38, %39, %40, %41, %42, %43, %44, %45, "
      "%46, %47, %48, %49, %50, %51, %52, %53, %54, %55, %56, %57, %58, %59, %60, %61, %62, %63"
      "}, %64, %65, p, 1, 1, %67, %68;\n}\n"
      : "+f"(d[0]), "+f"(d[1]), "+f"(d[2]), "+f"(d[3]), "+f"(d[4]), "+f"(d[5]), "+f"(d[6]), "+f"(d[7]), "+f"(d[8]),
        "+f"(d[9]), "+f"(d[10]), "+f"(d[11]), "+f"(d[12]), "+f"(d[13]), "+f"(d[14]), "+f"(d[15]), "+f"(d[16]),
        "+f"(d[17]), "+f"(d[18]), "+f"(d[19]), "+f"(d[20]), "+f"(d[21]), "+f"(d[22]), "+f"(d[23]), "+f"(d[24]),
        "+f"(d[25]), "+f"(d[26]), "+f"(d[27]), "+f"(d[28]), "+f"(d[29]), "+f"(d[30]), "+f"(d[31]), "+f"(d[32]),
        "+f"(d[33]), "+f"(d[34]), "+f"(d[35]), "+f"(d[36]), "+f"(d[37]), "+f"(d[38]), "+f"(d[39]), "+f"(d[40]),
        "+f"(d[41]), "+f"(d[42]), "+f"(d[43]), "+f"(d[44]), "+f"(d[45]), "+f"(d[46]), "+f"(d[47]), "+f"(d[48]),
        "+f"(d[49]), "+f"(d[50]), "+f"(d[51]), "+f"(d[52]), "+f"(d[53]), "+f"(d[54]), "+f"(d[55]), "+f"(d[56]),
        "+f"(d[57]), "+f"(d[58]), "+f"(d[59]), "+f"(d[60]), "+f"(d[61]), "+f"(d[62]), "+f"(d[63])
      : "l"(da), "l"(db), "r"(sd), "n"(TA), "n"(TB));
}
template <int TA, int TB>
__device__ __forceinline__ void wgmma_ss_n64(float (&d)[32], uint64_t da, uint64_t db, int sd) {
  asm volatile("{\n.reg .pred p;\nsetp.ne.b32 p, %34, 0;\n"
      "wgmma.mma_async.sync.aligned.m64n64k16.f32.bf16.bf16 {"
      "%0, %1, %2, %3, %4, %5, %6, %7, %8, %9, %10, %11, %12, %13, %14, %15, %16, %17, %18, %19, %20, %21, %22, %23, "
      "%24, %25, %26, %27, %28, %29, %30, %31"
      "}, %32, %33, p, 1, 1, %35, %36;\n}\n"
      : "+f"(d[0]), "+f"(d[1]), "+f"(d[2]), "+f"(d[3]), "+f"(d[4]), "+f"(d[5]), "+f"(d[6]), "+f"(d[7]), "+f"(d[8]),
        "+f"(d[9]), "+f"(d[10]), "+f"(d[11]), "+f"(d[12]), "+f"(d[13]), "+f"(d[14]), "+f"(d[15]), "+f"(d[16]),
        "+f"(d[17]), "+f"(d[18]), "+f"(d[19]), "+f"(d[20]), "+f"(d[21]), "+f"(d[22]), "+f"(d[23]), "+f"(d[24]),
        "+f"(d[25]), "+f"(d[26]), "+f"(d[27]), "+f"(d[28]), "+f"(d[29]), "+f"(d[30]), "+f"(d[31])
      : "l"(da), "l"(db), "r"(sd), "n"(TA), "n"(TB));
}
template <int SA, int TB>
__device__ __forceinline__ void wgmma_rs_n64(float (&d)[32], uint32_t a0, uint32_t a1, uint32_t a2, uint32_t a3, uint64_t db, int sd) {
  asm volatile("{\n.reg .pred p;\nsetp.ne.b32 p, %37, 0;\n"
      "wgmma.mma_async.sync.aligned.m64n64k16.f32.bf16.bf16 {"
      "%0, %1, %2, %3, %4, %5, %6, %7, %8, %9, %10, %11, %12, %13, %14, %15, %16, %17, %18, %19, %20, %21, %22, %23, "
      "%24, %25, %26, %27, %28, %29, %30, %31"
      "}, {%32, %33, %34, %35}, %36, p, %38, 1, %39;\n}\n"
      : "+f"(d[0]), "+f"(d[1]), "+f"(d[2]), "+f"(d[3]), "+f"(d[4]), "+f"(d[5]), "+f"(d[6]), "+f"(d[7]), "+f"(d[8]),
        "+f"(d[9]), "+f"(d[10]), "+f"(d[11]), "+f"(d[12]), "+f"(d[13]), "+f"(d[14]), "+f"(d[15]), "+f"(d[16]),
        "+f"(d[17]), "+f"(d[18]), "+f"(d[19]), "+f"(d[20]), "+f"(d[21]), "+f"(d[22]), "+f"(d[23]), "+f"(d[24]),
        "+f"(d[25]), "+f"(d[26]), "+f"(d[27]), "+f"(d[28]), "+f"(d[29]), "+f"(d[30]), "+f"(d[31])
      : "r"(a0), "r"(a1), "r"(a2), "r"(a3), "l"(db), "r"(sd), "n"(SA), "n"(TB));
}

__device__ __forceinline__ uint32_t BAR_FULL(uint32_t sb, int i) { return sb + SM_BAR + 8 * i; }
__device__ __forceinline__ uint32_t BAR_EMPTY(uint32_t sb, int i) { return sb + SM_BAR + 64 + 8 * i; }
__device__ __forceinline__ uint32_t BAR_X(uint32_t sb, int i) { return sb + SM_BAR + 128 + 8 * i; }
__device__ __forceinline__ uint32_t BAR_Y(uint32_t sb, int i) { return sb + SM_BAR + 192 + 8 * i; }
__device__ __forceinline__ uint32_t BAR_XFREE(uint32_t sb) { return sb + SM_BAR + 256; }

__device__ __forceinline__ uint32_t BAR_E2(uint32_t sb, int i) { return sb + SM_BAR + 264 + 8 * i; }
#define CMASK 0xd4u
#define XORDER 0, 1, 11, 2, 3, 12, 13, 4, 5, 14, 6, 15, 16
#define XSPREAD 4
#define PFAT 2
#define SKEW 3
#define EQW 38
#define EQA 37
#define GL4 6
#define PFR 4
#define GS0 2
#define GL2 6
#define GS1 4
constexpr int Q_G1B = 18, Q_G2 = 32, Q_XR = 39, Q_P3 = 46, Q_END = 50;

__device__ __forceinline__ uint32_t y_addr(int kb) { return kb < 3 ? SM_RING + (kb + (Q_G2 + 4) % NSTAGE) * STAGE_BYTES : SM_X + (kb - 3) * 16384; }
static_assert((Q_G2 + 4) % NSTAGE + 2 < NSTAGE, "");

struct Ring {
  uint32_t slot, phase;
  __device__ __forceinline__ void next() { if (++slot == NSTAGE) { slot = 0; phase ^= 1; } }
};

__device__ __forceinline__ void release_slot(uint32_t sb, uint32_t slot, int tid, int times) {
  if (tid < 2 * times) mbar_arrive_cluster(BAR_EMPTY(sb, slot), tid & 1);
}

__device__ __forceinline__ void ffn_consumer(uint32_t sb, const uint8_t* smem, const Params& p, int bid, int wg, int tid, int mt, int jj) {
  const int lane = tid & 31, warp = tid >> 5, q = lane & 3, r0 = 16 * warp + (lane >> 2);
  uint32_t* const my_epoch = &p.s->epoch[blockIdx.x * 12 + (threadIdx.x >> 5)];
  const uint32_t epoch = ld_relaxed(my_epoch) + 1;
  Ring rg{0, 0};
  uint32_t u[64];
  float acc[128];
  uint32_t prev = 0, cmask = CMASK;
  int st = 0;
  auto g1_stage = [&](uint32_t slot, int s) {
    const uint64_t da = mk_desc(sb + SM_X + (s >> 1) * 16384 + wg * 8192 + (s & 1) * 64, 16, 1024, 1);
    const uint64_t db = mk_desc(sb + SM_RING + slot * STAGE_BYTES, 4096, 1024, 1);
    wg_fence();
    wgmma_ss_n256<0, 1>(acc, da, db, s != 0);
    wgmma_ss_n256<0, 1>(acc, da + 2, db + 128, 1);
    wg_commit();
  };
  if (wg == 1) {
    float ap[64];
    constexpr int QX = 32 - __builtin_clz(CMASK);
    constexpr int NPRE = QX + XSPREAD;
    uint4* const x1dst = p.s->x1t + ((64 * jj + r0 + 8) >> 2) * 1024 + (r0 & 3) * 128 + 8 * mt + (q ^ (mt & 3));
    const int x1lo = 64 * jj + r0 == 1 ? 110 * 1024 - 128 : -2048;
#pragma unroll
    for (int qi = 0; qi < NPRE; qi++) {
      const int slot = qi % NSTAGE, nc = __builtin_popcount(CMASK & ((1u << qi) - 1));
      if (qi == 0) TL(60);
      mbar_wait(BAR_FULL(sb, slot), (qi / NSTAGE) & 1);
      if (qi == 0) TL(61);
      if ((CMASK >> qi) & 1) {
#pragma unroll
        for (int kb = 2 * nc; kb < 2 * nc + 2 && kb < 7; kb++) {
          const uint64_t da = mk_desc(sb + SM_RING + slot * STAGE_BYTES + (kb & 1) * 8192, 8192, 1024, 1);
          const uint64_t db = mk_desc(sb + SM_X + kb * 16384, 16, 1024, 1);
          mbar_wait(BAR_X(sb, kb), 0);
          TL(16 + kb);
          wg_fence();
#pragma unroll
          for (int kk = 0; kk < 4; kk++) wgmma_ss_n128<1, 0>(ap, da + kk * 128, db + kk * 2, (kb | kk) != 0);
          wg_commit();
        }
      } else {
        if (((qi - nc) & 1) == 0 && qi - nc >= 4 * nc) mbar_wait(BAR_X(sb, (qi - nc) >> 1), 0);
        TL(32 + qi - nc);
        g1_stage(slot, qi - nc);
      }
      if (qi > 0) {
        wg_wait<1>();
        release_slot(sb, (qi - 1) % NSTAGE, tid, ((CMASK >> (qi - 1)) & 1) ? 2 : 1);
      }
      if (qi >= QX) {
        if (qi == QX) { fence_regs(ap); TL(2); }
#pragma unroll
        for (int t = (qi - QX) * (4 / XSPREAD); t < (qi - QX + 1) * (4 / XSPREAD); t++)
#pragma unroll
        for (int h = 0; h < 2; h++)
          x1dst[(h ? 0 : x1lo) + 512 * (t & 1) + 4 * (t >> 1)] = make_uint4((pack2(ap[16 * t + 2 * h], ap[16 * t + 2 * h + 1]) & ~1u) | (epoch & 1), pack2(ap[16 * t + 4 + 2 * h], ap[16 * t + 5 + 2 * h]),
                                             pack2(ap[16 * t + 8 + 2 * h], ap[16 * t + 9 + 2 * h]), pack2(ap[16 * t + 12 + 2 * h], ap[16 * t + 13 + 2 * h]));
      }
    }
    bar_arrive(7, 160);
    st = NPRE - 4; cmask = 0; prev = (NPRE - 1) % NSTAGE;
    rg.slot = NPRE % NSTAGE; rg.phase = (NPRE / NSTAGE) & 1;
  }
#pragma unroll 1
  for (int pass = 0; pass < 2; pass++) {
#pragma unroll 1
    for (; st < 14; st++) {
      while (cmask & 1) { cmask >>= 1; rg.next(); }
      cmask >>= 1;
      if (pass == 0 && (st & 1) == 0) mbar_wait(BAR_X(sb, st >> 1), 0);
      if (st == 14 - SKEW && wg == 1) bar_sync(9 + pass, 256);
      mbar_wait(BAR_FULL(sb, rg.slot), rg.phase);
      TL(32 + 14 * pass + st);
      g1_stage(rg.slot, st);
      wg_wait<1>();
      if (st > 0) release_slot(sb, prev, tid, 1);
      prev = rg.slot;
      rg.next();
    }
    st = 0;
    if (wg == 0) bar_arrive(9 + pass, 256);
    wg_wait<0>();
    fence_regs(acc);
    release_slot(sb, prev, tid, 1);
    TL(3 + 2 * pass);
#pragma unroll
    for (int i = 0; i < 32; i++) {
      const float g0 = 0.5f * acc[2 * i], g1 = 0.5f * acc[2 * i + 1];
      const float s0 = fmaf(g0, tanh_fast(g0), g0), s1 = fmaf(g1, tanh_fast(g1), g1);
      u[32 + i] = pack2(s0 * acc[64 + 2 * i], s1 * acc[64 + 2 * i + 1]);
    }
    if (pass == 0) {
#pragma unroll
      for (int i = 0; i < 32; i++) u[i] = u[32 + i];
    }
    TL(4 + 2 * pass);
  }
  fence_regs(u);
  float accA[32], accB[32];
  auto stage = [&](float (&acc)[32], int qi) {
    const int st = qi & 1;
    if (qi == EQW && wg == 0) bar_sync(1, 256);
    if (qi < Q_XR) mbar_wait(BAR_FULL(sb, qi % NSTAGE), (qi / NSTAGE) & 1);
    else mbar_wait(BAR_X(sb, qi - Q_XR), 1);
    const uint64_t db = mk_desc(sb + (qi < Q_XR ? SM_RING + (qi % NSTAGE) * STAGE_BYTES : SM_X + (qi - Q_XR) * 16384), 8192, 1024, 1);
    wg_fence();
#pragma unroll
    for (int kk = 0; kk < 8; kk++) {
      const uint32_t* a = u + 32 * st + 4 * kk;
      wgmma_rs_n64<1, 1>(acc, a[0], a[1], a[2], a[3], db + kk * 128, (st | kk) != 0);
    }
    wg_commit();
    if (qi == EQA && wg == 1) bar_arrive(1, 256);
  };
  auto retire = [&](int qi) {
    wg_wait<1>();
    if (qi >= Q_G2 && qi < Q_G2 + 4) release_slot(sb, qi % NSTAGE, tid, 1);
    else if (qi >= Q_G2 + 4 && qi < Q_G2 + 11 && tid == 0) mbar_arrive(BAR_E2(sb, qi - Q_G2 - 4));
  };
  const uint32_t par = epoch & 1;
  auto put = [&](float (&acc)[32], int c) {
    fence_regs(acc);
    int o = jj + 1 + c;
    if (o >= 7) o -= 7;
    uint4* dst = p.s->part + ((((mt * 7 + o) * 6 + c) * 2 + wg) * 4) * 128 + tid;
#pragma unroll
    for (int v = 0; v < 4; v++) {
      const float* a = acc + 8 * v;
      st_relaxed(dst + v * 128, make_uint4((pack2(a[0], a[1]) & ~1u) | par, pack2(a[2], a[3]), pack2(a[4], a[5]), pack2(a[6], a[7])));
    }
  };
  const uint4* const src = p.s->part + (((mt * 7 + jj) * 6 * 2 + wg) * 4) * 128 + tid;
  auto gload = [&](uint4 (&pv)[8], int c) {
#pragma unroll
    for (int i = 0; i < 8; i++) pv[i] = ld_relaxed(src + ((2 * c + (i >> 2)) * 8 + (i & 3)) * 128);
  };
  auto gload1 = [&](uint4 (&pv)[8], int c) {
#pragma unroll
    for (int i = 0; i < 4; i++) pv[4 * (c & 1) + i] = ld_relaxed(src + (c * 8 + i) * 128);
  };
  auto gsum = [&](uint4 (&pv)[8], int c, float s0, float s1) {
#pragma unroll 1
    for (uint32_t n = 0; n < SPIN_LIMIT; n++) {
      uint32_t bad = 0;
#pragma unroll
      for (int i = 0; i < 8; i++) bad |= pv[i].x ^ par;
      if (!__any_sync(0xffffffffu, bad & 1)) break;
      gload(pv, c);
    }
    TL(24 + c);
#pragma unroll
    for (int i = 0; i < 4; i++) {
      const uint32_t w[4] = {add2(pv[i].x, pv[4 + i].x), add2(pv[i].y, pv[4 + i].y), add2(pv[i].z, pv[4 + i].z), add2(pv[i].w, pv[4 + i].w)};
#pragma unroll
      for (int k = 0; k < 4; k++) {
        const float s = (k & 1) ? s1 : s0;
        accA[8 * i + 2 * k] = fmaf(s, bf_lo(w[k]), accA[8 * i + 2 * k]); accA[8 * i + 2 * k + 1] = fmaf(s, bf_hi(w[k]), accA[8 * i + 2 * k + 1]);
      }
    }
  };
  uint4 pv0[8], pv1[8], pv2[8];
  const int row = 128 * mt + 64 * wg + r0;
  uint32_t gt0, gt1;
#pragma unroll
  for (int c2 = 0; c2 < 4; c2++) {
    const int qi = Q_G2 + 4 * c2;
    stage(accA, qi);
    retire(qi - 1);
    stage(accA, qi + 1);
    if (c2 == 3) TL(27);
    if (c2 > 0) put(accB, 2 * c2 - 1);
    if (c2 == 2) gload1(pv0, 1);
    if (c2 == 3) gload1(pv1, 3);
    TL(7 + c2);
    if (c2 == 3) break;
    retire(qi);
    stage(accB, qi + 2);
    retire(qi + 1);
    stage(accB, qi + 3);
    put(accA, 2 * c2);
    if (c2 == 1) gload1(pv0, 0);
    if (c2 == 2) gload1(pv1, 2);
    if (c2 == 0) { gt0 = ld_relaxed(&p.s->gate[row]); gt1 = ld_relaxed(&p.s->gate[row + 8]); }
    retire(qi + 2);
  }
#pragma unroll
  for (int kb = 0; kb < 7; kb++) {
    const int qt = Q_XR + (kb >> 1);
    if ((kb & 1) == 0) mbar_wait(BAR_FULL(sb, qt % NSTAGE), (qt / NSTAGE) & 1);
    mbar_wait(BAR_Y(sb, kb), 0);
    const uint64_t da = mk_desc(sb + y_addr(kb) + wg * 8192, 8192, 1024, 1);
    const uint64_t db = mk_desc(sb + SM_RING + (qt % NSTAGE) * STAGE_BYTES + (kb & 1) * 8192, 16, 1024, 1);
    wg_fence();
#pragma unroll
    for (int kk = 0; kk < 4; kk++) wgmma_ss_n64<1, 0>(accB, da + kk * 128, db + kk * 2, (kb | kk) != 0);
    wg_commit();
    if (kb == 1) { wg_wait<2>(); fence_regs(accA); TL(15); }
    if (kb == GS0) gsum(pv0, 0, 1.f, 1.f);
    if (kb == GL4) gload1(pv2, 4);
    if (kb == GL2) gload1(pv2, 5);
    if (kb == GS1) gsum(pv1, 1, 1.f, 1.f);
  }
  TL(11);
  for (uint32_t n = 0; (((gt0 ^ epoch) | (gt1 ^ epoch)) & 0xffffu) && n < SPIN_LIMIT; n++) {
    gt0 = ld_relaxed(&p.s->gate[row]); gt1 = ld_relaxed(&p.s->gate[row + 8]);
  }
  const float ga0 = bf_hi(gt0), ga1 = bf_hi(gt1);
  const float gb0 = bf_round(1.f - ga0), gb1 = bf_round(1.f - ga1);
  const float gs0 = ga0 * (2.f / (float)(S_ * D_)), gs1 = ga1 * (2.f / (float)(S_ * D_));
  wg_wait<0>();
  fence_regs(accB);
#pragma unroll
  for (int i = 0; i < 32; i++) accA[i] = (i & 2) ? fmaf(gs1, accB[i], gb1 * accA[i]) : fmaf(gs0, accB[i], gb0 * accA[i]);
  fence_regs(accA);
  TL(12);
  gsum(pv2, 2, gb0, gb1);
  TL(13);
  uint4* const o = reinterpret_cast<uint4*>(p.out + (size_t)row * D_ + 64 * jj + 8 * q);
#pragma unroll
  for (int h = 0; h < 2; h++) {
#pragma unroll
    for (int k = 0; k < 2; k++) {
      uint32_t w[4];
#pragma unroll
      for (int j = 0; j < 4; j++) {
        const int i = 16 * k + 4 * j + 2 * h;
        w[j] = pack2(accA[i], accA[i + 1]);
      }
      const bool o1 = q & 1, o2 = q & 2;
      uint32_t a = __shfl_xor_sync(0xffffffffu, o1 ? w[0] : w[1], 1), b = __shfl_xor_sync(0xffffffffu, o1 ? w[2] : w[3], 1);
      if (o1) { w[0] = a; w[2] = b; } else { w[1] = a; w[3] = b; }
      a = __shfl_xor_sync(0xffffffffu, o2 ? w[0] : w[2], 2); b = __shfl_xor_sync(0xffffffffu, o2 ? w[1] : w[3], 2);
      if (o2) { w[0] = a; w[1] = b; } else { w[2] = a; w[3] = b; }
      o[h * D_ + 4 * k] = make_uint4(w[0], w[1], w[2], w[3]);
    }
  }
  if (lane == 0) *my_epoch = epoch;
  TL(14);
}

__device__ __forceinline__ void ring_issue(uint32_t sb, const Params& p, int qi, uint32_t slot, bool wait, uint32_t phase, int jj, uint32_t rank) {
  const CUtensorMap* m;
  int c0, c1, c2 = 0;
  bool half = false, is3d = false;
  if (qi < Q_G2) {
    const int nc = __popc(CMASK & ((1u << qi) - 1));
    if ((CMASK >> qi) & 1) {
      m = &p.ct; c0 = 64 * jj; c1 = 128 * nc + 64 * rank; half = nc == 3;
    } else {
      const int pass = qi >= Q_G1B;
      m = rank ? &p.wu : &p.wg; c0 = 0; c1 = 32 * (qi - nc - 14 * pass); c2 = 4 * jj + 2 * pass; is3d = true;
    }
  } else if (qi < Q_P3) {
    int o = jj + 1 + ((qi - Q_G2) >> 1);
    if (o >= 7) o -= 7;
    m = &p.wd; c0 = 64 * o; c1 = 256 * jj + 128 * (qi & 1) + 64 * rank;
  } else {
    m = &p.ct; c0 = 128 * (qi - Q_P3) + 64 * rank; c1 = 64 * jj; half = qi == Q_END - 1;
  }
  uint32_t bar = BAR_FULL(sb, slot), dst = sb + SM_RING + slot * STAGE_BYTES + rank * 8192;
  if (qi >= Q_XR && qi < Q_P3) {
    bar = BAR_X(sb, qi - Q_XR); dst = sb + SM_X + (qi - Q_XR) * 16384 + rank * 8192;
    if (qi == Q_XR) mbar_wait_cluster(BAR_XFREE(sb), 0);
  } else {
    if (wait) mbar_wait_cluster(BAR_EMPTY(sb, slot), phase ^ (qi >= Q_P3));
    mbar_expect_tx(bar, half ? 8192 : 16384);
  }
  if (is3d) tma3d_mc(dst, m, c0, c1, c2, bar);
  else if (!(half && rank)) tma2d_mc(dst, m, c0, c1, bar);
}

__device__ __forceinline__ void ffn_producer(uint32_t sb, const uint8_t* smem, int bid, const Params& p, int warp, int lane, int mt, int jj, uint32_t rank) {
  if (warp < 2) {
    if (lane == 0) {
      uint32_t slot = warp, phase = 0;
#pragma unroll 1
      for (int qi = NSTAGE + warp; qi < Q_END; qi += 2) {
        if (qi < Q_XR || qi >= Q_P3) ring_issue(sb, p, qi, slot, true, phase, jj, rank);
        if (warp == 1 && qi >= Q_G1B + 8 && qi < Q_XR) ring_issue(sb, p, Q_XR + ((qi - Q_G1B - 8) >> 1), 0, false, 0, jj, rank);
        TL(10 + qi);
        slot += 2;
        if (slot >= NSTAGE) { slot -= NSTAGE; phase ^= 1; }
      }
    }
  } else {
    const int wg = warp - 2;
    uint32_t* const my_epoch = &p.s->epoch[blockIdx.x * 12 + 8 + warp];
    const uint32_t epoch = ld_relaxed(my_epoch) + 1;
    if (wg == 0) {
      if (lane == 0) { prefetch_tmap(&p.wd); prefetch_tmap(&p.yt); }
      {
        const uint4* gw4 = reinterpret_cast<const uint4*>(p.gate_w);
        const uint4 ga = __ldg(gw4 + lane), gb = lane < 24 ? __ldg(gw4 + 32 + lane) : make_uint4(0, 0, 0, 0);
        if (lane < 7) { mbar_wait(BAR_X(sb, lane), 0); mbar_expect_tx(BAR_X(sb, lane), 16384); mbar_expect_tx(BAR_Y(sb, lane), 16384); }
        __syncwarp();
        float mine = 0.f;
#pragma unroll 1
        for (int u = 0; u < 19; u++) {
          const int r = min(19 * jj + u, 127);
          const uint8_t* xr = smem + SM_X + (lane >> 3) * 16384 + r * 128 + (((lane ^ r) & 7) << 4);
          const uint4 xa = *reinterpret_cast<const uint4*>(xr);
          const uint4 xb = lane < 24 ? *reinterpret_cast<const uint4*>(xr + 65536) : make_uint4(0, 0, 0, 0);
          float s = 0.f;
          auto dot2 = [&](uint32_t a, uint32_t b) {
            const uint32_t pr = mul2(a, b);
            s += bf_lo(pr) + bf_hi(pr);
          };
          dot2(xa.x, ga.x); dot2(xa.y, ga.y); dot2(xa.z, ga.z); dot2(xa.w, ga.w);
          dot2(xb.x, gb.x); dot2(xb.y, gb.y); dot2(xb.z, gb.z); dot2(xb.w, gb.w);
#pragma unroll
          for (int o = 16; o > 0; o >>= 1) s += __shfl_xor_sync(0xffffffffu, s, o);
          if (lane == u) mine = s;
        }
        if (lane < 19 && 19 * jj + lane < 128)
          st_relaxed(&p.s->gate[128 * mt + 19 * jj + lane], pack2(0.f, 1.f / (1.f + __expf(-bf_round(mine)))) | (epoch & 0xffffu));
      }
      TL(9);
      if (lane < 2) mbar_arrive_cluster(BAR_XFREE(sb), lane);
    } else {
      mbar_wait(BAR_X(sb, PFAT), 0);
      if (lane < 2 * PFR) {
        int row = 176 + PFR * bid + (lane >> 1);
        if (row >= D_) row -= D_;
        l2_prefetch(((lane & 1) ? p.pwu : p.pwg) + row * F_, F_ * 2);
      }
      TL(2);
      bar_sync(7, 160);
      if (lane == 0) { red_add(&p.s->cnt_x1[jj * 32], 1);
        l2_prefetch(p.pwd + bid * 16 * D_, 32 * D_); }
      TL(5);
    }
    mbar_wait(BAR_E2(sb, 0), 0);
    TL(3);
    const int kb = 2 * lane + wg;
    bool todo = kb < 7, ready = false;
    uint32_t n = 0;
    while (__any_sync(0xffffffffu, todo)) {
      if (todo) {
        uint32_t ok;
        if (!ready) {
          asm volatile("ld.acquire.gpu.global.u32 %0, [%1];" : "=r"(ok) : "l"(&p.s->cnt_y[kb * 32]) : "memory");
          ready = (int32_t)(ok - epoch * (kb ? 16 : 17)) >= 0;
        }
        asm volatile("{\n.reg .pred p;\nmbarrier.test_wait.parity.shared::cta.b64 p, [%1], 0;\nselp.u32 %0, 1, 0, p;\n}"
                     : "=r"(ok) : "r"(BAR_E2(sb, kb)) : "memory");
        if ((ok && ready) || ++n > SPIN_LIMIT) {
          tma3d(sb + y_addr(kb), &p.yt, 0, 64 * kb, 2 * mt, BAR_Y(sb, kb));
          todo = false;
        }
      }
      __nanosleep(40);
    }
    TL(4);
    if (lane == 0) *my_epoch = epoch;
  }
}

__device__ __forceinline__ void spectral_cta(uint32_t sb, uint8_t* smem, const Params& p, int sc, int wg) {
  const int t384 = threadIdx.x, lane = t384 & 31, warp12 = t384 >> 5, tid = t384 & 127;
  const int warp = tid >> 5, q = lane & 3;
  const int sl0 = 6 * sc + min(sc, 8), nsl = sc < 8 ? 7 : 6;
  if (t384 == 320) {
#pragma unroll 1
    for (int i = 0; i < nsl; i++) {
      mbar_expect_tx(BAR_X(sb, i), 2 * SLAB_BYTES);
      const int row = 128 * ((sl0 + i) >> 3) + 8 * ((sl0 + i) & 7);
      const uint32_t dst = sb + SP_Z + 2 * i * SLAB_BYTES;
      bulk_g2s(dst, p.w_r + row * DF_, SLAB_BYTES / 2, BAR_X(sb, i));
      bulk_g2s(dst + SLAB_BYTES / 2, p.w_r + (row + 64) * DF_, SLAB_BYTES / 2, BAR_X(sb, i));
      bulk_g2s(dst + SLAB_BYTES, p.w_i + row * DF_, SLAB_BYTES / 2, BAR_X(sb, i));
      bulk_g2s(dst + 3 * SLAB_BYTES / 2, p.w_i + (row + 64) * DF_, SLAB_BYTES / 2, BAR_X(sb, i));
    }
  } else if (t384 == 352 && sc < 19) {
    mbar_expect_tx(BAR_Y(sb, 6), 24576);
    bulk_g2s(sb + SP_TW, p.spec, 24576, BAR_Y(sb, 6));
  }
  uint32_t* const my_epoch = &p.s->epoch[blockIdx.x * 12 + warp12];
  const uint32_t epoch = ld_relaxed(my_epoch) + 1;
  uint32_t fe[16], tw[16];
#pragma unroll
  for (int i = 0; i < 4; i++) {
    const uint4 a = __ldg(reinterpret_cast<const uint4*>(p.spec->fe) + i * 128 + tid);
    const uint4 b = __ldg(reinterpret_cast<const uint4*>(p.spec->tw) + i * 128 + tid);
    fe[4 * i] = a.x; fe[4 * i + 1] = a.y; fe[4 * i + 2] = a.z; fe[4 * i + 3] = a.w;
    tw[4 * i] = b.x; tw[4 * i + 1] = b.y; tw[4 * i + 2] = b.z; tw[4 * i + 3] = b.w;
  }
  __syncwarp();
  asm volatile("barrier.cluster.wait.acquire.aligned;" ::: "memory");
#pragma unroll 2
  for (int un = wg; un < 8 * nsl; un += 3) {
    const int i = un >> 3, sl = sl0 + i, pr = 16 * (un & 7) + 4 * (lane >> 3) + warp, r = lane & 7;
    mbar_wait(BAR_X(sb, i), 0);
    if (pr < 113) {
      const uint16_t* w = reinterpret_cast<const uint16_t*>(smem + SP_Z + 2 * i * SLAB_BYTES) + r * DF_ + 2 * pr;
      const uint32_t m = pr < 112 ? 0xffffffffu : 0u;
      p.s->wt[pr * 1024 + sl * 8 + (r ^ ((sl >> 2) & 6))] =
          make_uint4(w[0] | ((uint32_t)w[8 * DF_] << 16), w[16 * DF_] | ((uint32_t)w[24 * DF_] << 16),
                     (w[1] | ((uint32_t)w[8 * DF_ + 1] << 16)) & m, (w[16 * DF_ + 1] | ((uint32_t)w[24 * DF_ + 1] << 16)) & m);
    }
  }
  __syncthreads();
  if (t384 == 352) { fence_gpu(); red_add(&p.s->cnt_w[0], 1); TL(2); }
  TL(1);
  if (sc == 19) return;
  const int nrnd = (sc == 18 && wg == 2) ? 1 : 2;
  auto pair_of = [&](int r) { const int i = 3 * sc + wg + 57 * r; return i ? i - 1 : 112; };
  auto fetch = [&]() {
    const int item = wg + 3 * lane, pr = pair_of(lane);
    const uint32_t bar = warp ? BAR_Y(sb, item) : BAR_FULL(sb, item);
    mbar_expect_tx(bar, 16384);
    wait_counter(warp ? &p.s->cnt_w[0] : &p.s->cnt_x1[(pr < 112 ? pr >> 4 : 0) * 32], epoch * (warp ? NSPEC : 16));
    if (warp) fence_async();
    bulk_g2s(sb + (warp ? SP_W : SP_Z) + item * 16384, (warp ? p.s->wt : p.s->x1t) + pr * 1024, 16384, bar);
  };
  if (lane < nrnd && warp == 0) fetch();
  __syncwarp();
  fence_regs(fe); fence_regs(tw);
  mbar_wait(BAR_Y(sb, 6), 0);
  TL(3);
  const uint64_t dT_n = mk_desc(sb + SP_T, 8192, 1024, 1);
#pragma unroll 1
  for (int rnd = 0; rnd < nrnd; rnd++) {
    const int item = wg + 3 * rnd, pr = pair_of(rnd);
    const uint32_t z = sb + SP_Z + item * 16384;
    uint32_t fa[16], fb[16];
    auto load_frag = [&](int off) {
#pragma unroll
      for (int i = 0; i < 4; i++) {
        const uint4 a = *reinterpret_cast<const uint4*>(smem + SP_TW + off + i * 2048 + tid * 16);
        fa[4 * i] = a.x; fa[4 * i + 1] = a.y; fa[4 * i + 2] = a.z; fa[4 * i + 3] = a.w;
      }
      fence_regs(fa);
    };
    load_frag(0);
    {
      const uint32_t live = pr == 0 ? 0xddu : (pr == 112 ? 0x11u : 0xffu);
#pragma unroll 1
      for (uint32_t n = 0; n < 4096; n++) {
        mbar_wait(BAR_FULL(sb, item), n & 1);
        uint32_t bad = 0;
#pragma unroll
        for (int i = 0; i < 8; i++) bad |= ((*reinterpret_cast<const volatile uint32_t*>(smem + SP_Z + item * 16384 + i * 2048 + tid * 16) ^ epoch) & 1) << i;
        uint32_t again;
        asm volatile("{\n.reg .pred p, q;\nsetp.ne.u32 p, %1, 0;\nbarrier.red.or.pred q, %2, 128, p;\nselp.u32 %0, 1, 0, q;\n}"
                     : "=r"(again) : "r"(bad & live), "r"(1 + wg) : "memory");
        if (!again) break;
        TL(20);
        if (tid == 0) { mbar_expect_tx(BAR_FULL(sb, item), 16384); bulk_g2s(z, p.s->x1t + pr * 1024, 16384, BAR_FULL(sb, item)); }
      }
    }
    TL(4 + 8 * rnd);
    if (rnd == 0 && wg > 0) bar_sync(3 + wg, 256);
    float aR[32], aI[32];
    {
      const uint64_t de = mk_desc(z, 4096, 512, 2);
      wg_fence();
#pragma unroll
      for (int kk = 0; kk < 4; kk++) {
        wgmma_rs_n64<1, 1>(aR, fe[4 * kk], fe[4 * kk + 1], fe[4 * kk + 2], fe[4 * kk + 3], de + kk * 64, kk != 0);
        wgmma_rs_n64<1, 1>(aI, fa[4 * kk], fa[4 * kk + 1], fa[4 * kk + 2], fa[4 * kk + 3], de + 512 + kk * 64, kk != 0);
      }
      wg_commit();
      if (rnd == 0 && wg < 2) bar_arrive(4 + wg, 256);
      if (rnd == 0 && lane < nrnd && warp == 1) fetch();
      __syncwarp();
      wg_wait<0>();
      fence_regs(aR); fence_regs(aI);
    }
    TL(5 + 8 * rnd);
#pragma unroll
    for (int v = 0; v < 8; v++) {
      uint32_t* f = (v < 4 ? fa : fb) + 2 * (v & 3);
      const uint32_t* t = tw + 2 * (v & 3);
      const float *e = aR + 4 * v, *o = aI + 4 * v;
      const uint32_t er = pack2(e[0], e[1]), ei = pack2(e[2], e[3]), qr = pack2(o[0], o[1]), qi = pack2(o[2], o[3]);
      const uint32_t u0r = add2(er, qr), u0i = add2(ei, qi), u1r = sub2(er, qr), u1i = sub2(ei, qi);
      f[0] = fma2(u0r, t[0], mul2(u0i, t[8]));
      f[8] = fms2(u0i, t[0], mul2(u0r, t[8]));
      f[1] = fma2(u1r, t[1], mul2(u1i, t[9]));
      f[9] = fms2(u1i, t[1], mul2(u1r, t[9]));
    }
    fence_regs(fa); fence_regs(fb);
    wg_fence();
#pragma unroll
    for (int kk = 0; kk < 4; kk++) {
      wgmma_rs_n64<1, 1>(aR, fa[4 * kk], fa[4 * kk + 1], fa[4 * kk + 2], fa[4 * kk + 3], dT_n + kk * 128, kk != 0);
      wgmma_rs_n64<1, 1>(aI, fb[4 * kk], fb[4 * kk + 1], fb[4 * kk + 2], fb[4 * kk + 3], dT_n + kk * 128, kk != 0);
    }
    wg_commit();
    if (rnd == 1 && tid == 0) {
      asm volatile("cp.async.bulk.wait_group 0;" ::: "memory");
      red_add(&p.s->cnt_y[(max(pr - 57, 0) >> 4) * 32], 1);
    }
    __syncwarp();
    mbar_wait(BAR_Y(sb, item), 0);
    wg_wait<0>();
    fence_regs(aR); fence_regs(aI);
    TL(6 + 8 * rnd);
    {
      const uint8_t* wp = smem + SP_W + item * 16384 + q * 1024 + warp * 128 + (((lane >> 2) ^ (2 * q)) << 4);
#pragma unroll
      for (int jb = 0; jb < 4; jb++) {
#pragma unroll
        for (int h = 0; h < 2; h++) {
          const uint4 w = *reinterpret_cast<const uint4*>(wp + jb * 4096 + h * 512);
          const int i = 4 * jb + 2 * h;
          const uint32_t ar = pack2(aR[i], aR[i + 1]), ai = pack2(aR[16 + i], aR[17 + i]);
          const uint32_t br = pack2(aI[i], aI[i + 1]), bi = pack2(aI[16 + i], aI[17 + i]);
          fa[2 * jb + h] = fms2(ar, w.x, mul2(ai, w.y));
          fa[8 + 2 * jb + h] = fma2(ar, w.y, mul2(ai, w.x));
          fb[2 * jb + h] = fms2(br, w.z, mul2(bi, w.w));
          fb[8 + 2 * jb + h] = fma2(br, w.w, mul2(bi, w.z));
        }
      }
    }
    fence_regs(fa); fence_regs(fb);
    wg_fence();
#pragma unroll
    for (int kk = 0; kk < 4; kk++) {
      wgmma_rs_n64<1, 0>(aR, fa[4 * kk], fa[4 * kk + 1], fa[4 * kk + 2], fa[4 * kk + 3], dT_n + kk * 2, kk != 0);
      wgmma_rs_n64<1, 0>(aI, fb[4 * kk], fb[4 * kk + 1], fb[4 * kk + 2], fb[4 * kk + 3], dT_n + kk * 2, kk != 0);
    }
    wg_commit();
    wg_wait<0>();
    fence_regs(aR); fence_regs(aI);
    TL(7 + 8 * rnd);
#pragma unroll
    for (int v = 0; v < 8; v++) {
      const float* a = (v < 4 ? aR : aI) + 4 * (v & 3);
      const uint32_t* t = tw + 2 * (v & 3);
      const uint32_t u0r = pack2(a[0], a[1]), u1r = pack2(a[2], a[3]), u0i = pack2(a[16], a[17]), u1i = pack2(a[18], a[19]);
      const uint32_t t0r = fms2(u0r, t[0], mul2(u0i, t[8])), t0i = fma2(u0i, t[0], mul2(u0r, t[8]));
      const uint32_t t1r = fms2(u1r, t[1], mul2(u1i, t[9])), t1i = fma2(u1i, t[1], mul2(u1r, t[9]));
      fa[v] = add2(t0i, t1i); fa[8 + v] = add2(t0r, t1r);
      fb[v] = sub2(t0i, t1i); fb[8 + v] = sub2(t0r, t1r);
    }
    bar_sync(1 + wg, 128);
#pragma unroll
    for (int u = 0; u < 4; u++) {
      const uint32_t a = z + (32 * (u >> 1) + 8 * warp + (lane & 7)) * 128 + (((4 * (u & 1) + (lane >> 3)) ^ (lane & 7)) << 4);
      stmatrix_x4(a, fa[4 * u], fa[4 * u + 1], fa[4 * u + 2], fa[4 * u + 3]);
      stmatrix_x4(a + 8192, fb[4 * u], fb[4 * u + 1], fb[4 * u + 2], fb[4 * u + 3]);
    }
    load_frag(8192);
    fence_async_smem();
    bar_sync(1 + wg, 128);
    TL(8 + 8 * rnd);
    {
      const uint64_t de = mk_desc(z, 8192, 1024, 1);
      wg_fence();
#pragma unroll
      for (int kk = 0; kk < 4; kk++) {
        wgmma_rs_n64<1, 1>(aR, fe[4 * kk], fe[4 * kk + 1], fe[4 * kk + 2], fe[4 * kk + 3], de + kk * 128, kk != 0);
        wgmma_rs_n64<1, 1>(aI, fa[4 * kk], fa[4 * kk + 1], fa[4 * kk + 2], fa[4 * kk + 3], de + 512 + kk * 128, kk != 0);
      }
      wg_commit();
      wg_wait<0>();
      fence_regs(aR); fence_regs(aI);
    }
    TL(9 + 8 * rnd);
    const bool edge = pr == 0 || pr == 112;
    if (edge) {
#pragma unroll
      for (int i = 0; i < 16; i++) { aR[i] *= 0.5f; aI[i] *= 0.5f; }
    }
#pragma unroll
    for (int i = 0; i < 8; i++) {
      const float* a = ((i & 1) ? aI : aR) + 16 * (i >> 2) + 2 - (i & 2);
      *reinterpret_cast<uint4*>(smem + SP_W + item * 16384 + (i >> 1) * 4096 + (i & 1) * 64 + (tid >> 2) * 128 + q * 16) =
          make_uint4(pack2(a[0], a[1]), pack2(a[4], a[5]), pack2(a[8], a[9]), pack2(a[12], a[13]));
    }
    fence_async_smem();
    bar_sync(1 + wg, 128);
    if (tid == 0) {
      const uint32_t src = sb + SP_W + item * 16384;
      __nv_bfloat16* dst = p.s->yt + (size_t)(pr < 112 ? 4 * pr : 1) * S_;
      bulk_s2g(dst, src, edge ? 4096 : 16384);
      if (pr == 0) bulk_s2g(dst + 2 * S_, src + 8192, 8192);
      asm volatile("cp.async.bulk.commit_group;" ::: "memory");
      if (rnd == nrnd - 1) {
        asm volatile("cp.async.bulk.wait_group 0;" ::: "memory");
        TL(11);
        red_add(&p.s->cnt_y[(pr < 112 ? pr >> 4 : 0) * 32], 1);
      }
    }
    __syncwarp();
    TL(10 + 8 * rnd);
  }
  if (lane == 0) *my_epoch = epoch;
}

__global__ void __cluster_dims__(2, 1, 1) __launch_bounds__(384, 1)
fused_kernel(const __grid_constant__ Params p) {
  extern __shared__ __align__(1024) uint8_t smem[];
  const uint32_t sb = smem_u32(smem);
  TL(0);
  const uint32_t rank = blockIdx.x & 1;
  const int hc = blockIdx.x >> 1;
  int grp, jj;
  if (hc < 4) { grp = 8; jj = hc; }
  else if (hc < 36) { grp = (hc - 4) & 7; jj = (hc - 4) >> 3; }
  else if (hc < 57) { jj = (hc - 36) / 7; grp = 1 + (hc - 36) - 7 * jj; jj += 4; }
  else if (hc < 60) { grp = 0; jj = hc - 53; }
  else { grp = 8; jj = hc - 56; }
  const int mt = 2 * grp + rank, bid = 2 * (7 * grp + jj) + rank;
  if (bid < NFFN) {
    const int t = threadIdx.x;
    if (t < 19 && 19 * jj + t < 128) asm volatile("prefetch.global.L2 [%0];" ::"l"(p.px + (128 * mt + 19 * jj + t) * D_));
    if (t >= 128 && t < 136) asm volatile("prefetch.global.L2 [%0];" ::"l"((rank ? p.pwu : p.pwg) + (4 * grp + (t & 3)) * F_ + 256 * jj + 16 * (t & 4)));
  }
  if (threadIdx.x == 256) {
#pragma unroll
    for (int i = 0; i < NSTAGE; i++) { mbar_init(BAR_FULL(sb, i), 1); mbar_init(BAR_EMPTY(sb, i), 4); }
    asm volatile("fence.mbarrier_init.release.cluster;" ::: "memory");
  } else if (threadIdx.x == 320) {
    mbar_init(BAR_X(sb, 0), 1);
    if (bid < NFFN) {
      mbar_expect_tx(BAR_X(sb, 0), 16384);
      tma2d(sb + SM_X, &p.x, 0, 128 * mt, BAR_X(sb, 0));
    }
#pragma unroll
    for (int i = 1; i < NSTAGE; i++) mbar_init(BAR_X(sb, i), 1);
    mbar_init(BAR_XFREE(sb), 2);
    asm volatile("fence.mbarrier_init.release.cluster;" ::: "memory");
  } else if (threadIdx.x == 352) {
#pragma unroll
    for (int i = 0; i < NSTAGE; i++) { mbar_init(BAR_Y(sb, i), 1); mbar_init(BAR_E2(sb, i), 2); }
    asm volatile("fence.mbarrier_init.release.cluster;" ::: "memory");
  } else if (threadIdx.x == 288 && bid < NFFN) {
    prefetch_tmap(rank ? &p.wu : &p.wg); prefetch_tmap(&p.ct);
  }
  __syncwarp();
  asm volatile("barrier.cluster.arrive.relaxed.aligned;" ::: "memory");
  const int wg = __shfl_sync(0xffffffffu, threadIdx.x >> 7, 0);
  if (bid >= NFFN) {
    spectral_cta(sb, smem, p, bid - NFFN, wg);
  } else if (wg < 2) {
    asm volatile("setmaxnreg.inc.sync.aligned.u32 232;");
    asm volatile("barrier.cluster.wait.acquire.aligned;" ::: "memory");
    TL(1);
    ffn_consumer(sb, smem, p, bid, wg, threadIdx.x & 127, mt, jj);
  } else {
    asm volatile("setmaxnreg.dec.sync.aligned.u32 40;");
    asm volatile("barrier.cluster.wait.acquire.aligned;" ::: "memory");
    TL(1);
    if (threadIdx.x == 320) {
      constexpr int order[13] = {XORDER};
#pragma unroll
      for (int i = 0; i < 13; i++) {
        if (order[i] < 8) {
          ring_issue(sb, p, order[i], order[i], false, 0, jj, rank);
        } else {
          const int kb = order[i] - 10;
          mbar_expect_tx(BAR_X(sb, kb), 16384);
          tma2d(sb + SM_X + kb * 16384, &p.x, 64 * kb, 128 * mt, BAR_X(sb, kb));
        }
      }
      TL(2);
    }
    __syncwarp();
    ffn_producer(sb, smem, bid, p, (threadIdx.x >> 5) & 3, threadIdx.x & 31, mt, jj, rank);
  }
}

typedef CUresult (*EncodeFn)(CUtensorMap*, CUtensorMapDataType, cuuint32_t, void*, const cuuint64_t*, const cuuint64_t*,
                             const cuuint32_t*, const cuuint32_t*, CUtensorMapInterleave, CUtensorMapSwizzle,
                             CUtensorMapL2promotion, CUtensorMapFloatOOBfill);

void make_map(EncodeFn fn, CUtensorMap* m, const void* base, int rank, const cuuint64_t* dims, const cuuint64_t* strides,
              const cuuint32_t* box, CUtensorMapSwizzle sw) {
  const cuuint32_t es[4] = {1, 1, 1, 1};
  fn(m, CU_TENSOR_MAP_DATA_TYPE_BFLOAT16, rank, const_cast<void*>(base), dims, strides, box, es,
     CU_TENSOR_MAP_INTERLEAVE_NONE, sw, CU_TENSOR_MAP_L2_PROMOTION_L2_256B, CU_TENSOR_MAP_FLOAT_OOB_FILL_NONE);
}

}

extern "C" void kernel_launch(void* const* d_in, const int* in_sizes, int n_in, void* d_out, int out_size) {
  const __nv_bfloat16* x = (const __nv_bfloat16*)d_in[0];
  const __nv_bfloat16* w_r = (const __nv_bfloat16*)d_in[1];
  const __nv_bfloat16* w_i = (const __nv_bfloat16*)d_in[2];
  const __nv_bfloat16* wg = (const __nv_bfloat16*)d_in[4];
  const __nv_bfloat16* wu = (const __nv_bfloat16*)d_in[5];
  const __nv_bfloat16* wd = (const __nv_bfloat16*)d_in[6];
  const __nv_bfloat16* gate_w = (const __nv_bfloat16*)d_in[7];

  void* fnp = nullptr;
  cudaDriverEntryPointQueryResult qr;
  cudaGetDriverEntryPoint("cuTensorMapEncodeTiled", &fnp, cudaEnableDefault, &qr);
  EncodeFn fn = (EncodeFn)fnp;
  void *ctab, *spec, *scr;
  cudaGetSymbolAddress(&ctab, g_ctab);
  cudaGetSymbolAddress(&spec, g_spec);
  cudaGetSymbolAddress(&scr, g_scratch);
  const void* yt = (const char*)scr + offsetof(Scratch, yt);
  Params p;
  p.s = (Scratch*)scr; p.out = (__nv_bfloat16*)d_out;
  p.px = x; p.w_r = w_r; p.w_i = w_i; p.gate_w = gate_w; p.pwg = wg; p.pwu = wu; p.pwd = wd;
  p.ctab = (const tab::Table*)ctab; p.spec = (const tab::Spec*)spec;
  {
    const cuuint64_t d[2] = {D_, S_}, s[1] = {D_ * 2};
    const cuuint32_t b[2] = {64, 128};
    make_map(fn, &p.x, x, 2, d, s, b, CU_TENSOR_MAP_SWIZZLE_128B);
  }
  {
    const cuuint64_t d[3] = {64, D_, F_ / 64}, s[2] = {F_ * 2, 128};
    const cuuint32_t b[3] = {64, 32, 2};
    make_map(fn, &p.wg, wg, 3, d, s, b, CU_TENSOR_MAP_SWIZZLE_128B);
    make_map(fn, &p.wu, wu, 3, d, s, b, CU_TENSOR_MAP_SWIZZLE_128B);
  }
  {
    const cuuint64_t d[2] = {D_, F_}, s[1] = {D_ * 2};
    const cuuint32_t b[2] = {64, 64};
    make_map(fn, &p.wd, wd, 2, d, s, b, CU_TENSOR_MAP_SWIZZLE_128B);
  }
  {
    const cuuint64_t d[2] = {D_, D_}, s[1] = {D_ * 2};
    const cuuint32_t b[2] = {64, 64};
    make_map(fn, &p.ct, ctab, 2, d, s, b, CU_TENSOR_MAP_SWIZZLE_128B);
  }
  {
    const cuuint64_t d[3] = {64, D_, S_ / 64}, s[2] = {S_ * 2, 128};
    const cuuint32_t b[3] = {64, 64, 2};
    make_map(fn, &p.yt, yt, 3, d, s, b, CU_TENSOR_MAP_SWIZZLE_128B);
  }
  cudaFuncSetAttribute(fused_kernel, cudaFuncAttributeMaxDynamicSharedMemorySize, SM_TOTAL);
  fused_kernel<<<NCTA, 384, SM_TOTAL, cudaStreamPerThread>>>(p);
}
```
